```python
import torch

def _softmax(x, axis=-1):
    return torch.softmax(x, dim=axis)
def _gelu(x):
    return torch.nn.functional.gelu(x, approximate="tanh")
def _silu(x):
    return torch.nn.functional.silu(x)
def _sigmoid(x):
    return torch.sigmoid(x)
def _layernorm(x, axis=-1, eps=1e-5):
    m = x.mean(dim=axis, keepdim=True)
    v = x.var(dim=axis, keepdim=True, unbiased=False)
    return (x - m) / torch.sqrt(v + eps)
def _scatter_add(tgt, idx, src, axis=0):
    return tgt.clone().index_add_(axis, idx, src)
def _segment_sum(src, seg, n):
    out = torch.zeros((n,) + src.shape[1:], dtype=src.dtype)
    return out.index_add_(0, seg, src)
def _pad(x, pw):
    flat = tuple(v for pair in reversed(pw) for v in pair)
    return torch.nn.functional.pad(x, flat)

kernel_name = 'recurrent_scan__linear_attn_block__glu_gated_swiglu__prompt'

def setup_inputs():

    _w = (lambda a: (lambda t: t.to(torch.bfloat16) if t.is_floating_point() else t)(torch.as_tensor(a)))
    def _A_setup():
        B, S, D = 1, 2048, 448
        return {
            "x": _w((lambda *s: torch.randn(*s, dtype=torch.bfloat16) * 0.05)(B, S, D)),
            "wqkv": _w((lambda *s: torch.randn(*s, dtype=torch.bfloat16) * 0.8)(D, 3 * D)),
            "wo": _w((lambda *s: torch.randn(*s, dtype=torch.bfloat16) * 0.8)(D, D)),
        }
    _A_in = _A_setup()

    def _B_setup():
        B, S, D, F = 1, 2048, 448, 1792
        return {
            "x": _w((lambda *s: torch.randn(*s, dtype=torch.bfloat16) * 0.05)(B, S, D)),
            "w1": _w((lambda *s: torch.randn(*s, dtype=torch.bfloat16) * 0.2)(D, F) * (2.0 / D) ** 0.5),
            "w3": _w((lambda *s: torch.randn(*s, dtype=torch.bfloat16) * 0.2)(D, F) * (2.0 / D) ** 0.5),
            "w2": _w((lambda *s: torch.randn(*s, dtype=torch.bfloat16) * 0.2)(F, D) * (2.0 / F) ** 0.5),
        }
    _B_in = _B_setup()

    return {
        "A_x": _A_in["x"],
        "A_wqkv": _A_in["wqkv"],
        "A_wo": _A_in["wo"],
        "B_x": _B_in["x"],
        "B_w1": _B_in["w1"],
        "B_w3": _B_in["w3"],
        "B_w2": _B_in["w2"],
    }

def reference(A_x, A_wqkv, A_wo, B_x, B_w1, B_w3, B_w2):
    def _A_ref(x, wqkv, wo):
        B, S, D = x.shape
        H = 16; Dh = D // H
        qkv = (lambda x, *d: x.permute(*d))((x @ wqkv).reshape(B, S, 3, H, Dh), 2, 0, 3, 1, 4)
        q, k, v = qkv[0], qkv[1], qkv[2]
        phi = lambda t: torch.where(t > 0, t + 1, torch.exp(t)) + 1e-6
        pq, pk = phi(q), phi(k)
        kv = torch.einsum("bhsd,bhse->bhde", pk, v)
        z = torch.einsum("bhsd->bhd", pk)
        num = torch.einsum("bhqd,bhde->bhqe", pq, kv)
        den = torch.einsum("bhqd,bhd->bhq", pq, z)[..., None] + 1e-6
        o = num / den
        return (lambda x, *d: x.permute(*d))(o, 0, 2, 1, 3).reshape(B, S, D) @ wo

    def _B_ref(x, w1, w3, w2):
        gate = torch.einsum("bsd,df->bsf", x, w1)
        up = torch.einsum("bsd,df->bsf", x, w3)
        h = _silu(gate) * up
        out = torch.einsum("bsf,fd->bsd", h, w2)
        return out

    x = A_x
    xn = _layernorm(x, axis=-1)
    s = _A_ref(xn, A_wqkv, A_wo)
    g = _silu(_B_ref(xn, B_w1, B_w3, B_w2))
    return x + s * g
```

```cpp
#include <cuda_runtime.h>
#include <cuda.h>
#include <cuda_bf16.h>
#include <stdint.h>

namespace {

constexpr int SEQ = 2048, DM = 448, FF = 1792;
constexpr uint32_t U = 8192;
constexpr uint32_t SM_BASE = 1024;
constexpr uint32_t MISC = 28 * U;
constexpr uint32_t SMEM_BYTES = 28 * U + 3072;
constexpr uint32_t VA = 21 * U, VB = 24 * U + 4096, VC = 14 * U, VD = 17 * U + 4096;
constexpr uint32_t KVM_U = 26;

enum : int { XF = 0, FA = 14, FB = 21, FC = 28, FD = 35, FG = 42, FO = 50, FW = 57, HF = 59,
             EA = 65, EB = 72, EC = 79, ED = 86, EG = 93, XCONS = 101, PKST = 102, LD1 = 103, LD2 = 104, OST = 105,
             PF = 106, ACK = 109,
             KVDONE = 110, KVRED = 111,
             KVM = 112,
             NBAR = 113 };

struct Maps { CUtensorMap x, wqkv, w1a, w3a, w1b, w3b, w2a, w2b, w2c, wo, o, out; };

__device__ uint32_t g_epoch[128];
__device__ uint32_t g_f1[8 * 32];
__device__ uint32_t g_f2[16 * 32];
__device__ float g_kv[2 * 8 * 4096];
__device__ __nv_bfloat16 g_o[SEQ * DM];
__device__ uint4 g_p[16 * 2 * 4 * 3 * 2 * 512];
#define TS(role, i)
#define GTS(role, i)
#define CTS(i)
#define TSDUMP(role)

__device__ __forceinline__ uint32_t smem_u32(const void* p) { return (uint32_t)__cvta_generic_to_shared(p); }
__device__ __forceinline__ void mbar_init(uint32_t bar, uint32_t cnt) { asm volatile("mbarrier.init.shared::cta.b64 [%0], %1;" ::"r"(bar), "r"(cnt) : "memory"); }
__device__ __forceinline__ void mbar_expect_tx(uint32_t bar, uint32_t bytes) { asm volatile("mbarrier.arrive.expect_tx.shared::cta.b64 _, [%0], %1;" ::"r"(bar), "r"(bytes) : "memory"); }
__device__ __forceinline__ void mbar_arrive(uint32_t bar) { asm volatile("mbarrier.arrive.shared::cta.b64 _, [%0];" ::"r"(bar) : "memory"); }
__device__ __forceinline__ void mbar_arrive_remote(uint32_t rbar) { asm volatile("mbarrier.arrive.shared::cluster.b64 _, [%0];" ::"r"(rbar) : "memory"); }
__device__ __forceinline__ void mbar_wait(uint32_t bar) {
  asm volatile("{ .reg .pred p; .reg .u32 n; mov.u32 n, 0;\n"
               "W_L: mbarrier.try_wait.parity.shared::cta.b64 p, [%0], 0;\n"
               "@p bra W_D;\n add.u32 n, n, 1;\n setp.lt.u32 p, n, 4194304;\n @p bra W_L;\n trap;\n W_D: }" ::"r"(bar) : "memory");
}
__device__ __forceinline__ void mbar_wait_cl(uint32_t bar) {
  asm volatile("{ .reg .pred p; .reg .u32 n; mov.u32 n, 0;\n"
               "W_L: mbarrier.try_wait.parity.shared::cta.b64 p, [%0], 0;\n"
               "@p bra W_D;\n add.u32 n, n, 1;\n setp.lt.u32 p, n, 4194304;\n @p bra W_L;\n trap;\n W_D: }" ::"r"(bar) : "memory");
}
__device__ __forceinline__ void tma2d(uint32_t dst, const CUtensorMap* m, int c0, int c1, uint32_t bar) {
  asm volatile("cp.async.bulk.tensor.2d.shared::cluster.global.mbarrier::complete_tx::bytes [%0], [%1, {%3, %4}], [%2];" ::"r"(dst), "l"(m), "r"(bar), "r"(c0), "r"(c1) : "memory");
}
__device__ __forceinline__ void tma2d_store(const CUtensorMap* m, int c0, int c1, uint32_t src) {
  asm volatile("cp.async.bulk.tensor.2d.global.shared::cta.bulk_group [%0, {%2, %3}], [%1];" ::"l"(m), "r"(src), "r"(c0), "r"(c1) : "memory");
}
__device__ __forceinline__ void bulk_s2c(uint32_t rdst, uint32_t src, uint32_t bytes, uint32_t rbar) {
  asm volatile("cp.async.bulk.shared::cluster.shared::cta.mbarrier::complete_tx::bytes [%0], [%1], %2, [%3];" ::"r"(rdst), "r"(src), "r"(bytes), "r"(rbar) : "memory");
}
__device__ __forceinline__ uint32_t mapa(uint32_t a, uint32_t cta) { uint32_t r; asm volatile("mapa.shared::cluster.u32 %0, %1, %2;" : "=r"(r) : "r"(a), "r"(cta)); return r; }
__device__ __forceinline__ bool elect_one() { uint32_t p; asm volatile("{ .reg .pred P; elect.sync _|P, 0xffffffff; selp.u32 %0, 1, 0, P; }" : "=r"(p)); return p; }
__device__ __forceinline__ int laneid() { int l; asm volatile("mov.u32 %0, %%laneid;" : "=r"(l)); return l; }
__device__ __forceinline__ void fence_async() { asm volatile("fence.proxy.async.shared::cta;" ::: "memory"); }
__device__ __forceinline__ void wg_fence() { asm volatile("wgmma.fence.sync.aligned;" ::: "memory"); }
__device__ __forceinline__ void wg_commit() { asm volatile("wgmma.commit_group.sync.aligned;" ::: "memory"); }
template <int N> __device__ __forceinline__ void wg_wait() { asm volatile("wgmma.wait_group.sync.aligned %0;" ::"n"(N) : "memory"); }
template <int N> __device__ __forceinline__ void pin(float* a) {
#pragma unroll
  for (int i = 0; i < N; i++) asm volatile("" : "+f"(a[i])::"memory");
}
template <int N> __device__ __forceinline__ void pinr(uint32_t* a) {
#pragma unroll
  for (int i = 0; i < N; i++) asm volatile("" : "+r"(a[i])::"memory");
}
__device__ __forceinline__ void ldsm4(uint32_t* r, uint32_t a) { asm volatile("ldmatrix.sync.aligned.m8n8.x4.shared.b16 {%0,%1,%2,%3}, [%4];" : "=r"(r[0]), "=r"(r[1]), "=r"(r[2]), "=r"(r[3]) : "r"(a) : "memory"); }
__device__ __forceinline__ void stsm4(uint32_t a, uint32_t r0, uint32_t r1, uint32_t r2, uint32_t r3) { asm volatile("stmatrix.sync.aligned.m8n8.x4.shared.b16 [%0], {%1,%2,%3,%4};" ::"r"(a), "r"(r0), "r"(r1), "r"(r2), "r"(r3) : "memory"); }
__device__ __forceinline__ void stsm2(uint32_t a, uint32_t r0, uint32_t r1) { asm volatile("stmatrix.sync.aligned.m8n8.x2.shared.b16 [%0], {%1,%2};" ::"r"(a), "r"(r0), "r"(r1) : "memory"); }
__device__ __forceinline__ void sts4(uint32_t a, const uint32_t* r) { asm volatile("st.shared.v4.b32 [%0], {%1,%2,%3,%4};" ::"r"(a), "r"(r[0]), "r"(r[1]), "r"(r[2]), "r"(r[3]) : "memory"); }
__device__ __forceinline__ void lds4(uint32_t* r, uint32_t a) { asm volatile("ld.shared.v4.b32 {%0,%1,%2,%3}, [%4];" : "=r"(r[0]), "=r"(r[1]), "=r"(r[2]), "=r"(r[3]) : "r"(a) : "memory"); }
__device__ __forceinline__ uint32_t pack2(float lo, float hi) { uint32_t r; asm("cvt.rn.bf16x2.f32 %0, %1, %2;" : "=r"(r) : "f"(hi), "f"(lo)); return r; }
__device__ __forceinline__ float blo(uint32_t v) { return __uint_as_float(v << 16); }
__device__ __forceinline__ float bhi(uint32_t v) { return __uint_as_float(v & 0xFFFF0000u); }
__device__ __forceinline__ float ex2(float x) { float y; asm("ex2.approx.ftz.f32 %0, %1;" : "=f"(y) : "f"(x)); return y; }
__device__ __forceinline__ float rcp(float x) { float y; asm("rcp.approx.ftz.f32 %0, %1;" : "=f"(y) : "f"(x)); return y; }
__device__ __forceinline__ float bfr(float x) { return __bfloat162float(__float2bfloat16_rn(x)); }
__device__ __forceinline__ uint32_t ld_acq(const uint32_t* p) { uint32_t v; asm volatile("ld.acquire.gpu.global.u32 %0, [%1];" : "=r"(v) : "l"(p) : "memory"); return v; }
__device__ __forceinline__ void poll_flag(const uint32_t* p, uint32_t target) {
  uint32_t n = 0;
  while ((int)(ld_acq(p) - target) < 0) { if (++n > (1u << 21)) asm volatile("trap;"); }
}
__device__ __forceinline__ void st_ll(uint4* p, uint32_t a, uint32_t b, uint32_t c, uint32_t d) {
  asm volatile("{ .reg .b128 t; .reg .b64 lo, hi; mov.b64 lo, {%1,%2}; mov.b64 hi, {%3,%4}; mov.b128 t, {lo,hi}; st.relaxed.gpu.global.b128 [%0], t; }" ::"l"(p), "r"(a), "r"(b), "r"(c), "r"(d) : "memory");
}
__device__ __forceinline__ void ld_ll(uint32_t* r, const uint4* p) {
  asm volatile("{ .reg .b128 t; .reg .b64 lo, hi; ld.relaxed.gpu.global.b128 t, [%4]; mov.b128 {lo,hi}, t; mov.b64 {%0,%1}, lo; mov.b64 {%2,%3}, hi; }" : "=r"(r[0]), "=r"(r[1]), "=r"(r[2]), "=r"(r[3]) : "l"(p) : "memory");
}
__device__ __forceinline__ constexpr uint64_t desc(uint32_t off, uint32_t lbo) {
  return (uint64_t)((SM_BASE + off) >> 4) | ((uint64_t)(lbo >> 4) << 16) | ((uint64_t)64 << 32) | ((uint64_t)1 << 62);
}

__device__ __forceinline__ void rs120_0(float* d, const uint32_t* a, uint64_t db){
  asm volatile("{ .reg .pred p; setp.ne.b32 p, 0, 0; wgmma.mma_async.sync.aligned.m64n120k16.f32.bf16.bf16 {%0, %1, %2, %3, %4, %5, %6, %7, %8, %9, %10, %11, %12, %13, %14, %15, %16, %17, %18, %19, %20, %21, %22, %23, %24, %25, %26, %27, %28, %29, %30, %31, %32, %33, %34, %35, %36, %37, %38, %39, %40, %41, %42, %43, %44, %45, %46, %47, %48, %49, %50, %51, %52, %53, %54, %55, %56, %57, %58, %59}, {%60,%61,%62,%63}, %64, p, 1, 1, 1; }"
   : "=f"(d[0]), "=f"(d[1]), "=f"(d[2]), "=f"(d[3]), "=f"(d[4]), "=f"(d[5]), "=f"(d[6]), "=f"(d[7]), "=f"(d[8]), "=f"(d[9]), "=f"(d[10]), "=f"(d[11]), "=f"(d[12]), "=f"(d[13]), "=f"(d[14]), "=f"(d[15]), "=f"(d[16]), "=f"(d[17]), "=f"(d[18]), "=f"(d[19]), "=f"(d[20]), "=f"(d[21]), "=f"(d[22]), "=f"(d[23]), "=f"(d[24]), "=f"(d[25]), "=f"(d[26]), "=f"(d[27]), "=f"(d[28]), "=f"(d[29]), "=f"(d[30]), "=f"(d[31]), "=f"(d[32]), "=f"(d[33]), "=f"(d[34]), "=f"(d[35]), "=f"(d[36]), "=f"(d[37]), "=f"(d[38]), "=f"(d[39]), "=f"(d[40]), "=f"(d[41]), "=f"(d[42]), "=f"(d[43]), "=f"(d[44]), "=f"(d[45]), "=f"(d[46]), "=f"(d[47]), "=f"(d[48]), "=f"(d[49]), "=f"(d[50]), "=f"(d[51]), "=f"(d[52]), "=f"(d[53]), "=f"(d[54]), "=f"(d[55]), "=f"(d[56]), "=f"(d[57]), "=f"(d[58]), "=f"(d[59]) : "r"(a[0]),"r"(a[1]),"r"(a[2]),"r"(a[3]), "l"(db));
}
__device__ __forceinline__ void rs120_1(float* d, const uint32_t* a, uint64_t db){
  asm volatile("{ .reg .pred p; setp.ne.b32 p, 1, 0; wgmma.mma_async.sync.aligned.m64n120k16.f32.bf16.bf16 {%0, %1, %2, %3, %4, %5, %6, %7, %8, %9, %10, %11, %12, %13, %14, %15, %16, %17, %18, %19, %20, %21, %22, %23, %24, %25, %26, %27, %28, %29, %30, %31, %32, %33, %34, %35, %36, %37, %38, %39, %40, %41, %42, %43, %44, %45, %46, %47, %48, %49, %50, %51, %52, %53, %54, %55, %56, %57, %58, %59}, {%60,%61,%62,%63}, %64, p, 1, 1, 1; }"
   : "+f"(d[0]), "+f"(d[1]), "+f"(d[2]), "+f"(d[3]), "+f"(d[4]), "+f"(d[5]), "+f"(d[6]), "+f"(d[7]), "+f"(d[8]), "+f"(d[9]), "+f"(d[10]), "+f"(d[11]), "+f"(d[12]), "+f"(d[13]), "+f"(d[14]), "+f"(d[15]), "+f"(d[16]), "+f"(d[17]), "+f"(d[18]), "+f"(d[19]), "+f"(d[20]), "+f"(d[21]), "+f"(d[22]), "+f"(d[23]), "+f"(d[24]), "+f"(d[25]), "+f"(d[26]), "+f"(d[27]), "+f"(d[28]), "+f"(d[29]), "+f"(d[30]), "+f"(d[31]), "+f"(d[32]), "+f"(d[33]), "+f"(d[34]), "+f"(d[35]), "+f"(d[36]), "+f"(d[37]), "+f"(d[38]), "+f"(d[39]), "+f"(d[40]), "+f"(d[41]), "+f"(d[42]), "+f"(d[43]), "+f"(d[44]), "+f"(d[45]), "+f"(d[46]), "+f"(d[47]), "+f"(d[48]), "+f"(d[49]), "+f"(d[50]), "+f"(d[51]), "+f"(d[52]), "+f"(d[53]), "+f"(d[54]), "+f"(d[55]), "+f"(d[56]), "+f"(d[57]), "+f"(d[58]), "+f"(d[59]) : "r"(a[0]),"r"(a[1]),"r"(a[2]),"r"(a[3]), "l"(db));
}
__device__ __forceinline__ void rs184_0(float* d, const uint32_t* a, uint64_t db){
  asm volatile("{ .reg .pred p; setp.ne.b32 p, 0, 0; wgmma.mma_async.sync.aligned.m64n184k16.f32.bf16.bf16 {%0, %1, %2, %3, %4, %5, %6, %7, %8, %9, %10, %11, %12, %13, %14, %15, %16, %17, %18, %19, %20, %21, %22, %23, %24, %25, %26, %27, %28, %29, %30, %31, %32, %33, %34, %35, %36, %37, %38, %39, %40, %41, %42, %43, %44, %45, %46, %47, %48, %49, %50, %51, %52, %53, %54, %55, %56, %57, %58, %59, %60, %61, %62, %63, %64, %65, %66, %67, %68, %69, %70, %71, %72, %73, %74, %75, %76, %77, %78, %79, %80, %81, %82, %83, %84, %85, %86, %87, %88, %89, %90, %91}, {%92,%93,%94,%95}, %96, p, 1, 1, 1; }"
   : "=f"(d[0]), "=f"(d[1]), "=f"(d[2]), "=f"(d[3]), "=f"(d[4]), "=f"(d[5]), "=f"(d[6]), "=f"(d[7]), "=f"(d[8]), "=f"(d[9]), "=f"(d[10]), "=f"(d[11]), "=f"(d[12]), "=f"(d[13]), "=f"(d[14]), "=f"(d[15]), "=f"(d[16]), "=f"(d[17]), "=f"(d[18]), "=f"(d[19]), "=f"(d[20]), "=f"(d[21]), "=f"(d[22]), "=f"(d[23]), "=f"(d[24]), "=f"(d[25]), "=f"(d[26]), "=f"(d[27]), "=f"(d[28]), "=f"(d[29]), "=f"(d[30]), "=f"(d[31]), "=f"(d[32]), "=f"(d[33]), "=f"(d[34]), "=f"(d[35]), "=f"(d[36]), "=f"(d[37]), "=f"(d[38]), "=f"(d[39]), "=f"(d[40]), "=f"(d[41]), "=f"(d[42]), "=f"(d[43]), "=f"(d[44]), "=f"(d[45]), "=f"(d[46]), "=f"(d[47]), "=f"(d[48]), "=f"(d[49]), "=f"(d[50]), "=f"(d[51]), "=f"(d[52]), "=f"(d[53]), "=f"(d[54]), "=f"(d[55]), "=f"(d[56]), "=f"(d[57]), "=f"(d[58]), "=f"(d[59]), "=f"(d[60]), "=f"(d[61]), "=f"(d[62]), "=f"(d[63]), "=f"(d[64]), "=f"(d[65]), "=f"(d[66]), "=f"(d[67]), "=f"(d[68]), "=f"(d[69]), "=f"(d[70]), "=f"(d[71]), "=f"(d[72]), "=f"(d[73]), "=f"(d[74]), "=f"(d[75]), "=f"(d[76]), "=f"(d[77]), "=f"(d[78]), "=f"(d[79]), "=f"(d[80]), "=f"(d[81]), "=f"(d[82]), "=f"(d[83]), "=f"(d[84]), "=f"(d[85]), "=f"(d[86]), "=f"(d[87]), "=f"(d[88]), "=f"(d[89]), "=f"(d[90]), "=f"(d[91]) : "r"(a[0]),"r"(a[1]),"r"(a[2]),"r"(a[3]), "l"(db));
}
__device__ __forceinline__ void rs184_1(float* d, const uint32_t* a, uint64_t db){
  asm volatile("{ .reg .pred p; setp.ne.b32 p, 1, 0; wgmma.mma_async.sync.aligned.m64n184k16.f32.bf16.bf16 {%0, %1, %2, %3, %4, %5, %6, %7, %8, %9, %10, %11, %12, %13, %14, %15, %16, %17, %18, %19, %20, %21, %22, %23, %24, %25, %26, %27, %28, %29, %30, %31, %32, %33, %34, %35, %36, %37, %38, %39, %40, %41, %42, %43, %44, %45, %46, %47, %48, %49, %50, %51, %52, %53, %54, %55, %56, %57, %58, %59, %60, %61, %62, %63, %64, %65, %66, %67, %68, %69, %70, %71, %72, %73, %74, %75, %76, %77, %78, %79, %80, %81, %82, %83, %84, %85, %86, %87, %88, %89, %90, %91}, {%92,%93,%94,%95}, %96, p, 1, 1, 1; }"
   : "+f"(d[0]), "+f"(d[1]), "+f"(d[2]), "+f"(d[3]), "+f"(d[4]), "+f"(d[5]), "+f"(d[6]), "+f"(d[7]), "+f"(d[8]), "+f"(d[9]), "+f"(d[10]), "+f"(d[11]), "+f"(d[12]), "+f"(d[13]), "+f"(d[14]), "+f"(d[15]), "+f"(d[16]), "+f"(d[17]), "+f"(d[18]), "+f"(d[19]), "+f"(d[20]), "+f"(d[21]), "+f"(d[22]), "+f"(d[23]), "+f"(d[24]), "+f"(d[25]), "+f"(d[26]), "+f"(d[27]), "+f"(d[28]), "+f"(d[29]), "+f"(d[30]), "+f"(d[31]), "+f"(d[32]), "+f"(d[33]), "+f"(d[34]), "+f"(d[35]), "+f"(d[36]), "+f"(d[37]), "+f"(d[38]), "+f"(d[39]), "+f"(d[40]), "+f"(d[41]), "+f"(d[42]), "+f"(d[43]), "+f"(d[44]), "+f"(d[45]), "+f"(d[46]), "+f"(d[47]), "+f"(d[48]), "+f"(d[49]), "+f"(d[50]), "+f"(d[51]), "+f"(d[52]), "+f"(d[53]), "+f"(d[54]), "+f"(d[55]), "+f"(d[56]), "+f"(d[57]), "+f"(d[58]), "+f"(d[59]), "+f"(d[60]), "+f"(d[61]), "+f"(d[62]), "+f"(d[63]), "+f"(d[64]), "+f"(d[65]), "+f"(d[66]), "+f"(d[67]), "+f"(d[68]), "+f"(d[69]), "+f"(d[70]), "+f"(d[71]), "+f"(d[72]), "+f"(d[73]), "+f"(d[74]), "+f"(d[75]), "+f"(d[76]), "+f"(d[77]), "+f"(d[78]), "+f"(d[79]), "+f"(d[80]), "+f"(d[81]), "+f"(d[82]), "+f"(d[83]), "+f"(d[84]), "+f"(d[85]), "+f"(d[86]), "+f"(d[87]), "+f"(d[88]), "+f"(d[89]), "+f"(d[90]), "+f"(d[91]) : "r"(a[0]),"r"(a[1]),"r"(a[2]),"r"(a[3]), "l"(db));
}
__device__ __forceinline__ void rs160_0(float* d, const uint32_t* a, uint64_t db){
  asm volatile("{ .reg .pred p; setp.ne.b32 p, 0, 0; wgmma.mma_async.sync.aligned.m64n160k16.f32.bf16.bf16 {%0, %1, %2, %3, %4, %5, %6, %7, %8, %9, %10, %11, %12, %13, %14, %15, %16, %17, %18, %19, %20, %21, %22, %23, %24, %25, %26, %27, %28, %29, %30, %31, %32, %33, %34, %35, %36, %37, %38, %39, %40, %41, %42, %43, %44, %45, %46, %47, %48, %49, %50, %51, %52, %53, %54, %55, %56, %57, %58, %59, %60, %61, %62, %63, %64, %65, %66, %67, %68, %69, %70, %71, %72, %73, %74, %75, %76, %77, %78, %79}, {%80,%81,%82,%83}, %84, p, 1, 1, 1; }"
   : "=f"(d[0]), "=f"(d[1]), "=f"(d[2]), "=f"(d[3]), "=f"(d[4]), "=f"(d[5]), "=f"(d[6]), "=f"(d[7]), "=f"(d[8]), "=f"(d[9]), "=f"(d[10]), "=f"(d[11]), "=f"(d[12]), "=f"(d[13]), "=f"(d[14]), "=f"(d[15]), "=f"(d[16]), "=f"(d[17]), "=f"(d[18]), "=f"(d[19]), "=f"(d[20]), "=f"(d[21]), "=f"(d[22]), "=f"(d[23]), "=f"(d[24]), "=f"(d[25]), "=f"(d[26]), "=f"(d[27]), "=f"(d[28]), "=f"(d[29]), "=f"(d[30]), "=f"(d[31]), "=f"(d[32]), "=f"(d[33]), "=f"(d[34]), "=f"(d[35]), "=f"(d[36]), "=f"(d[37]), "=f"(d[38]), "=f"(d[39]), "=f"(d[40]), "=f"(d[41]), "=f"(d[42]), "=f"(d[43]), "=f"(d[44]), "=f"(d[45]), "=f"(d[46]), "=f"(d[47]), "=f"(d[48]), "=f"(d[49]), "=f"(d[50]), "=f"(d[51]), "=f"(d[52]), "=f"(d[53]), "=f"(d[54]), "=f"(d[55]), "=f"(d[56]), "=f"(d[57]), "=f"(d[58]), "=f"(d[59]), "=f"(d[60]), "=f"(d[61]), "=f"(d[62]), "=f"(d[63]), "=f"(d[64]), "=f"(d[65]), "=f"(d[66]), "=f"(d[67]), "=f"(d[68]), "=f"(d[69]), "=f"(d[70]), "=f"(d[71]), "=f"(d[72]), "=f"(d[73]), "=f"(d[74]), "=f"(d[75]), "=f"(d[76]), "=f"(d[77]), "=f"(d[78]), "=f"(d[79]) : "r"(a[0]),"r"(a[1]),"r"(a[2]),"r"(a[3]), "l"(db));
}
__device__ __forceinline__ void rs160_1(float* d, const uint32_t* a, uint64_t db){
  asm volatile("{ .reg .pred p; setp.ne.b32 p, 1, 0; wgmma.mma_async.sync.aligned.m64n160k16.f32.bf16.bf16 {%0, %1, %2, %3, %4, %5, %6, %7, %8, %9, %10, %11, %12, %13, %14, %15, %16, %17, %18, %19, %20, %21, %22, %23, %24, %25, %26, %27, %28, %29, %30, %31, %32, %33, %34, %35, %36, %37, %38, %39, %40, %41, %42, %43, %44, %45, %46, %47, %48, %49, %50, %51, %52, %53, %54, %55, %56, %57, %58, %59, %60, %61, %62, %63, %64, %65, %66, %67, %68, %69, %70, %71, %72, %73, %74, %75, %76, %77, %78, %79}, {%80,%81,%82,%83}, %84, p, 1, 1, 1; }"
   : "+f"(d[0]), "+f"(d[1]), "+f"(d[2]), "+f"(d[3]), "+f"(d[4]), "+f"(d[5]), "+f"(d[6]), "+f"(d[7]), "+f"(d[8]), "+f"(d[9]), "+f"(d[10]), "+f"(d[11]), "+f"(d[12]), "+f"(d[13]), "+f"(d[14]), "+f"(d[15]), "+f"(d[16]), "+f"(d[17]), "+f"(d[18]), "+f"(d[19]), "+f"(d[20]), "+f"(d[21]), "+f"(d[22]), "+f"(d[23]), "+f"(d[24]), "+f"(d[25]), "+f"(d[26]), "+f"(d[27]), "+f"(d[28]), "+f"(d[29]), "+f"(d[30]), "+f"(d[31]), "+f"(d[32]), "+f"(d[33]), "+f"(d[34]), "+f"(d[35]), "+f"(d[36]), "+f"(d[37]), "+f"(d[38]), "+f"(d[39]), "+f"(d[40]), "+f"(d[41]), "+f"(d[42]), "+f"(d[43]), "+f"(d[44]), "+f"(d[45]), "+f"(d[46]), "+f"(d[47]), "+f"(d[48]), "+f"(d[49]), "+f"(d[50]), "+f"(d[51]), "+f"(d[52]), "+f"(d[53]), "+f"(d[54]), "+f"(d[55]), "+f"(d[56]), "+f"(d[57]), "+f"(d[58]), "+f"(d[59]), "+f"(d[60]), "+f"(d[61]), "+f"(d[62]), "+f"(d[63]), "+f"(d[64]), "+f"(d[65]), "+f"(d[66]), "+f"(d[67]), "+f"(d[68]), "+f"(d[69]), "+f"(d[70]), "+f"(d[71]), "+f"(d[72]), "+f"(d[73]), "+f"(d[74]), "+f"(d[75]), "+f"(d[76]), "+f"(d[77]), "+f"(d[78]), "+f"(d[79]) : "r"(a[0]),"r"(a[1]),"r"(a[2]),"r"(a[3]), "l"(db));
}
__device__ __forceinline__ void rs112_0(float* d, const uint32_t* a, uint64_t db){
  asm volatile("{ .reg .pred p; setp.ne.b32 p, 0, 0; wgmma.mma_async.sync.aligned.m64n112k16.f32.bf16.bf16 {%0, %1, %2, %3, %4, %5, %6, %7, %8, %9, %10, %11, %12, %13, %14, %15, %16, %17, %18, %19, %20, %21, %22, %23, %24, %25, %26, %27, %28, %29, %30, %31, %32, %33, %34, %35, %36, %37, %38, %39, %40, %41, %42, %43, %44, %45, %46, %47, %48, %49, %50, %51, %52, %53, %54, %55}, {%56,%57,%58,%59}, %60, p, 1, 1, 1; }"
   : "=f"(d[0]), "=f"(d[1]), "=f"(d[2]), "=f"(d[3]), "=f"(d[4]), "=f"(d[5]), "=f"(d[6]), "=f"(d[7]), "=f"(d[8]), "=f"(d[9]), "=f"(d[10]), "=f"(d[11]), "=f"(d[12]), "=f"(d[13]), "=f"(d[14]), "=f"(d[15]), "=f"(d[16]), "=f"(d[17]), "=f"(d[18]), "=f"(d[19]), "=f"(d[20]), "=f"(d[21]), "=f"(d[22]), "=f"(d[23]), "=f"(d[24]), "=f"(d[25]), "=f"(d[26]), "=f"(d[27]), "=f"(d[28]), "=f"(d[29]), "=f"(d[30]), "=f"(d[31]), "=f"(d[32]), "=f"(d[33]), "=f"(d[34]), "=f"(d[35]), "=f"(d[36]), "=f"(d[37]), "=f"(d[38]), "=f"(d[39]), "=f"(d[40]), "=f"(d[41]), "=f"(d[42]), "=f"(d[43]), "=f"(d[44]), "=f"(d[45]), "=f"(d[46]), "=f"(d[47]), "=f"(d[48]), "=f"(d[49]), "=f"(d[50]), "=f"(d[51]), "=f"(d[52]), "=f"(d[53]), "=f"(d[54]), "=f"(d[55]) : "r"(a[0]),"r"(a[1]),"r"(a[2]),"r"(a[3]), "l"(db));
}
__device__ __forceinline__ void rs112_1(float* d, const uint32_t* a, uint64_t db){
  asm volatile("{ .reg .pred p; setp.ne.b32 p, 1, 0; wgmma.mma_async.sync.aligned.m64n112k16.f32.bf16.bf16 {%0, %1, %2, %3, %4, %5, %6, %7, %8, %9, %10, %11, %12, %13, %14, %15, %16, %17, %18, %19, %20, %21, %22, %23, %24, %25, %26, %27, %28, %29, %30, %31, %32, %33, %34, %35, %36, %37, %38, %39, %40, %41, %42, %43, %44, %45, %46, %47, %48, %49, %50, %51, %52, %53, %54, %55}, {%56,%57,%58,%59}, %60, p, 1, 1, 1; }"
   : "+f"(d[0]), "+f"(d[1]), "+f"(d[2]), "+f"(d[3]), "+f"(d[4]), "+f"(d[5]), "+f"(d[6]), "+f"(d[7]), "+f"(d[8]), "+f"(d[9]), "+f"(d[10]), "+f"(d[11]), "+f"(d[12]), "+f"(d[13]), "+f"(d[14]), "+f"(d[15]), "+f"(d[16]), "+f"(d[17]), "+f"(d[18]), "+f"(d[19]), "+f"(d[20]), "+f"(d[21]), "+f"(d[22]), "+f"(d[23]), "+f"(d[24]), "+f"(d[25]), "+f"(d[26]), "+f"(d[27]), "+f"(d[28]), "+f"(d[29]), "+f"(d[30]), "+f"(d[31]), "+f"(d[32]), "+f"(d[33]), "+f"(d[34]), "+f"(d[35]), "+f"(d[36]), "+f"(d[37]), "+f"(d[38]), "+f"(d[39]), "+f"(d[40]), "+f"(d[41]), "+f"(d[42]), "+f"(d[43]), "+f"(d[44]), "+f"(d[45]), "+f"(d[46]), "+f"(d[47]), "+f"(d[48]), "+f"(d[49]), "+f"(d[50]), "+f"(d[51]), "+f"(d[52]), "+f"(d[53]), "+f"(d[54]), "+f"(d[55]) : "r"(a[0]),"r"(a[1]),"r"(a[2]),"r"(a[3]), "l"(db));
}
__device__ __forceinline__ void rs64_0(float* d, const uint32_t* a, uint64_t db){
  asm volatile("{ .reg .pred p; setp.ne.b32 p, 0, 0; wgmma.mma_async.sync.aligned.m64n64k16.f32.bf16.bf16 {%0, %1, %2, %3, %4, %5, %6, %7, %8, %9, %10, %11, %12, %13, %14, %15, %16, %17, %18, %19, %20, %21, %22, %23, %24, %25, %26, %27, %28, %29, %30, %31}, {%32,%33,%34,%35}, %36, p, 1, 1, 1; }"
   : "=f"(d[0]), "=f"(d[1]), "=f"(d[2]), "=f"(d[3]), "=f"(d[4]), "=f"(d[5]), "=f"(d[6]), "=f"(d[7]), "=f"(d[8]), "=f"(d[9]), "=f"(d[10]), "=f"(d[11]), "=f"(d[12]), "=f"(d[13]), "=f"(d[14]), "=f"(d[15]), "=f"(d[16]), "=f"(d[17]), "=f"(d[18]), "=f"(d[19]), "=f"(d[20]), "=f"(d[21]), "=f"(d[22]), "=f"(d[23]), "=f"(d[24]), "=f"(d[25]), "=f"(d[26]), "=f"(d[27]), "=f"(d[28]), "=f"(d[29]), "=f"(d[30]), "=f"(d[31]) : "r"(a[0]),"r"(a[1]),"r"(a[2]),"r"(a[3]), "l"(db));
}
__device__ __forceinline__ void rs64_1(float* d, const uint32_t* a, uint64_t db){
  asm volatile("{ .reg .pred p; setp.ne.b32 p, 1, 0; wgmma.mma_async.sync.aligned.m64n64k16.f32.bf16.bf16 {%0, %1, %2, %3, %4, %5, %6, %7, %8, %9, %10, %11, %12, %13, %14, %15, %16, %17, %18, %19, %20, %21, %22, %23, %24, %25, %26, %27, %28, %29, %30, %31}, {%32,%33,%34,%35}, %36, p, 1, 1, 1; }"
   : "+f"(d[0]), "+f"(d[1]), "+f"(d[2]), "+f"(d[3]), "+f"(d[4]), "+f"(d[5]), "+f"(d[6]), "+f"(d[7]), "+f"(d[8]), "+f"(d[9]), "+f"(d[10]), "+f"(d[11]), "+f"(d[12]), "+f"(d[13]), "+f"(d[14]), "+f"(d[15]), "+f"(d[16]), "+f"(d[17]), "+f"(d[18]), "+f"(d[19]), "+f"(d[20]), "+f"(d[21]), "+f"(d[22]), "+f"(d[23]), "+f"(d[24]), "+f"(d[25]), "+f"(d[26]), "+f"(d[27]), "+f"(d[28]), "+f"(d[29]), "+f"(d[30]), "+f"(d[31]) : "r"(a[0]),"r"(a[1]),"r"(a[2]),"r"(a[3]), "l"(db));
}
__device__ __forceinline__ void rs56_0(float* d, const uint32_t* a, uint64_t db){
  asm volatile("{ .reg .pred p; setp.ne.b32 p, 0, 0; wgmma.mma_async.sync.aligned.m64n56k16.f32.bf16.bf16 {%0, %1, %2, %3, %4, %5, %6, %7, %8, %9, %10, %11, %12, %13, %14, %15, %16, %17, %18, %19, %20, %21, %22, %23, %24, %25, %26, %27}, {%28,%29,%30,%31}, %32, p, 1, 1, 1; }"
   : "=f"(d[0]), "=f"(d[1]), "=f"(d[2]), "=f"(d[3]), "=f"(d[4]), "=f"(d[5]), "=f"(d[6]), "=f"(d[7]), "=f"(d[8]), "=f"(d[9]), "=f"(d[10]), "=f"(d[11]), "=f"(d[12]), "=f"(d[13]), "=f"(d[14]), "=f"(d[15]), "=f"(d[16]), "=f"(d[17]), "=f"(d[18]), "=f"(d[19]), "=f"(d[20]), "=f"(d[21]), "=f"(d[22]), "=f"(d[23]), "=f"(d[24]), "=f"(d[25]), "=f"(d[26]), "=f"(d[27]) : "r"(a[0]),"r"(a[1]),"r"(a[2]),"r"(a[3]), "l"(db));
}
__device__ __forceinline__ void rs56_1(float* d, const uint32_t* a, uint64_t db){
  asm volatile("{ .reg .pred p; setp.ne.b32 p, 1, 0; wgmma.mma_async.sync.aligned.m64n56k16.f32.bf16.bf16 {%0, %1, %2, %3, %4, %5, %6, %7, %8, %9, %10, %11, %12, %13, %14, %15, %16, %17, %18, %19, %20, %21, %22, %23, %24, %25, %26, %27}, {%28,%29,%30,%31}, %32, p, 1, 1, 1; }"
   : "+f"(d[0]), "+f"(d[1]), "+f"(d[2]), "+f"(d[3]), "+f"(d[4]), "+f"(d[5]), "+f"(d[6]), "+f"(d[7]), "+f"(d[8]), "+f"(d[9]), "+f"(d[10]), "+f"(d[11]), "+f"(d[12]), "+f"(d[13]), "+f"(d[14]), "+f"(d[15]), "+f"(d[16]), "+f"(d[17]), "+f"(d[18]), "+f"(d[19]), "+f"(d[20]), "+f"(d[21]), "+f"(d[22]), "+f"(d[23]), "+f"(d[24]), "+f"(d[25]), "+f"(d[26]), "+f"(d[27]) : "r"(a[0]),"r"(a[1]),"r"(a[2]),"r"(a[3]), "l"(db));
}
__device__ __forceinline__ void ss56_0(float* d, uint64_t da, uint64_t db){
  asm volatile("{ .reg .pred p; setp.ne.b32 p, 0, 0; wgmma.mma_async.sync.aligned.m64n56k16.f32.bf16.bf16 {%0, %1, %2, %3, %4, %5, %6, %7, %8, %9, %10, %11, %12, %13, %14, %15, %16, %17, %18, %19, %20, %21, %22, %23, %24, %25, %26, %27}, %28, %29, p, 1, 1, 0, 1; }"
   : "=f"(d[0]), "=f"(d[1]), "=f"(d[2]), "=f"(d[3]), "=f"(d[4]), "=f"(d[5]), "=f"(d[6]), "=f"(d[7]), "=f"(d[8]), "=f"(d[9]), "=f"(d[10]), "=f"(d[11]), "=f"(d[12]), "=f"(d[13]), "=f"(d[14]), "=f"(d[15]), "=f"(d[16]), "=f"(d[17]), "=f"(d[18]), "=f"(d[19]), "=f"(d[20]), "=f"(d[21]), "=f"(d[22]), "=f"(d[23]), "=f"(d[24]), "=f"(d[25]), "=f"(d[26]), "=f"(d[27]) : "l"(da), "l"(db));
}
__device__ __forceinline__ void ss56_1(float* d, uint64_t da, uint64_t db){
  asm volatile("{ .reg .pred p; setp.ne.b32 p, 1, 0; wgmma.mma_async.sync.aligned.m64n56k16.f32.bf16.bf16 {%0, %1, %2, %3, %4, %5, %6, %7, %8, %9, %10, %11, %12, %13, %14, %15, %16, %17, %18, %19, %20, %21, %22, %23, %24, %25, %26, %27}, %28, %29, p, 1, 1, 0, 1; }"
   : "+f"(d[0]), "+f"(d[1]), "+f"(d[2]), "+f"(d[3]), "+f"(d[4]), "+f"(d[5]), "+f"(d[6]), "+f"(d[7]), "+f"(d[8]), "+f"(d[9]), "+f"(d[10]), "+f"(d[11]), "+f"(d[12]), "+f"(d[13]), "+f"(d[14]), "+f"(d[15]), "+f"(d[16]), "+f"(d[17]), "+f"(d[18]), "+f"(d[19]), "+f"(d[20]), "+f"(d[21]), "+f"(d[22]), "+f"(d[23]), "+f"(d[24]), "+f"(d[25]), "+f"(d[26]), "+f"(d[27]) : "l"(da), "l"(db));
}
__device__ __forceinline__ void ss64_0(float* d, uint64_t da, uint64_t db){
  asm volatile("{ .reg .pred p; setp.ne.b32 p, 0, 0; wgmma.mma_async.sync.aligned.m64n64k16.f32.bf16.bf16 {%0, %1, %2, %3, %4, %5, %6, %7, %8, %9, %10, %11, %12, %13, %14, %15, %16, %17, %18, %19, %20, %21, %22, %23, %24, %25, %26, %27, %28, %29, %30, %31}, %32, %33, p, 1, 1, 1, 1; }"
   : "=f"(d[0]), "=f"(d[1]), "=f"(d[2]), "=f"(d[3]), "=f"(d[4]), "=f"(d[5]), "=f"(d[6]), "=f"(d[7]), "=f"(d[8]), "=f"(d[9]), "=f"(d[10]), "=f"(d[11]), "=f"(d[12]), "=f"(d[13]), "=f"(d[14]), "=f"(d[15]), "=f"(d[16]), "=f"(d[17]), "=f"(d[18]), "=f"(d[19]), "=f"(d[20]), "=f"(d[21]), "=f"(d[22]), "=f"(d[23]), "=f"(d[24]), "=f"(d[25]), "=f"(d[26]), "=f"(d[27]), "=f"(d[28]), "=f"(d[29]), "=f"(d[30]), "=f"(d[31]) : "l"(da), "l"(db));
}
__device__ __forceinline__ void ss64_1(float* d, uint64_t da, uint64_t db){
  asm volatile("{ .reg .pred p; setp.ne.b32 p, 1, 0; wgmma.mma_async.sync.aligned.m64n64k16.f32.bf16.bf16 {%0, %1, %2, %3, %4, %5, %6, %7, %8, %9, %10, %11, %12, %13, %14, %15, %16, %17, %18, %19, %20, %21, %22, %23, %24, %25, %26, %27, %28, %29, %30, %31}, %32, %33, p, 1, 1, 1, 1; }"
   : "+f"(d[0]), "+f"(d[1]), "+f"(d[2]), "+f"(d[3]), "+f"(d[4]), "+f"(d[5]), "+f"(d[6]), "+f"(d[7]), "+f"(d[8]), "+f"(d[9]), "+f"(d[10]), "+f"(d[11]), "+f"(d[12]), "+f"(d[13]), "+f"(d[14]), "+f"(d[15]), "+f"(d[16]), "+f"(d[17]), "+f"(d[18]), "+f"(d[19]), "+f"(d[20]), "+f"(d[21]), "+f"(d[22]), "+f"(d[23]), "+f"(d[24]), "+f"(d[25]), "+f"(d[26]), "+f"(d[27]), "+f"(d[28]), "+f"(d[29]), "+f"(d[30]), "+f"(d[31]) : "l"(da), "l"(db));
}
__device__ __forceinline__ void rs56_z(float* d, const uint32_t* a, uint64_t db){
  asm volatile("{ .reg .pred p; setp.ne.b32 p, 0, 0; wgmma.mma_async.sync.aligned.m64n56k16.f32.bf16.bf16 {%0, %1, %2, %3, %4, %5, %6, %7, %8, %9, %10, %11, %12, %13, %14, %15, %16, %17, %18, %19, %20, %21, %22, %23, %24, %25, %26, %27}, {%28,%29,%30,%31}, %32, p, 1, 1, 1; }"
   : "+f"(d[0]), "+f"(d[1]), "+f"(d[2]), "+f"(d[3]), "+f"(d[4]), "+f"(d[5]), "+f"(d[6]), "+f"(d[7]), "+f"(d[8]), "+f"(d[9]), "+f"(d[10]), "+f"(d[11]), "+f"(d[12]), "+f"(d[13]), "+f"(d[14]), "+f"(d[15]), "+f"(d[16]), "+f"(d[17]), "+f"(d[18]), "+f"(d[19]), "+f"(d[20]), "+f"(d[21]), "+f"(d[22]), "+f"(d[23]), "+f"(d[24]), "+f"(d[25]), "+f"(d[26]), "+f"(d[27]) : "r"(a[0]),"r"(a[1]),"r"(a[2]),"r"(a[3]), "l"(db));
}
__device__ __forceinline__ void ss56_z(float* d, uint64_t da, uint64_t db){
  asm volatile("{ .reg .pred p; setp.ne.b32 p, 0, 0; wgmma.mma_async.sync.aligned.m64n56k16.f32.bf16.bf16 {%0, %1, %2, %3, %4, %5, %6, %7, %8, %9, %10, %11, %12, %13, %14, %15, %16, %17, %18, %19, %20, %21, %22, %23, %24, %25, %26, %27}, %28, %29, p, 1, 1, 0, 1; }"
   : "+f"(d[0]), "+f"(d[1]), "+f"(d[2]), "+f"(d[3]), "+f"(d[4]), "+f"(d[5]), "+f"(d[6]), "+f"(d[7]), "+f"(d[8]), "+f"(d[9]), "+f"(d[10]), "+f"(d[11]), "+f"(d[12]), "+f"(d[13]), "+f"(d[14]), "+f"(d[15]), "+f"(d[16]), "+f"(d[17]), "+f"(d[18]), "+f"(d[19]), "+f"(d[20]), "+f"(d[21]), "+f"(d[22]), "+f"(d[23]), "+f"(d[24]), "+f"(d[25]), "+f"(d[26]), "+f"(d[27]) : "l"(da), "l"(db));
}
template<int N> __device__ __forceinline__ void rs(float* d, const uint32_t* a, uint64_t db, bool first){
  if constexpr (N==120) { if(first) rs120_0(d,a,db); else rs120_1(d,a,db); }
  if constexpr (N==184) { if(first) rs184_0(d,a,db); else rs184_1(d,a,db); }
  if constexpr (N==160) { if(first) rs160_0(d,a,db); else rs160_1(d,a,db); }
  if constexpr (N==112) { if(first) rs112_0(d,a,db); else rs112_1(d,a,db); }
  if constexpr (N==64) { if(first) rs64_0(d,a,db); else rs64_1(d,a,db); }
  if constexpr (N==56) { if(first) rs56_0(d,a,db); else rs56_1(d,a,db); }
}

constexpr float LOG2E = 1.4426950408889634f;
__device__ __forceinline__ float phi(float a, float r, float rl) {
  float e = ex2(a * rl);
  float p = fmaf(a, r, 1.0f);
  return (a > 0.f ? p : e) + 1e-6f;
}
__device__ __forceinline__ float sig_r(float a, float nrl) { return rcp(1.0f + ex2(a * nrl)); }

#define BAR(i) (sb + MISC + 8u * (uint32_t)(i))

__host__ __device__ constexpr int unitB(int g) { return g == 0 ? 0 : g == 1 ? 3 : g == 6 ? 8 : 14 + 3 * (g - 2); }
__host__ __device__ constexpr int unitC(int g) { return g == 0 ? 11 : g == 1 ? 5 : g == 6 ? 8 : 14 + 3 * (g - 2); }
__host__ __device__ constexpr int unitD(int g) { return g == 0 ? 11 : 14 + 3 * ((g - 1) & 3); }
__host__ __device__ constexpr int depB(int g) { return g < 2 ? XCONS : g == 2 ? EA + 1 : g == 3 ? EA + 2 : g == 4 ? EA + 4 : g == 5 ? EA + 5 : KVDONE; }
__host__ __device__ constexpr int depC(int g) { return g == 0 ? KVDONE : EB + g; }
__host__ __device__ constexpr int depD(int g) { return g == 0 ? EC : g < 5 ? EC + g + 1 : ED + g - 4; }
template <int P> __host__ __device__ constexpr int unitP(int g) { return P == 0 ? 14 + 2 * g : P == 1 ? unitB(g) : P == 2 ? unitC(g) : unitD(g); }
template <typename Fn> __host__ __device__ constexpr uint64_t packtab(Fn f) { uint64_t t = 0; for (int g = 0; g < 7; g++) t |= (uint64_t)f(g) << (8 * g); return t; }

template <int P, int N, typename Fn>
__device__ __forceinline__ void pass1(float* acc, const uint32_t* xf, uint32_t sb, uint32_t pb, bool lane0, Fn shadow) {
  constexpr int F0 = FA + 7 * P, E0 = EA + 7 * P;
#pragma unroll
  for (int g = 0; g < 7; g++) {
    mbar_wait(BAR(F0 + g));
    wg_fence();
#pragma unroll
    for (int kk = 0; kk < 4; kk++) rs<N>(acc, xf + 16 * g + 4 * kk, desc(unitP<P>(g) * U + kk * 2048, U), g == 0 && kk == 0);
    wg_commit();
    shadow(g);
    if (g > 0) {
      wg_wait<1>();
      if (lane0) {
        mbar_arrive(BAR(E0 + g - 1));
        if ((P == 1 || P == 2) && g == 2) mbar_arrive_remote(pb + MISC + 8u * (PF + P - 1));
        if (P == 3 && g == 1) mbar_arrive_remote(pb + MISC + 8u * (PF + 2));
      }
    }
  }
  wg_wait<0>();
  if (lane0) mbar_arrive(BAR(E0 + 6));
  pin<N / 2>(acc);
}

__device__ __forceinline__ void hfrag64(uint32_t* h, const float* acc, const float* r2, const float* nrl) {
#pragma unroll
  for (int m = 0; m < 16; m++) {
    const int w = m & 1;
    float a = acc[2 * m] * acc[32 + 2 * m] * (r2[w] * sig_r(acc[2 * m], nrl[w]));
    float b = acc[2 * m + 1] * acc[33 + 2 * m] * (r2[w] * sig_r(acc[2 * m + 1], nrl[w]));
    h[m] = pack2(a, b);
  }
}

__device__ __forceinline__ void send_ll(uint4* p, const float* a, float tagf) {
#pragma unroll
  for (int q = 0; q < 4; q++)
    st_ll(p + q * 128, pack2(a[7 * q], a[7 * q + 1]), pack2(a[7 * q + 2], a[7 * q + 3]), pack2(a[7 * q + 4], a[7 * q + 5]), pack2(a[7 * q + 6], tagf));
}
__device__ __forceinline__ void recv_ll(float* a, uint32_t* v, const uint4* p, uint32_t tag) {
  asm volatile(
      "{ .reg .pred p; .reg .b32 t, u, n; .reg .b128 w; .reg .b64 lo, hi;\n"
      "mov.u32 n, 0;\n"
      "R_L: xor.b32 t, %3, %17; xor.b32 u, %7, %17; or.b32 t, t, u; xor.b32 u, %11, %17; or.b32 t, t, u; xor.b32 u, %15, %17; or.b32 t, t, u;\n"
      "setp.lt.u32 p, t, 65536; vote.sync.all.pred p, p, 0xffffffff; @p bra R_D;\n"
      "ld.relaxed.gpu.global.b128 w, [%16]; mov.b128 {lo,hi}, w; mov.b64 {%0,%1}, lo; mov.b64 {%2,%3}, hi;\n"
      "ld.relaxed.gpu.global.b128 w, [%16+2048]; mov.b128 {lo,hi}, w; mov.b64 {%4,%5}, lo; mov.b64 {%6,%7}, hi;\n"
      "ld.relaxed.gpu.global.b128 w, [%16+4096]; mov.b128 {lo,hi}, w; mov.b64 {%8,%9}, lo; mov.b64 {%10,%11}, hi;\n"
      "ld.relaxed.gpu.global.b128 w, [%16+6144]; mov.b128 {lo,hi}, w; mov.b64 {%12,%13}, lo; mov.b64 {%14,%15}, hi;\n"
      "add.u32 n, n, 1; setp.lt.u32 p, n, 2097152; @p bra R_L; trap;\n"
      "R_D: }"
      : "+r"(v[0]), "+r"(v[1]), "+r"(v[2]), "+r"(v[3]), "+r"(v[4]), "+r"(v[5]), "+r"(v[6]), "+r"(v[7]), "+r"(v[8]), "+r"(v[9]), "+r"(v[10]),
        "+r"(v[11]), "+r"(v[12]), "+r"(v[13]), "+r"(v[14]), "+r"(v[15])
      : "l"(p), "r"(tag << 16)
      : "memory");
#pragma unroll
  for (int q = 0; q < 4; q++) {
    a[7 * q] += blo(v[4 * q]); a[7 * q + 1] += bhi(v[4 * q]);
    a[7 * q + 2] += blo(v[4 * q + 1]); a[7 * q + 3] += bhi(v[4 * q + 1]);
    a[7 * q + 4] += blo(v[4 * q + 2]); a[7 * q + 5] += bhi(v[4 * q + 2]);
    a[7 * q + 6] += blo(v[4 * q + 3]);
  }
}

__global__ void __cluster_dims__(2, 1, 1) __launch_bounds__(384, 1)
fused_kernel(const __grid_constant__ Maps M, const __nv_bfloat16* __restrict__ x) {
  extern __shared__ __align__(1024) uint8_t smem_raw[];
  uint32_t sb = smem_u32(smem_raw);
  asm volatile("" : "+r"(sb));
  const int tid = threadIdx.x;
  const int warp = __shfl_sync(0xffffffffu, tid >> 5, 0);
  const int lane = tid & 31;
  const int wg = warp >> 2;
  const int r = blockIdx.x >> 3, j = blockIdx.x & 7, kq = j >> 1, n = j & 1;

#define INIT_SHARE(w) do { if (elect_one()) { \
    _Pragma("unroll 1") for (int b = FB + (w); b < NBAR; b += 11) { \
      const uint32_t cnt = b < EA ? 1u : b < KVDONE ? 8u : b < KVM ? 4u : 3u; \
      mbar_init(BAR(b), cnt); \
      if (b < EA) mbar_expect_tx(BAR(b), b < FC ? 23552u : b < FG ? 20480u : b < FO ? 25088u : b < FW ? 16384u : b < HF ? 25088u : b < HF + 4 ? 8192u : 12288u); \
    } \
    fence_async(); } \
    asm volatile("fence.mbarrier_init.release.cluster;" ::: "memory"); \
    __syncwarp(); \
    asm volatile("barrier.cluster.arrive.relaxed.aligned;" ::: "memory"); } while (0)

  if (__builtin_expect(wg == 2, 1)) {
    asm volatile("setmaxnreg.dec.sync.aligned.u32 24;");
    if (__builtin_expect(warp == 8, 1)) {
      const bool el = elect_one();
      if (el) {
        TS(2, 0); GTS(2, 30);
#pragma unroll 1
        for (int b = 0; b < 7; b++) {
          mbar_init(BAR(XF + b), 1); mbar_expect_tx(BAR(XF + b), 8192);
          mbar_init(BAR(XF + 7 + b), 1); mbar_expect_tx(BAR(XF + 7 + b), 8192);
          mbar_init(BAR(FA + b), 1); mbar_expect_tx(BAR(FA + b), 14336);
        }
        fence_async();
      }
      asm volatile("fence.mbarrier_init.release.cluster;" ::: "memory");
      __syncwarp();
      asm volatile("barrier.cluster.arrive.relaxed.aligned;" ::: "memory");
      if (el) {
        TS(2, 8);
        const int row0 = r * 128, ca = j * 56;
#pragma unroll 1
        for (int kb = 0; kb < 7; kb++) {
          tma2d(sb + kb * 16384, &M.x, kb * 64, row0, BAR(XF + kb));
          if (kb == 0) TS(2, 9);
        }
        TS(2, 10);
#pragma unroll 1
        for (int g = 0; g < 7; g++) {
          tma2d(sb + (14 + 2 * g) * U, &M.wqkv, 448 + ca, g * 64, BAR(FA + g));
          tma2d(sb + (15 + 2 * g) * U, &M.wqkv, 896 + ca, g * 64, BAR(FA + g));
          if (g == 1) {
            TS(2, 11);
#pragma unroll 1
            for (int kb = 0; kb < 7; kb++) tma2d(sb + kb * 16384 + 8192, &M.x, kb * 64, row0 + 64, BAR(XF + 7 + kb));
          }
        }
        TS(2, 1);
      }
      __syncwarp();
      asm volatile("barrier.cluster.wait.acquire.aligned;" ::: "memory");
      if (el) {
        const uint32_t ep = g_epoch[blockIdx.x] + 1;
        const int f0 = j * 224, ca = j * 56;
#pragma unroll 1
        for (int p = 0; p < 3; p++) {
          const uint64_t ut = p == 0 ? packtab(unitB) : p == 1 ? packtab(unitC) : packtab(unitD);
          const uint64_t dt = p == 0 ? packtab(depB) : p == 1 ? packtab(depC) : packtab(depD);
          const CUtensorMap* m3 = p == 0 ? &M.wqkv : p == 1 ? &M.w1b : &M.w3b;
          const int c3 = p == 0 ? ca : f0 + 192;
#pragma unroll 1
          for (int g = 0; g < 7; g++) {
            const uint32_t dst = sb + (uint32_t)((ut >> (8 * g)) & 255) * U;
            const uint32_t fb = BAR(FB + 7 * p + g);
            mbar_wait(BAR((uint32_t)((dt >> (8 * g)) & 255)));
            tma2d(dst, &M.w1a, f0 + 64 * p, g * 64, fb);
            tma2d(dst + U, &M.w3a, f0 + 64 * p, g * 64, fb);
            tma2d(dst + 2 * U, m3, c3, g * 64, fb);
          }
          TS(2, 2 + p);
        }
        const int fp = (j ^ 1) * 224;
        const int c1 = n * 224 + (1 - (kq >> 1)) * 112;
        const int c2 = n * 224 + (kq ^ 1) * 56, c3 = n * 224 + kq * 56;
        mbar_wait(BAR(ED + 4));
        tma2d(sb + VA, &M.w2a, c1, f0, BAR(FG + 0)); tma2d(sb + VA + 14336, &M.w2b, c1 + 64, f0, BAR(FG + 0));
        tma2d(sb + VB, &M.w2a, c1, fp, BAR(FG + 1)); tma2d(sb + VB + 14336, &M.w2b, c1 + 64, fp, BAR(FG + 1));
        mbar_wait(BAR(ED + 6));
        tma2d(sb + VC, &M.w2a, c1, f0 + 112, BAR(FG + 2)); tma2d(sb + VC + 14336, &M.w2b, c1 + 64, f0 + 112, BAR(FG + 2));
        tma2d(sb + VD, &M.w2a, c1, fp + 112, BAR(FG + 3)); tma2d(sb + VD + 14336, &M.w2b, c1 + 64, fp + 112, BAR(FG + 3));
        TS(2, 5);
        poll_flag(&g_f2[r * 32], 8u * ep);
        asm volatile("fence.proxy.async;" ::: "memory");
        TS(2, 6);
        mbar_wait(BAR(LD1));
#pragma unroll 1
        for (int t = 0; t < 4; t++) tma2d(sb + t * 16384, &M.o, t * 64, r * 128, BAR(FO + t));
        mbar_wait(BAR(EG + 0)); tma2d(sb + VA, &M.w2c, c2, f0, BAR(FG + 4));
        mbar_wait(BAR(EG + 1)); tma2d(sb + VB, &M.w2c, c2, fp, BAR(FG + 5));
        mbar_wait(BAR(EG + 2)); tma2d(sb + VC, &M.w2c, c3, f0, BAR(FG + 6));
        mbar_wait(BAR(EG + 3)); tma2d(sb + VD, &M.w2c, c3, fp, BAR(FG + 7));
        mbar_wait(BAR(LD2));
        mbar_wait_cl(BAR(ACK));
#pragma unroll 1
        for (int t = 4; t < 7; t++) tma2d(sb + t * 16384, &M.o, t * 64, r * 128, BAR(FO + t));
        mbar_wait(BAR(EG + 4)); tma2d(sb + VA, &M.wo, c3, 0, BAR(FW + 0));
        mbar_wait(BAR(EG + 5)); tma2d(sb + VB, &M.wo, c3, 224, BAR(FW + 1));
        g_epoch[blockIdx.x] = ep;
        TS(2, 7);
        TSDUMP(2);
      }
    } else {
      if (elect_one()) {
        const CUtensorMap* mp = &M.wqkv + (warp - 9) * 4;
        if ((sb & 0x3FFFFu) != SM_BASE) asm volatile("trap;");
#pragma unroll
        for (int i = 0; i < 4; i++) if (i < 3 || warp < 11) asm volatile("prefetch.tensormap [%0];" ::"l"(mp + i) : "memory");
      }
      INIT_SHARE(warp - 1);
      asm volatile("barrier.cluster.wait.acquire.aligned;" ::: "memory");
      const uint32_t ep = g_epoch[blockIdx.x] + 1;
      const int at = tid - 288;
      if (at < 64) reinterpret_cast<float4*>(g_kv + ((ep & 1) ^ 1) * 32768 + blockIdx.x * 256)[at] = make_float4(0.f, 0.f, 0.f, 0.f);
      mbar_wait(BAR(EA + 6));
      const uint32_t kvm = sb + KVM_U * U;
#pragma unroll 1
      for (int c = at; c < 512; c += 96) {
        const int d = c >> 3, cc = c & 7;
        const bool used = d < 56 && (cc == 7 || (d < 28 ? cc < 4 : (cc >= 3)));
        if (!used) { const uint32_t z[4] = {0, 0, 0, 0}; sts4(kvm + d * 128 + ((cc ^ (d & 7)) << 4), z); }
      }
      if (warp == 9) {
        mbar_wait(BAR(KVRED));
        if (lane == 0) {
          asm volatile("fence.acq_rel.gpu;" ::: "memory");
          asm volatile("red.release.gpu.global.add.u32 [%0], 1;" ::"l"(&g_f1[j * 32]) : "memory");
          TS(3, 0);
        }
      }
      if (lane == 0) poll_flag(&g_f1[j * 32], 16u * ep);
      __syncwarp();
      if (at == 0) TS(3, 1);
      {
        const float* kv = g_kv + (ep & 1) * 32768 + j * 4096;
#pragma unroll 1
        for (int idx = at; idx < 280; idx += 96) {
          const int d = idx / 5, m = idx - d * 5;
          const int cc = m == 4 ? 7 : m + (d >= 28 ? 3 : 0);
          const float4* src = reinterpret_cast<const float4*>(kv + d * 64 + cc * 8);
          const float4 v0 = __ldcg(src), v1 = __ldcg(src + 1);
          const uint32_t w[4] = {pack2(v0.x, v0.y), pack2(v0.z, v0.w), pack2(v1.x, v1.y), pack2(v1.z, v1.w)};
          sts4(kvm + d * 128 + ((cc ^ (d & 7)) << 4), w);
        }
      }
      fence_async();
      __syncwarp();
      if (lane == 0) mbar_arrive(BAR(KVM));
      if (at == 0) TS(3, 2);
      if (warp == 9) {
        mbar_wait(BAR(OST));
        if (lane == 0) {
          asm volatile("fence.acq_rel.gpu;" ::: "memory");
          asm volatile("red.release.gpu.global.add.u32 [%0], 1;" ::"l"(&g_f2[r * 32]) : "memory");
          TS(3, 3);
          TSDUMP(3);
        }
      }
    }
  } else {
    INIT_SHARE(warp);
    asm volatile("setmaxnreg.inc.sync.aligned.u32 240;");
    const uint32_t ep = g_epoch[blockIdx.x] + 1;
    asm volatile("barrier.cluster.wait.acquire.aligned;" ::: "memory");
    CTS(0);
    const int w4 = warp & 3;
#define LANE() const int ln = laneid(), g8 = ln >> 2, t4 = ln & 3; (void)g8; (void)t4
    const bool lane0 = lane == 0;
    const uint32_t pb = mapa(sb, n ^ 1);
    const uint32_t so = sb + (uint32_t)((wg * 64 + w4 * 16 + (lane & 7) + ((lane >> 3) & 1) * 8) * 128 + (((lane >> 4) ^ (lane & 7)) << 4));
    uint32_t xf[112];
    float rs_[2];
#define RSD() pin<2>(rs_); const float rl[2] = {rs_[0] * LOG2E, rs_[1] * LOG2E}, nrl[2] = {-rl[0], -rl[1]}, r2[2] = {rs_[0] * rs_[0], rs_[1] * rs_[1]}; (void)rl; (void)nrl; (void)r2
    float dl0, dl1;
    uint32_t pm0, pm1;
    {
      float c[4][4];
#pragma unroll
      for (int i = 0; i < 16; i++) c[i >> 2][i & 3] = 0.f;
#pragma unroll
      for (int kb = 0; kb < 7; kb++) {
        mbar_wait(BAR(XF + kb) + wg * 56);
        if (kb == 0) CTS(14);
        if (kb == 6) CTS(15);
#pragma unroll
        for (int kk = 0; kk < 4; kk++) {
          uint32_t* a = xf + 16 * kb + 4 * kk;
          ldsm4(a, (so ^ (kk << 5)) + kb * 16384);
          asm volatile("mma.sync.aligned.m16n8k16.row.col.f32.bf16.bf16.f32 {%0,%1,%2,%3}, {%4,%5,%6,%7}, {%8,%8}, {%0,%1,%2,%3};"
                       : "+f"(c[kk][0]), "+f"(c[kk][1]), "+f"(c[kk][2]), "+f"(c[kk][3])
                       : "r"(a[0]), "r"(a[1]), "r"(a[2]), "r"(a[3]), "r"(0x3F803F80u));
        }
      }
      const float m0 = ((c[0][0] + c[1][0]) + (c[2][0] + c[3][0])) * (1.0f / 448.0f);
      const float m1 = ((c[0][2] + c[1][2]) + (c[2][2] + c[3][2])) * (1.0f / 448.0f);
      const uint32_t p0 = pack2(m0, m0), p1 = pack2(m1, m1);
      dl0 = m0 - blo(p0); dl1 = m1 - blo(p1);
      __syncwarp();
      if (lane0) mbar_arrive(BAR(XCONS));
      pm0 = p0; pm1 = p1;
#pragma unroll
      for (int i = 0; i < 16; i++) asm volatile("sub.rn.bf16x2 %0, %0, %1;" : "+r"(xf[i]) : "r"((i & 1) ? p1 : p0));
    }
    CTS(1);
    uint32_t pq[14];
    {
      float acc[60];
      float ss[4] = {0.f, 0.f, 0.f, 0.f};
      pass1<0, 120>(acc, xf, sb, pb, lane0, [&](int g) {
        if (g < 6) {
#pragma unroll
          for (int i = 0; i < 16; i++) asm volatile("sub.rn.bf16x2 %0, %0, %1;" : "+r"(xf[16 * g + 16 + i]) : "r"((i & 1) ? pm1 : pm0));
        }
#pragma unroll
        for (int i = 0; i < 16; i++) {
          const float lo = blo(xf[16 * g + i]), hi = bhi(xf[16 * g + i]);
          ss[i & 1] = fmaf(lo, lo, ss[i & 1]);
          ss[2 + (i & 1)] = fmaf(hi, hi, ss[2 + (i & 1)]);
        }
        pin<4>(ss);
        if (g == 6) {
          float s0 = ss[0] + ss[2], s1 = ss[1] + ss[3];
          s0 += __shfl_xor_sync(0xffffffffu, s0, 1); s1 += __shfl_xor_sync(0xffffffffu, s1, 1);
          s0 += __shfl_xor_sync(0xffffffffu, s0, 2); s1 += __shfl_xor_sync(0xffffffffu, s1, 2);
          const float v0 = fmaxf(s0 * (1.0f / 448.0f) - dl0 * dl0, 0.f), v1 = fmaxf(s1 * (1.0f / 448.0f) - dl1 * dl1, 0.f);
          rs_[0] = 1.0f / bfr(sqrtf(bfr(bfr(v0) + 1e-5f)));
          rs_[1] = 1.0f / bfr(sqrtf(bfr(bfr(v1) + 1e-5f)));
          pin<2>(rs_);
        }
      });
      CTS(2);
      RSD();
      LANE();
      uint32_t pk[16], pv[16];
#pragma unroll
      for (int m = 0; m < 14; m++) {
        const int w = m & 1;
        pk[m] = pack2(phi(acc[2 * m], rs_[w], rl[w]), phi(acc[2 * m + 1], rs_[w], rl[w]));
        pv[m] = pack2(acc[32 + 2 * m] * rs_[w], acc[33 + 2 * m] * rs_[w]);
      }
      pk[14] = pk[15] = 0u;
      pv[14] = pv[15] = t4 == 0 ? 0x3F803F80u : 0u;
      mbar_wait(BAR(XCONS));
#pragma unroll
      for (int kk = 0; kk < 4; kk++) {
        stsm4((so ^ (kk << 5)) + 8 * U, pk[4 * kk], pk[4 * kk + 1], pk[4 * kk + 2], pk[4 * kk + 3]);
        stsm4((so ^ (kk << 5)) + 10 * U, pv[4 * kk], pv[4 * kk + 1], pv[4 * kk + 2], pv[4 * kk + 3]);
      }
      fence_async();
      __syncwarp();
      if (lane0) mbar_arrive(BAR(PKST));
      if (wg == 1) {
        float kv[32];
        mbar_wait(BAR(PKST));
        wg_fence();
#pragma unroll
        for (int ks = 0; ks < 8; ks++) {
          if (ks == 0) ss64_0(kv, desc(8 * U, U), desc(10 * U, U));
          else ss64_1(kv, desc(8 * U + ks * 2048, U), desc(10 * U + ks * 2048, U));
        }
        wg_commit();
        wg_wait<0>();
        pin<32>(kv);
        if (lane0) mbar_arrive(BAR(KVDONE));
        float* kg = g_kv + (ep & 1) * 32768 + j * 4096 + (w4 * 16 + g8) * 64 + 2 * t4;
#pragma unroll
        for (int h = 0; h < 2; h++) {
          const int d = w4 * 16 + g8 + 8 * h;
          const bool h0 = d < 28;
          if (d < 56) {
#pragma unroll
            for (int i = 0; i < 7; i++) {
              const bool e0 = (8 * i + 2 * t4) < 28;
              if (e0 == h0) asm volatile("red.relaxed.gpu.global.add.v2.f32 [%0], {%1,%2};" ::"l"(kg + h * 512 + 8 * i), "f"(kv[4 * i + 2 * h]), "f"(kv[4 * i + 2 * h + 1]) : "memory");
            }
            if (t4 == 0) asm volatile("red.relaxed.gpu.global.add.f32 [%0], %1;" ::"l"(kg + h * 512 + 56 + (h0 ? 0 : 1)), "f"(kv[28 + 2 * h]) : "memory");
          }
        }
        __syncwarp();
        if (lane0) mbar_arrive(BAR(KVRED));
      }
      CTS(3);
    }
    const uint32_t hoff = (uint32_t)(wg * 8192 + w4 * 2048 + laneid() * 16);
    {
      float acc[92];
      pass1<1, 184>(acc, xf, sb, pb, lane0, [&](int) {});
      CTS(4);
      RSD();
      uint32_t h[16];
      hfrag64(h, acc, r2, nrl);
      mbar_wait(BAR(EB + 1));
#pragma unroll
      for (int s = 0; s < 4; s++) sts4(sb + hoff + s * 512, h + 4 * s);
      fence_async();
      mbar_wait_cl(BAR(PF + 0));
      __syncwarp();
      if (lane0) bulk_s2c(pb + 2 * U + hoff, sb + hoff, 2048, pb + MISC + 8u * (HF + 0) + wg * 8);
#pragma unroll
      for (int m = 0; m < 14; m++) {
        const int w = m & 1;
        pq[m] = pack2(phi(acc[64 + 2 * m], rs_[w], rl[w]), phi(acc[65 + 2 * m], rs_[w], rl[w]));
      }
      pq[12] ^= sb; pq[13] ^= sb;
      pinr<14>(pq);
      CTS(5);
    }
    uint32_t sg[8];
    {
      float acc[80];
      pass1<2, 160>(acc, xf, sb, pb, lane0, [&](int) {});
      CTS(6);
      RSD();
      uint32_t h[16];
      hfrag64(h, acc, r2, nrl);
      mbar_wait(BAR(EC + 1));
#pragma unroll
      for (int s = 0; s < 4; s++) sts4(sb + 4 * U + hoff + s * 512, h + 4 * s);
      fence_async();
      mbar_wait_cl(BAR(PF + 1));
      __syncwarp();
      if (lane0) bulk_s2c(pb + 6 * U + hoff, sb + 4 * U + hoff, 2048, pb + MISC + 8u * (HF + 2) + wg * 8);
      float nm[32];
      mbar_wait(BAR(KVM));
      {
        uint32_t q3[4];
        asm volatile("xor.b32 %0, %4, %6; xor.b32 %1, %5, %6; mov.b32 %2, 0; mov.b32 %3, 0;" : "=r"(q3[0]), "=r"(q3[1]), "=r"(q3[2]), "=r"(q3[3]) : "r"(pq[12]), "r"(pq[13]), "r"(sb));
        wg_fence();
        rs64_0(nm, pq, desc(KVM_U * U, U));
        rs64_1(nm, pq + 4, desc(KVM_U * U + 2048, U));
        rs64_1(nm, pq + 8, desc(KVM_U * U + 4096, U));
        rs64_1(nm, q3, desc(KVM_U * U + 6144, U));
      }
      wg_commit();
#pragma unroll
      for (int m = 0; m < 8; m++) {
        const int w = m & 1;
        sg[m] = pack2(acc[64 + 2 * m] * (rs_[w] * sig_r(acc[64 + 2 * m], nrl[w])), acc[65 + 2 * m] * (rs_[w] * sig_r(acc[65 + 2 * m], nrl[w])));
      }
      pinr<8>(sg);
      wg_wait<0>();
      pin<32>(nm);
      LANE();
      float rd[4];
#pragma unroll
      for (int i = 0; i < 4; i++) rd[i] = rcp(__shfl_sync(0xffffffffu, nm[28 + i], ln & 28) + 1e-6f);
      uint32_t* op = reinterpret_cast<uint32_t*>(g_o + (size_t)(r * 128 + wg * 64 + w4 * 16 + g8) * DM + j * 56 + 2 * t4);
#pragma unroll
      for (int i = 0; i < 7; i++) {
        const bool h0 = i < 3 || (i == 3 && t4 < 2);
        const float ra = h0 ? rd[0] : rd[1], rb = h0 ? rd[2] : rd[3];
        op[4 * i] = pack2(nm[4 * i] * ra, nm[4 * i + 1] * ra);
        op[4 * i + 8 * (DM / 2)] = pack2(nm[4 * i + 2] * rb, nm[4 * i + 3] * rb);
      }
      __syncwarp();
      if (lane0) mbar_arrive(BAR(OST));
      CTS(7);
    }
    uint32_t hf[112];
    float a1[56];
    {
      float acc[80];
      pass1<3, 160>(acc, xf, sb, pb, lane0, [&](int) {});
      CTS(8);
#pragma unroll
      for (int s = 0; s < 4; s++) { lds4(hf + 4 * s, sb + hoff + s * 512); lds4(hf + 16 + 4 * s, sb + 4 * U + hoff + s * 512); }
      mbar_wait(BAR(FG + 0));
      wg_fence();
#pragma unroll
      for (int s = 0; s < 7; s++) rs<112>(a1, hf + 4 * s, desc(VA + s * 2048, 14336), s == 0);
      wg_commit();
      mbar_wait_cl(BAR(HF + 0) + wg * 8);
      mbar_wait_cl(BAR(HF + 2) + wg * 8);
#pragma unroll
      for (int s = 0; s < 4; s++) { lds4(hf + 56 + 4 * s, sb + 2 * U + hoff + s * 512); lds4(hf + 72 + 4 * s, sb + 6 * U + hoff + s * 512); }
      __syncwarp();
      if (lane0) mbar_arrive(BAR(LD1));
      mbar_wait(BAR(FG + 1));
      wg_fence();
#pragma unroll
      for (int s = 0; s < 7; s++) rs<112>(a1, hf + 56 + 4 * s, desc(VB + s * 2048, 14336), false);
      wg_commit();
      mbar_wait(BAR(EC + 6));
      RSD();
      hfrag64(hf + 32, acc, r2, nrl);
#pragma unroll
      for (int m = 0; m < 8; m++) {
        const int w = m & 1;
        hf[48 + m] = pack2(blo(sg[m]) * (acc[64 + 2 * m] * rs_[w]), bhi(sg[m]) * (acc[65 + 2 * m] * rs_[w]));
      }
      const uint32_t doff = (uint32_t)(wg * 12288 + w4 * 3072 + laneid() * 16);
#pragma unroll
      for (int s = 0; s < 6; s++) sts4(sb + 8 * U + doff + s * 512, hf + 32 + 4 * s);
      fence_async();
      mbar_wait_cl(BAR(PF + 2));
      __syncwarp();
      if (lane0) bulk_s2c(pb + 11 * U + doff, sb + 8 * U + doff, 3072, pb + MISC + 8u * (HF + 4) + wg * 8);
      CTS(9);
      wg_wait<1>();
      if (lane0) mbar_arrive(BAR(EG + 0));
      mbar_wait(BAR(FG + 2));
      wg_fence();
#pragma unroll
      for (int s = 0; s < 7; s++) rs<112>(a1, hf + 28 + 4 * s, desc(VC + s * 2048, 14336), false);
      wg_commit();
      wg_wait<1>();
      if (lane0) mbar_arrive(BAR(EG + 1));
      mbar_wait_cl(BAR(HF + 4) + wg * 8);
#pragma unroll
      for (int s = 0; s < 6; s++) lds4(hf + 88 + 4 * s, sb + 11 * U + doff + s * 512);
      __syncwarp();
      if (lane0) { mbar_arrive(BAR(LD2)); mbar_arrive_remote(pb + MISC + 8u * ACK); }
      mbar_wait(BAR(FG + 3));
      wg_fence();
#pragma unroll
      for (int s = 0; s < 7; s++) rs<112>(a1, hf + 84 + 4 * s, desc(VD + s * 2048, 14336), false);
      wg_commit();
      wg_wait<1>();
      if (lane0) mbar_arrive(BAR(EG + 2));
      CTS(10);
    }
    const uint32_t tag = 0x4000u | (ep & 0x1FFFu);
    const float tagf = __uint_as_float(tag << 16);
    uint4* pbase = g_p + (size_t)((r * 2 + n) * 4) * 3072 + wg * 512 + w4 * 32 + laneid();
    float a2[28];
    float* a3 = a1;
    float* aw = a2;
    mbar_wait(BAR(FG + 4));
    wg_fence();
#pragma unroll
    for (int s = 0; s < 14; s++) rs<56>(a2, hf + 4 * s, desc(VA + s * 2048, U), s == 0);
    wg_commit();
    wg_wait<1>();
    if (lane0) mbar_arrive(BAR(EG + 3));
    pin<56>(a1);
    {
      const int c = 2 * (1 - (kq >> 1));
      send_ll(pbase + c * 3072 + ((kq ^ c) - 1) * 1024, a1, tagf);
      send_ll(pbase + (c + 1) * 3072 + ((kq ^ (c + 1)) - 1) * 1024, a1 + 28, tagf);
    }
    mbar_wait(BAR(FG + 5));
    wg_fence();
#pragma unroll
    for (int s = 0; s < 14; s++) rs<56>(a2, hf + 56 + 4 * s, desc(VB + s * 2048, U), false);
    wg_commit();
    wg_wait<1>();
    if (lane0) mbar_arrive(BAR(EG + 4));
    mbar_wait(BAR(FG + 6));
    wg_fence();
#pragma unroll
    for (int s = 0; s < 14; s++) { if (s == 0) rs56_z(a3, hf, desc(VC, U)); else rs56_1(a3, hf + 4 * s, desc(VC + s * 2048, U)); }
    wg_commit();
    wg_wait<1>();
    if (lane0) mbar_arrive(BAR(EG + 5));
    pin<28>(a2);
    send_ll(pbase + (kq ^ 1) * 3072, a2, tagf);
    mbar_wait(BAR(FG + 7));
    wg_fence();
#pragma unroll
    for (int s = 0; s < 14; s++) rs<56>(a3, hf + 56 + 4 * s, desc(VD + s * 2048, U), false);
    wg_commit();
    CTS(11);
    const int row = r * 128 + wg * 64 + w4 * 16, col = n * 224 + kq * 56;
    uint32_t xr[14], v0[16], v1[16], v2[16];
    const uint4* pin_ = pbase + kq * 3072;
    const uint64_t adw = (uint64_t)(wg * 512);
#pragma unroll
    for (int t = 0; t < 7; t++) {
      mbar_wait(BAR(FO + t));
      if (t == 0) mbar_wait(BAR(FW + 0));
      if (t == 3) mbar_wait(BAR(FW + 1));
      wg_fence();
#pragma unroll
      for (int kk = 0; kk < 4; kk++) {
        const int s = 4 * t + kk;
        const uint64_t da = desc(t * 16384 + kk * 32, 16) + adw, db = desc((s < 14 ? VA + s * 2048 : VB + (s - 14) * 2048), U);
        if (s == 0) ss56_z(aw, da, db); else ss56_1(aw, da, db);
      }
      wg_commit();
      if (t == 1) {
        wg_wait<2>();
        pin<28>(a3);
        LANE();
        const uint32_t* xp = reinterpret_cast<const uint32_t*>(x + (size_t)(row + g8) * DM + col + 2 * t4);
#pragma unroll
        for (int q = 0; q < 4; q++) { ld_ll(v1 + 4 * q, pin_ + 1024 + q * 128); ld_ll(v2 + 4 * q, pin_ + 2048 + q * 128); }
#pragma unroll
        for (int i = 0; i < 7; i++) {
          asm volatile("ld.global.nc.b32 %0, [%1];" : "=r"(xr[2 * i]) : "l"(xp + 4 * i));
          asm volatile("ld.global.nc.b32 %0, [%1];" : "=r"(xr[2 * i + 1]) : "l"(xp + 4 * i + 8 * (DM / 2)));
        }
      }
      if (t == 4) {
#pragma unroll
        for (int q = 0; q < 4; q++) ld_ll(v0 + 4 * q, pin_ + q * 128);
      }
    }
    recv_ll(a3, v1, pin_ + 1024, tag);
    recv_ll(a3, v2, pin_ + 2048, tag);
    recv_ll(a3, v0, pin_, tag);
#pragma unroll
    for (int i = 0; i < 28; i++) a3[i] = a3[i] * sig_r(a3[i], -LOG2E);
    wg_wait<0>();
    pin<28>(aw);
    CTS(12);
    uint32_t ob[14];
#pragma unroll
    for (int m = 0; m < 14; m++) ob[m] = pack2(fmaf(aw[2 * m], a3[2 * m], blo(xr[m])), fmaf(aw[2 * m + 1], a3[2 * m + 1], bhi(xr[m])));
    const uint32_t stg = sb + wg * 8192 + w4 * 2048;
    LANE();
    const uint32_t sa = stg + (ln & 15) * 112 + (ln >> 4) * 16;
#pragma unroll
    for (int kk = 0; kk < 3; kk++) stsm4(sa + kk * 32, ob[4 * kk], ob[4 * kk + 1], ob[4 * kk + 2], ob[4 * kk + 3]);
    stsm2(stg + (ln & 15) * 112 + 96, ob[12], ob[13]);
    fence_async();
    __syncwarp();
    if (lane0) {
      tma2d_store(&M.out, col, row, stg);
      asm volatile("cp.async.bulk.commit_group;" ::: "memory");
      asm volatile("cp.async.bulk.wait_group.read 0;" ::: "memory");
    }
    CTS(13);
    if ((tid & 127) == 0) { GTS(wg, 30); TSDUMP(wg); }
  }
}

typedef CUresult (*EncodeFn)(CUtensorMap*, CUtensorMapDataType, cuuint32_t, void*, const cuuint64_t*, const cuuint64_t*, const cuuint32_t*,
                             const cuuint32_t*, CUtensorMapInterleave, CUtensorMapSwizzle, CUtensorMapL2promotion, CUtensorMapFloatOOBfill);

void make_map(EncodeFn enc, CUtensorMap* m, const void* base, uint64_t cols, uint64_t rows, uint32_t bc, uint32_t br, bool sw) {
  cuuint64_t dims[2] = {cols, rows}, str[1] = {cols * 2};
  cuuint32_t box[2] = {bc, br}, es[2] = {1, 1};
  enc(m, CU_TENSOR_MAP_DATA_TYPE_BFLOAT16, 2, const_cast<void*>(base), dims, str, box, es, CU_TENSOR_MAP_INTERLEAVE_NONE,
      sw ? CU_TENSOR_MAP_SWIZZLE_128B : CU_TENSOR_MAP_SWIZZLE_NONE, CU_TENSOR_MAP_L2_PROMOTION_L2_128B, CU_TENSOR_MAP_FLOAT_OOB_FILL_NONE);
}

}

extern "C" void kernel_launch(void* const* d_in, const int* in_sizes, int n_in, void* d_out, int out_size) {
  (void)in_sizes; (void)n_in; (void)out_size;
  void* fn = nullptr;
  cudaDriverEntryPointQueryResult q;
  cudaGetDriverEntryPoint("cuTensorMapEncodeTiled", &fn, cudaEnableDefault, &q);
  EncodeFn enc = (EncodeFn)fn;
  void* op = nullptr;
  cudaGetSymbolAddress(&op, g_o);
  Maps M;
  make_map(enc, &M.x, d_in[0], DM, SEQ, 64, 64, true);
  make_map(enc, &M.wqkv, d_in[1], 3 * DM, DM, 56, 64, true);
  make_map(enc, &M.w1a, d_in[4], FF, DM, 64, 64, true);
  make_map(enc, &M.w3a, d_in[5], FF, DM, 64, 64, true);
  make_map(enc, &M.w1b, d_in[4], FF, DM, 32, 64, true);
  make_map(enc, &M.w3b, d_in[5], FF, DM, 32, 64, true);
  make_map(enc, &M.w2a, d_in[6], DM, FF, 64, 112, true);
  make_map(enc, &M.w2b, d_in[6], DM, FF, 48, 112, true);
  make_map(enc, &M.w2c, d_in[6], DM, FF, 56, 224, true);
  make_map(enc, &M.wo, d_in[2], DM, DM, 56, 224, true);
  make_map(enc, &M.o, op, DM, SEQ, 64, 128, true);
  make_map(enc, &M.out, d_out, DM, SEQ, 56, 16, false);
  cudaFuncSetAttribute(fused_kernel, cudaFuncAttributeMaxDynamicSharedMemorySize, (int)SMEM_BYTES);
  fused_kernel<<<128, 384, SMEM_BYTES>>>(M, (const __nv_bfloat16*)d_in[0]);
}
```

```cpp
#include <cuda_runtime.h>
#include <cuda.h>
#include <cuda_bf16.h>
#include <stdint.h>

namespace {

constexpr int SEQ = 2048, DM = 448, FF = 1792;
constexpr uint32_t U = 8192;
constexpr uint32_t SM_BASE = 1024;
constexpr uint32_t MISC = 28 * U;
constexpr uint32_t SMEM_BYTES = 28 * U + 3072;
constexpr uint32_t KVM_U = 26;

enum : int { FA = 0, FB = 7, FC = 14, FD = 21, FT = 28, FW = 36, HF = 43, KVL = 49,
             LH0 = 50, LH1, EA1 = 52, EA2, EA4, EA5, EA6, EB1 = 57, EC0 = 63, ED1 = 70, ED2, ED4, ED5, ED6, ET = 75,
             PKST = 83, LD2, PF = 85, ACK = 88, XC0, XC1, KVST, OST = 92, KVM = 94, OFREE, XR, KVFREE, SR, NBAR = 99 };
constexpr int KVP = 36;
constexpr uint32_t KV_BYTES = 56 * KVP * 4;

struct Maps { CUtensorMap kv, wq, w1a, w3a, w1b, w3b, w2a, w2b, w2c, w2d, woa, wob, o, ost, outa, outb, xra, xrb; };

struct Ptrs { const __nv_bfloat16 *x, *wqkv, *wo, *w1, *w3, *w2; };

__device__ uint32_t g_epoch[128];
__device__ uint32_t g_f1[8 * 32];
__device__ uint32_t g_f2[16 * 32];
__device__ __align__(128) float g_kv[2 * 8 * 2048];
__device__ __nv_bfloat16 g_o[SEQ * DM];
__device__ uint4 g_p[16 * 2 * 4 * 3 * 1024];
#define TS(role, i)
#define GTS(role, i)
#define CTS(i)
#define TSDUMP(role)

__device__ __forceinline__ uint32_t smem_u32(const void* p) { return (uint32_t)__cvta_generic_to_shared(p); }
__device__ __forceinline__ void mbar_init(uint32_t bar, uint32_t cnt) { asm volatile("mbarrier.init.shared::cta.b64 [%0], %1;" ::"r"(bar), "r"(cnt) : "memory"); }
__device__ __forceinline__ void mbar_expect_tx(uint32_t bar, uint32_t bytes) { asm volatile("mbarrier.arrive.expect_tx.shared::cta.b64 _, [%0], %1;" ::"r"(bar), "r"(bytes) : "memory"); }
__device__ __forceinline__ void mbar_arrive_n(uint32_t bar, uint32_t n) { asm volatile("mbarrier.arrive.shared::cta.b64 _, [%0], %1;" ::"r"(bar), "r"(n) : "memory"); }
__device__ __forceinline__ void mbar_arrive(uint32_t bar) { asm volatile("mbarrier.arrive.shared::cta.b64 _, [%0];" ::"r"(bar) : "memory"); }
__device__ __forceinline__ void mbar_arrive_remote(uint32_t rbar) { asm volatile("mbarrier.arrive.shared::cluster.b64 _, [%0];" ::"r"(rbar) : "memory"); }
__device__ __forceinline__ void mbar_wait(uint32_t bar) {
  asm volatile("{ .reg .pred p; .reg .u32 n; mov.u32 n, 0;\n"
               "W_L: mbarrier.try_wait.parity.shared::cta.b64 p, [%0], 0;\n"
               "@p bra W_D;\n add.u32 n, n, 1;\n setp.lt.u32 p, n, 4194304;\n @p bra W_L;\n trap;\n W_D: }" ::"r"(bar) : "memory");
}
__device__ __forceinline__ void tma2d(uint32_t dst, const CUtensorMap* m, int c0, int c1, uint32_t bar) {
  asm volatile("cp.async.bulk.tensor.2d.shared::cluster.global.mbarrier::complete_tx::bytes [%0], [%1, {%3, %4}], [%2];" ::"r"(dst), "l"(m), "r"(bar), "r"(c0), "r"(c1) : "memory");
}
__device__ __forceinline__ void tma3d(uint32_t dst, const CUtensorMap* m, int c0, int c1, int c2, uint32_t bar) {
  asm volatile("cp.async.bulk.tensor.3d.shared::cluster.global.mbarrier::complete_tx::bytes [%0], [%1, {%3, %4, %5}], [%2];" ::"r"(dst), "l"(m), "r"(bar), "r"(c0), "r"(c1), "r"(c2) : "memory");
}
__device__ __forceinline__ void bulk_s2g(void* g, uint32_t src, uint32_t bytes) {
  asm volatile("cp.async.bulk.global.shared::cta.bulk_group [%0], [%1], %2;" ::"l"(g), "r"(src), "r"(bytes) : "memory");
}
__device__ __forceinline__ void bulk_commit() { asm volatile("cp.async.bulk.commit_group;" ::: "memory"); }
__device__ __forceinline__ void bulk_wait_read() { asm volatile("cp.async.bulk.wait_group.read 0;" ::: "memory"); }
__device__ __forceinline__ void bulk_wait_all() { asm volatile("cp.async.bulk.wait_group 0;" ::: "memory"); }
__device__ __forceinline__ void l2_prefetch(const void* g, uint32_t bytes) { asm volatile("cp.async.bulk.prefetch.L2.global [%0], %1;" ::"l"(g), "r"(bytes) : "memory"); }
__device__ __forceinline__ void map_prefetch(const CUtensorMap* m) { asm volatile("prefetch.tensormap [%0];" ::"l"(m) : "memory"); }
__device__ __forceinline__ void tma2d_store(const CUtensorMap* m, int c0, int c1, uint32_t src) {
  asm volatile("cp.async.bulk.tensor.2d.global.shared::cta.bulk_group [%0, {%2, %3}], [%1];" ::"l"(m), "r"(src), "r"(c0), "r"(c1) : "memory");
}
__device__ __forceinline__ void bulk_s2c(uint32_t rdst, uint32_t src, uint32_t bytes, uint32_t rbar) {
  asm volatile("cp.async.bulk.shared::cluster.shared::cta.mbarrier::complete_tx::bytes [%0], [%1], %2, [%3];" ::"r"(rdst), "r"(src), "r"(bytes), "r"(rbar) : "memory");
}
__device__ __forceinline__ uint32_t mapa(uint32_t a, uint32_t cta) { uint32_t r; asm volatile("mapa.shared::cluster.u32 %0, %1, %2;" : "=r"(r) : "r"(a), "r"(cta)); return r; }
__device__ __forceinline__ bool elect_one() { uint32_t p; asm volatile("{ .reg .pred P; elect.sync _|P, 0xffffffff; selp.u32 %0, 1, 0, P; }" : "=r"(p)); return p; }
__device__ __forceinline__ int laneid() { int l; asm volatile("mov.u32 %0, %%laneid;" : "=r"(l)); return l; }
__device__ __forceinline__ void fence_async() { asm volatile("fence.proxy.async.shared::cta;" ::: "memory"); }
__device__ __forceinline__ void wg_fence() { asm volatile("wgmma.fence.sync.aligned;" ::: "memory"); }
__device__ __forceinline__ void wg_commit() { asm volatile("wgmma.commit_group.sync.aligned;" ::: "memory"); }
template <int N> __device__ __forceinline__ void wg_wait() { asm volatile("wgmma.wait_group.sync.aligned %0;" ::"n"(N) : "memory"); }
template <int N> __device__ __forceinline__ void pin(float* a) {
#pragma unroll
  for (int i = 0; i < N; i++) asm volatile("" : "+f"(a[i])::"memory");
}
template <int N> __device__ __forceinline__ void pinr(uint32_t* a) {
#pragma unroll
  for (int i = 0; i < N; i++) asm volatile("" : "+r"(a[i])::"memory");
}
__device__ __forceinline__ void ldsm4(uint32_t* r, uint32_t a) { asm volatile("ldmatrix.sync.aligned.m8n8.x4.shared.b16 {%0,%1,%2,%3}, [%4];" : "=r"(r[0]), "=r"(r[1]), "=r"(r[2]), "=r"(r[3]) : "r"(a) : "memory"); }
__device__ __forceinline__ void stsm4(uint32_t a, uint32_t r0, uint32_t r1, uint32_t r2, uint32_t r3) { asm volatile("stmatrix.sync.aligned.m8n8.x4.shared.b16 [%0], {%1,%2,%3,%4};" ::"r"(a), "r"(r0), "r"(r1), "r"(r2), "r"(r3) : "memory"); }
__device__ __forceinline__ void stsm2(uint32_t a, uint32_t r0, uint32_t r1) { asm volatile("stmatrix.sync.aligned.m8n8.x2.shared.b16 [%0], {%1,%2};" ::"r"(a), "r"(r0), "r"(r1) : "memory"); }
__device__ __forceinline__ void sts4(uint32_t a, const uint32_t* r) { asm volatile("st.shared.v4.b32 [%0], {%1,%2,%3,%4};" ::"r"(a), "r"(r[0]), "r"(r[1]), "r"(r[2]), "r"(r[3]) : "memory"); }
__device__ __forceinline__ void lds4(uint32_t* r, uint32_t a) { asm volatile("ld.shared.v4.b32 {%0,%1,%2,%3}, [%4];" : "=r"(r[0]), "=r"(r[1]), "=r"(r[2]), "=r"(r[3]) : "r"(a) : "memory"); }
__device__ __forceinline__ uint32_t pack2(float lo, float hi) { uint32_t r; asm("cvt.rn.bf16x2.f32 %0, %1, %2;" : "=r"(r) : "f"(hi), "f"(lo)); return r; }
__device__ __forceinline__ float blo(uint32_t v) { return __uint_as_float(v << 16); }
__device__ __forceinline__ float bhi(uint32_t v) { return __uint_as_float(v & 0xFFFF0000u); }
__device__ __forceinline__ float ex2(float x) { float y; asm("ex2.approx.ftz.f32 %0, %1;" : "=f"(y) : "f"(x)); return y; }
__device__ __forceinline__ float rcp(float x) { float y; asm("rcp.approx.ftz.f32 %0, %1;" : "=f"(y) : "f"(x)); return y; }
__device__ __forceinline__ float sqrt_(float x) { float y; asm("sqrt.approx.ftz.f32 %0, %1;" : "=f"(y) : "f"(x)); return y; }
__device__ __forceinline__ void mma16816(float* c, const uint32_t* a, uint32_t b0, uint32_t b1) {
  asm volatile("mma.sync.aligned.m16n8k16.row.col.f32.bf16.bf16.f32 {%0,%1,%2,%3}, {%4,%5,%6,%7}, {%8,%9}, {%0,%1,%2,%3};"
               : "+f"(c[0]), "+f"(c[1]), "+f"(c[2]), "+f"(c[3]) : "r"(a[0]), "r"(a[1]), "r"(a[2]), "r"(a[3]), "r"(b0), "r"(b1));
}
__device__ __forceinline__ float tanh_(float x) { float y; asm("tanh.approx.f32 %0, %1;" : "=f"(y) : "f"(x)); return y; }
__device__ __forceinline__ float bfr(float x) { return __bfloat162float(__float2bfloat16_rn(x)); }
__device__ __forceinline__ uint32_t ld_acq(const uint32_t* p) { uint32_t v; asm volatile("ld.acquire.gpu.global.u32 %0, [%1];" : "=r"(v) : "l"(p) : "memory"); return v; }
__device__ __forceinline__ void poll_flag(const uint32_t* p, uint32_t target) {
  uint32_t n = 0;
  while ((int)(ld_acq(p) - target) < 0) { if (++n > (1u << 21)) asm volatile("trap;"); }
}
#define SIGNAL(p) asm volatile("red.relaxed.gpu.global.add.u32 [%0], 1;" ::"l"(p) : "memory")
__device__ __forceinline__ void ld_ll(uint32_t* r, const uint4* p) {
  asm volatile("{ .reg .b128 t; .reg .b64 lo, hi; ld.relaxed.gpu.global.b128 t, [%4]; mov.b128 {lo,hi}, t; mov.b64 {%0,%1}, lo; mov.b64 {%2,%3}, hi; }" : "=r"(r[0]), "=r"(r[1]), "=r"(r[2]), "=r"(r[3]) : "l"(p) : "memory");
}
__device__ __forceinline__ constexpr uint64_t desc(uint32_t off, uint32_t lbo) {
  return (uint64_t)((SM_BASE + off) >> 4) | ((uint64_t)(lbo >> 4) << 16) | ((uint64_t)64 << 32) | ((uint64_t)1 << 62);
}

__device__ __forceinline__ void rs120_0(float* d, const uint32_t* a, uint64_t db){
  asm volatile("{ .reg .pred p; setp.ne.b32 p, 0, 0; wgmma.mma_async.sync.aligned.m64n120k16.f32.bf16.bf16 {%0, %1, %2, %3, %4, %5, %6, %7, %8, %9, %10, %11, %12, %13, %14, %15, %16, %17, %18, %19, %20, %21, %22, %23, %24, %25, %26, %27, %28, %29, %30, %31, %32, %33, %34, %35, %36, %37, %38, %39, %40, %41, %42, %43, %44, %45, %46, %47, %48, %49, %50, %51, %52, %53, %54, %55, %56, %57, %58, %59}, {%60,%61,%62,%63}, %64, p, 1, 1, 1; }"
   : "=f"(d[0]), "=f"(d[1]), "=f"(d[2]), "=f"(d[3]), "=f"(d[4]), "=f"(d[5]), "=f"(d[6]), "=f"(d[7]), "=f"(d[8]), "=f"(d[9]), "=f"(d[10]), "=f"(d[11]), "=f"(d[12]), "=f"(d[13]), "=f"(d[14]), "=f"(d[15]), "=f"(d[16]), "=f"(d[17]), "=f"(d[18]), "=f"(d[19]), "=f"(d[20]), "=f"(d[21]), "=f"(d[22]), "=f"(d[23]), "=f"(d[24]), "=f"(d[25]), "=f"(d[26]), "=f"(d[27]), "=f"(d[28]), "=f"(d[29]), "=f"(d[30]), "=f"(d[31]), "=f"(d[32]), "=f"(d[33]), "=f"(d[34]), "=f"(d[35]), "=f"(d[36]), "=f"(d[37]), "=f"(d[38]), "=f"(d[39]), "=f"(d[40]), "=f"(d[41]), "=f"(d[42]), "=f"(d[43]), "=f"(d[44]), "=f"(d[45]), "=f"(d[46]), "=f"(d[47]), "=f"(d[48]), "=f"(d[49]), "=f"(d[50]), "=f"(d[51]), "=f"(d[52]), "=f"(d[53]), "=f"(d[54]), "=f"(d[55]), "=f"(d[56]), "=f"(d[57]), "=f"(d[58]), "=f"(d[59]) : "r"(a[0]),"r"(a[1]),"r"(a[2]),"r"(a[3]), "l"(db));
}
__device__ __forceinline__ void rs120_1(float* d, const uint32_t* a, uint64_t db){
  asm volatile("{ .reg .pred p; setp.ne.b32 p, 1, 0; wgmma.mma_async.sync.aligned.m64n120k16.f32.bf16.bf16 {%0, %1, %2, %3, %4, %5, %6, %7, %8, %9, %10, %11, %12, %13, %14, %15, %16, %17, %18, %19, %20, %21, %22, %23, %24, %25, %26, %27, %28, %29, %30, %31, %32, %33, %34, %35, %36, %37, %38, %39, %40, %41, %42, %43, %44, %45, %46, %47, %48, %49, %50, %51, %52, %53, %54, %55, %56, %57, %58, %59}, {%60,%61,%62,%63}, %64, p, 1, 1, 1; }"
   : "+f"(d[0]), "+f"(d[1]), "+f"(d[2]), "+f"(d[3]), "+f"(d[4]), "+f"(d[5]), "+f"(d[6]), "+f"(d[7]), "+f"(d[8]), "+f"(d[9]), "+f"(d[10]), "+f"(d[11]), "+f"(d[12]), "+f"(d[13]), "+f"(d[14]), "+f"(d[15]), "+f"(d[16]), "+f"(d[17]), "+f"(d[18]), "+f"(d[19]), "+f"(d[20]), "+f"(d[21]), "+f"(d[22]), "+f"(d[23]), "+f"(d[24]), "+f"(d[25]), "+f"(d[26]), "+f"(d[27]), "+f"(d[28]), "+f"(d[29]), "+f"(d[30]), "+f"(d[31]), "+f"(d[32]), "+f"(d[33]), "+f"(d[34]), "+f"(d[35]), "+f"(d[36]), "+f"(d[37]), "+f"(d[38]), "+f"(d[39]), "+f"(d[40]), "+f"(d[41]), "+f"(d[42]), "+f"(d[43]), "+f"(d[44]), "+f"(d[45]), "+f"(d[46]), "+f"(d[47]), "+f"(d[48]), "+f"(d[49]), "+f"(d[50]), "+f"(d[51]), "+f"(d[52]), "+f"(d[53]), "+f"(d[54]), "+f"(d[55]), "+f"(d[56]), "+f"(d[57]), "+f"(d[58]), "+f"(d[59]) : "r"(a[0]),"r"(a[1]),"r"(a[2]),"r"(a[3]), "l"(db));
}
__device__ __forceinline__ void rs128_0(float* d, const uint32_t* a, uint64_t db){
  asm volatile("{ .reg .pred p; setp.ne.b32 p, 0, 0; wgmma.mma_async.sync.aligned.m64n128k16.f32.bf16.bf16 {%0, %1, %2, %3, %4, %5, %6, %7, %8, %9, %10, %11, %12, %13, %14, %15, %16, %17, %18, %19, %20, %21, %22, %23, %24, %25, %26, %27, %28, %29, %30, %31, %32, %33, %34, %35, %36, %37, %38, %39, %40, %41, %42, %43, %44, %45, %46, %47, %48, %49, %50, %51, %52, %53, %54, %55, %56, %57, %58, %59, %60, %61, %62, %63}, {%64,%65,%66,%67}, %68, p, 1, 1, 1; }"
   : "=f"(d[0]), "=f"(d[1]), "=f"(d[2]), "=f"(d[3]), "=f"(d[4]), "=f"(d[5]), "=f"(d[6]), "=f"(d[7]), "=f"(d[8]), "=f"(d[9]), "=f"(d[10]), "=f"(d[11]), "=f"(d[12]), "=f"(d[13]), "=f"(d[14]), "=f"(d[15]), "=f"(d[16]), "=f"(d[17]), "=f"(d[18]), "=f"(d[19]), "=f"(d[20]), "=f"(d[21]), "=f"(d[22]), "=f"(d[23]), "=f"(d[24]), "=f"(d[25]), "=f"(d[26]), "=f"(d[27]), "=f"(d[28]), "=f"(d[29]), "=f"(d[30]), "=f"(d[31]), "=f"(d[32]), "=f"(d[33]), "=f"(d[34]), "=f"(d[35]), "=f"(d[36]), "=f"(d[37]), "=f"(d[38]), "=f"(d[39]), "=f"(d[40]), "=f"(d[41]), "=f"(d[42]), "=f"(d[43]), "=f"(d[44]), "=f"(d[45]), "=f"(d[46]), "=f"(d[47]), "=f"(d[48]), "=f"(d[49]), "=f"(d[50]), "=f"(d[51]), "=f"(d[52]), "=f"(d[53]), "=f"(d[54]), "=f"(d[55]), "=f"(d[56]), "=f"(d[57]), "=f"(d[58]), "=f"(d[59]), "=f"(d[60]), "=f"(d[61]), "=f"(d[62]), "=f"(d[63]) : "r"(a[0]),"r"(a[1]),"r"(a[2]),"r"(a[3]), "l"(db));
}
__device__ __forceinline__ void rs128_1(float* d, const uint32_t* a, uint64_t db){
  asm volatile("{ .reg .pred p; setp.ne.b32 p, 1, 0; wgmma.mma_async.sync.aligned.m64n128k16.f32.bf16.bf16 {%0, %1, %2, %3, %4, %5, %6, %7, %8, %9, %10, %11, %12, %13, %14, %15, %16, %17, %18, %19, %20, %21, %22, %23, %24, %25, %26, %27, %28, %29, %30, %31, %32, %33, %34, %35, %36, %37, %38, %39, %40, %41, %42, %43, %44, %45, %46, %47, %48, %49, %50, %51, %52, %53, %54, %55, %56, %57, %58, %59, %60, %61, %62, %63}, {%64,%65,%66,%67}, %68, p, 1, 1, 1; }"
   : "+f"(d[0]), "+f"(d[1]), "+f"(d[2]), "+f"(d[3]), "+f"(d[4]), "+f"(d[5]), "+f"(d[6]), "+f"(d[7]), "+f"(d[8]), "+f"(d[9]), "+f"(d[10]), "+f"(d[11]), "+f"(d[12]), "+f"(d[13]), "+f"(d[14]), "+f"(d[15]), "+f"(d[16]), "+f"(d[17]), "+f"(d[18]), "+f"(d[19]), "+f"(d[20]), "+f"(d[21]), "+f"(d[22]), "+f"(d[23]), "+f"(d[24]), "+f"(d[25]), "+f"(d[26]), "+f"(d[27]), "+f"(d[28]), "+f"(d[29]), "+f"(d[30]), "+f"(d[31]), "+f"(d[32]), "+f"(d[33]), "+f"(d[34]), "+f"(d[35]), "+f"(d[36]), "+f"(d[37]), "+f"(d[38]), "+f"(d[39]), "+f"(d[40]), "+f"(d[41]), "+f"(d[42]), "+f"(d[43]), "+f"(d[44]), "+f"(d[45]), "+f"(d[46]), "+f"(d[47]), "+f"(d[48]), "+f"(d[49]), "+f"(d[50]), "+f"(d[51]), "+f"(d[52]), "+f"(d[53]), "+f"(d[54]), "+f"(d[55]), "+f"(d[56]), "+f"(d[57]), "+f"(d[58]), "+f"(d[59]), "+f"(d[60]), "+f"(d[61]), "+f"(d[62]), "+f"(d[63]) : "r"(a[0]),"r"(a[1]),"r"(a[2]),"r"(a[3]), "l"(db));
}
__device__ __forceinline__ void rs160_0(float* d, const uint32_t* a, uint64_t db){
  asm volatile("{ .reg .pred p; setp.ne.b32 p, 0, 0; wgmma.mma_async.sync.aligned.m64n160k16.f32.bf16.bf16 {%0, %1, %2, %3, %4, %5, %6, %7, %8, %9, %10, %11, %12, %13, %14, %15, %16, %17, %18, %19, %20, %21, %22, %23, %24, %25, %26, %27, %28, %29, %30, %31, %32, %33, %34, %35, %36, %37, %38, %39, %40, %41, %42, %43, %44, %45, %46, %47, %48, %49, %50, %51, %52, %53, %54, %55, %56, %57, %58, %59, %60, %61, %62, %63, %64, %65, %66, %67, %68, %69, %70, %71, %72, %73, %74, %75, %76, %77, %78, %79}, {%80,%81,%82,%83}, %84, p, 1, 1, 1; }"
   : "=f"(d[0]), "=f"(d[1]), "=f"(d[2]), "=f"(d[3]), "=f"(d[4]), "=f"(d[5]), "=f"(d[6]), "=f"(d[7]), "=f"(d[8]), "=f"(d[9]), "=f"(d[10]), "=f"(d[11]), "=f"(d[12]), "=f"(d[13]), "=f"(d[14]), "=f"(d[15]), "=f"(d[16]), "=f"(d[17]), "=f"(d[18]), "=f"(d[19]), "=f"(d[20]), "=f"(d[21]), "=f"(d[22]), "=f"(d[23]), "=f"(d[24]), "=f"(d[25]), "=f"(d[26]), "=f"(d[27]), "=f"(d[28]), "=f"(d[29]), "=f"(d[30]), "=f"(d[31]), "=f"(d[32]), "=f"(d[33]), "=f"(d[34]), "=f"(d[35]), "=f"(d[36]), "=f"(d[37]), "=f"(d[38]), "=f"(d[39]), "=f"(d[40]), "=f"(d[41]), "=f"(d[42]), "=f"(d[43]), "=f"(d[44]), "=f"(d[45]), "=f"(d[46]), "=f"(d[47]), "=f"(d[48]), "=f"(d[49]), "=f"(d[50]), "=f"(d[51]), "=f"(d[52]), "=f"(d[53]), "=f"(d[54]), "=f"(d[55]), "=f"(d[56]), "=f"(d[57]), "=f"(d[58]), "=f"(d[59]), "=f"(d[60]), "=f"(d[61]), "=f"(d[62]), "=f"(d[63]), "=f"(d[64]), "=f"(d[65]), "=f"(d[66]), "=f"(d[67]), "=f"(d[68]), "=f"(d[69]), "=f"(d[70]), "=f"(d[71]), "=f"(d[72]), "=f"(d[73]), "=f"(d[74]), "=f"(d[75]), "=f"(d[76]), "=f"(d[77]), "=f"(d[78]), "=f"(d[79]) : "r"(a[0]),"r"(a[1]),"r"(a[2]),"r"(a[3]), "l"(db));
}
__device__ __forceinline__ void rs160_1(float* d, const uint32_t* a, uint64_t db){
  asm volatile("{ .reg .pred p; setp.ne.b32 p, 1, 0; wgmma.mma_async.sync.aligned.m64n160k16.f32.bf16.bf16 {%0, %1, %2, %3, %4, %5, %6, %7, %8, %9, %10, %11, %12, %13, %14, %15, %16, %17, %18, %19, %20, %21, %22, %23, %24, %25, %26, %27, %28, %29, %30, %31, %32, %33, %34, %35, %36, %37, %38, %39, %40, %41, %42, %43, %44, %45, %46, %47, %48, %49, %50, %51, %52, %53, %54, %55, %56, %57, %58, %59, %60, %61, %62, %63, %64, %65, %66, %67, %68, %69, %70, %71, %72, %73, %74, %75, %76, %77, %78, %79}, {%80,%81,%82,%83}, %84, p, 1, 1, 1; }"
   : "+f"(d[0]), "+f"(d[1]), "+f"(d[2]), "+f"(d[3]), "+f"(d[4]), "+f"(d[5]), "+f"(d[6]), "+f"(d[7]), "+f"(d[8]), "+f"(d[9]), "+f"(d[10]), "+f"(d[11]), "+f"(d[12]), "+f"(d[13]), "+f"(d[14]), "+f"(d[15]), "+f"(d[16]), "+f"(d[17]), "+f"(d[18]), "+f"(d[19]), "+f"(d[20]), "+f"(d[21]), "+f"(d[22]), "+f"(d[23]), "+f"(d[24]), "+f"(d[25]), "+f"(d[26]), "+f"(d[27]), "+f"(d[28]), "+f"(d[29]), "+f"(d[30]), "+f"(d[31]), "+f"(d[32]), "+f"(d[33]), "+f"(d[34]), "+f"(d[35]), "+f"(d[36]), "+f"(d[37]), "+f"(d[38]), "+f"(d[39]), "+f"(d[40]), "+f"(d[41]), "+f"(d[42]), "+f"(d[43]), "+f"(d[44]), "+f"(d[45]), "+f"(d[46]), "+f"(d[47]), "+f"(d[48]), "+f"(d[49]), "+f"(d[50]), "+f"(d[51]), "+f"(d[52]), "+f"(d[53]), "+f"(d[54]), "+f"(d[55]), "+f"(d[56]), "+f"(d[57]), "+f"(d[58]), "+f"(d[59]), "+f"(d[60]), "+f"(d[61]), "+f"(d[62]), "+f"(d[63]), "+f"(d[64]), "+f"(d[65]), "+f"(d[66]), "+f"(d[67]), "+f"(d[68]), "+f"(d[69]), "+f"(d[70]), "+f"(d[71]), "+f"(d[72]), "+f"(d[73]), "+f"(d[74]), "+f"(d[75]), "+f"(d[76]), "+f"(d[77]), "+f"(d[78]), "+f"(d[79]) : "r"(a[0]),"r"(a[1]),"r"(a[2]),"r"(a[3]), "l"(db));
}
__device__ __forceinline__ void rs64_0(float* d, const uint32_t* a, uint64_t db){
  asm volatile("{ .reg .pred p; setp.ne.b32 p, 0, 0; wgmma.mma_async.sync.aligned.m64n64k16.f32.bf16.bf16 {%0, %1, %2, %3, %4, %5, %6, %7, %8, %9, %10, %11, %12, %13, %14, %15, %16, %17, %18, %19, %20, %21, %22, %23, %24, %25, %26, %27, %28, %29, %30, %31}, {%32,%33,%34,%35}, %36, p, 1, 1, 1; }"
   : "=f"(d[0]), "=f"(d[1]), "=f"(d[2]), "=f"(d[3]), "=f"(d[4]), "=f"(d[5]), "=f"(d[6]), "=f"(d[7]), "=f"(d[8]), "=f"(d[9]), "=f"(d[10]), "=f"(d[11]), "=f"(d[12]), "=f"(d[13]), "=f"(d[14]), "=f"(d[15]), "=f"(d[16]), "=f"(d[17]), "=f"(d[18]), "=f"(d[19]), "=f"(d[20]), "=f"(d[21]), "=f"(d[22]), "=f"(d[23]), "=f"(d[24]), "=f"(d[25]), "=f"(d[26]), "=f"(d[27]), "=f"(d[28]), "=f"(d[29]), "=f"(d[30]), "=f"(d[31]) : "r"(a[0]),"r"(a[1]),"r"(a[2]),"r"(a[3]), "l"(db));
}
__device__ __forceinline__ void rs64_1(float* d, const uint32_t* a, uint64_t db){
  asm volatile("{ .reg .pred p; setp.ne.b32 p, 1, 0; wgmma.mma_async.sync.aligned.m64n64k16.f32.bf16.bf16 {%0, %1, %2, %3, %4, %5, %6, %7, %8, %9, %10, %11, %12, %13, %14, %15, %16, %17, %18, %19, %20, %21, %22, %23, %24, %25, %26, %27, %28, %29, %30, %31}, {%32,%33,%34,%35}, %36, p, 1, 1, 1; }"
   : "+f"(d[0]), "+f"(d[1]), "+f"(d[2]), "+f"(d[3]), "+f"(d[4]), "+f"(d[5]), "+f"(d[6]), "+f"(d[7]), "+f"(d[8]), "+f"(d[9]), "+f"(d[10]), "+f"(d[11]), "+f"(d[12]), "+f"(d[13]), "+f"(d[14]), "+f"(d[15]), "+f"(d[16]), "+f"(d[17]), "+f"(d[18]), "+f"(d[19]), "+f"(d[20]), "+f"(d[21]), "+f"(d[22]), "+f"(d[23]), "+f"(d[24]), "+f"(d[25]), "+f"(d[26]), "+f"(d[27]), "+f"(d[28]), "+f"(d[29]), "+f"(d[30]), "+f"(d[31]) : "r"(a[0]),"r"(a[1]),"r"(a[2]),"r"(a[3]), "l"(db));
}
__device__ __forceinline__ void rs56_0(float* d, const uint32_t* a, uint64_t db){
  asm volatile("{ .reg .pred p; setp.ne.b32 p, 0, 0; wgmma.mma_async.sync.aligned.m64n56k16.f32.bf16.bf16 {%0, %1, %2, %3, %4, %5, %6, %7, %8, %9, %10, %11, %12, %13, %14, %15, %16, %17, %18, %19, %20, %21, %22, %23, %24, %25, %26, %27}, {%28,%29,%30,%31}, %32, p, 1, 1, 1; }"
   : "=f"(d[0]), "=f"(d[1]), "=f"(d[2]), "=f"(d[3]), "=f"(d[4]), "=f"(d[5]), "=f"(d[6]), "=f"(d[7]), "=f"(d[8]), "=f"(d[9]), "=f"(d[10]), "=f"(d[11]), "=f"(d[12]), "=f"(d[13]), "=f"(d[14]), "=f"(d[15]), "=f"(d[16]), "=f"(d[17]), "=f"(d[18]), "=f"(d[19]), "=f"(d[20]), "=f"(d[21]), "=f"(d[22]), "=f"(d[23]), "=f"(d[24]), "=f"(d[25]), "=f"(d[26]), "=f"(d[27]) : "r"(a[0]),"r"(a[1]),"r"(a[2]),"r"(a[3]), "l"(db));
}
__device__ __forceinline__ void rs56_1(float* d, const uint32_t* a, uint64_t db){
  asm volatile("{ .reg .pred p; setp.ne.b32 p, 1, 0; wgmma.mma_async.sync.aligned.m64n56k16.f32.bf16.bf16 {%0, %1, %2, %3, %4, %5, %6, %7, %8, %9, %10, %11, %12, %13, %14, %15, %16, %17, %18, %19, %20, %21, %22, %23, %24, %25, %26, %27}, {%28,%29,%30,%31}, %32, p, 1, 1, 1; }"
   : "+f"(d[0]), "+f"(d[1]), "+f"(d[2]), "+f"(d[3]), "+f"(d[4]), "+f"(d[5]), "+f"(d[6]), "+f"(d[7]), "+f"(d[8]), "+f"(d[9]), "+f"(d[10]), "+f"(d[11]), "+f"(d[12]), "+f"(d[13]), "+f"(d[14]), "+f"(d[15]), "+f"(d[16]), "+f"(d[17]), "+f"(d[18]), "+f"(d[19]), "+f"(d[20]), "+f"(d[21]), "+f"(d[22]), "+f"(d[23]), "+f"(d[24]), "+f"(d[25]), "+f"(d[26]), "+f"(d[27]) : "r"(a[0]),"r"(a[1]),"r"(a[2]),"r"(a[3]), "l"(db));
}
__device__ __forceinline__ void rs32_0(float* d, const uint32_t* a, uint64_t db){
  asm volatile("{ .reg .pred p; setp.ne.b32 p, 0, 0; wgmma.mma_async.sync.aligned.m64n32k16.f32.bf16.bf16 {%0, %1, %2, %3, %4, %5, %6, %7, %8, %9, %10, %11, %12, %13, %14, %15}, {%16,%17,%18,%19}, %20, p, 1, 1, 1; }"
   : "=f"(d[0]), "=f"(d[1]), "=f"(d[2]), "=f"(d[3]), "=f"(d[4]), "=f"(d[5]), "=f"(d[6]), "=f"(d[7]), "=f"(d[8]), "=f"(d[9]), "=f"(d[10]), "=f"(d[11]), "=f"(d[12]), "=f"(d[13]), "=f"(d[14]), "=f"(d[15]) : "r"(a[0]),"r"(a[1]),"r"(a[2]),"r"(a[3]), "l"(db));
}
__device__ __forceinline__ void rs32_1(float* d, const uint32_t* a, uint64_t db){
  asm volatile("{ .reg .pred p; setp.ne.b32 p, 1, 0; wgmma.mma_async.sync.aligned.m64n32k16.f32.bf16.bf16 {%0, %1, %2, %3, %4, %5, %6, %7, %8, %9, %10, %11, %12, %13, %14, %15}, {%16,%17,%18,%19}, %20, p, 1, 1, 1; }"
   : "+f"(d[0]), "+f"(d[1]), "+f"(d[2]), "+f"(d[3]), "+f"(d[4]), "+f"(d[5]), "+f"(d[6]), "+f"(d[7]), "+f"(d[8]), "+f"(d[9]), "+f"(d[10]), "+f"(d[11]), "+f"(d[12]), "+f"(d[13]), "+f"(d[14]), "+f"(d[15]) : "r"(a[0]),"r"(a[1]),"r"(a[2]),"r"(a[3]), "l"(db));
}
__device__ __forceinline__ void ss64_0(float* d, uint64_t da, uint64_t db){
  asm volatile("{ .reg .pred p; setp.ne.b32 p, 0, 0; wgmma.mma_async.sync.aligned.m64n64k16.f32.bf16.bf16 {%0, %1, %2, %3, %4, %5, %6, %7, %8, %9, %10, %11, %12, %13, %14, %15, %16, %17, %18, %19, %20, %21, %22, %23, %24, %25, %26, %27, %28, %29, %30, %31}, %32, %33, p, 1, 1, 1, 1; }"
   : "=f"(d[0]), "=f"(d[1]), "=f"(d[2]), "=f"(d[3]), "=f"(d[4]), "=f"(d[5]), "=f"(d[6]), "=f"(d[7]), "=f"(d[8]), "=f"(d[9]), "=f"(d[10]), "=f"(d[11]), "=f"(d[12]), "=f"(d[13]), "=f"(d[14]), "=f"(d[15]), "=f"(d[16]), "=f"(d[17]), "=f"(d[18]), "=f"(d[19]), "=f"(d[20]), "=f"(d[21]), "=f"(d[22]), "=f"(d[23]), "=f"(d[24]), "=f"(d[25]), "=f"(d[26]), "=f"(d[27]), "=f"(d[28]), "=f"(d[29]), "=f"(d[30]), "=f"(d[31]) : "l"(da), "l"(db));
}
__device__ __forceinline__ void ss64_1(float* d, uint64_t da, uint64_t db){
  asm volatile("{ .reg .pred p; setp.ne.b32 p, 1, 0; wgmma.mma_async.sync.aligned.m64n64k16.f32.bf16.bf16 {%0, %1, %2, %3, %4, %5, %6, %7, %8, %9, %10, %11, %12, %13, %14, %15, %16, %17, %18, %19, %20, %21, %22, %23, %24, %25, %26, %27, %28, %29, %30, %31}, %32, %33, p, 1, 1, 1, 1; }"
   : "+f"(d[0]), "+f"(d[1]), "+f"(d[2]), "+f"(d[3]), "+f"(d[4]), "+f"(d[5]), "+f"(d[6]), "+f"(d[7]), "+f"(d[8]), "+f"(d[9]), "+f"(d[10]), "+f"(d[11]), "+f"(d[12]), "+f"(d[13]), "+f"(d[14]), "+f"(d[15]), "+f"(d[16]), "+f"(d[17]), "+f"(d[18]), "+f"(d[19]), "+f"(d[20]), "+f"(d[21]), "+f"(d[22]), "+f"(d[23]), "+f"(d[24]), "+f"(d[25]), "+f"(d[26]), "+f"(d[27]), "+f"(d[28]), "+f"(d[29]), "+f"(d[30]), "+f"(d[31]) : "l"(da), "l"(db));
}
__device__ __forceinline__ void rs64_z(float* d, const uint32_t* a, uint64_t db){
  asm volatile("{ .reg .pred p; setp.ne.b32 p, 0, 0; wgmma.mma_async.sync.aligned.m64n64k16.f32.bf16.bf16 {%0, %1, %2, %3, %4, %5, %6, %7, %8, %9, %10, %11, %12, %13, %14, %15, %16, %17, %18, %19, %20, %21, %22, %23, %24, %25, %26, %27, %28, %29, %30, %31}, {%32,%33,%34,%35}, %36, p, 1, 1, 1; }"
   : "+f"(d[0]), "+f"(d[1]), "+f"(d[2]), "+f"(d[3]), "+f"(d[4]), "+f"(d[5]), "+f"(d[6]), "+f"(d[7]), "+f"(d[8]), "+f"(d[9]), "+f"(d[10]), "+f"(d[11]), "+f"(d[12]), "+f"(d[13]), "+f"(d[14]), "+f"(d[15]), "+f"(d[16]), "+f"(d[17]), "+f"(d[18]), "+f"(d[19]), "+f"(d[20]), "+f"(d[21]), "+f"(d[22]), "+f"(d[23]), "+f"(d[24]), "+f"(d[25]), "+f"(d[26]), "+f"(d[27]), "+f"(d[28]), "+f"(d[29]), "+f"(d[30]), "+f"(d[31]) : "r"(a[0]),"r"(a[1]),"r"(a[2]),"r"(a[3]), "l"(db));
}
__device__ __forceinline__ void rs32_z(float* d, const uint32_t* a, uint64_t db){
  asm volatile("{ .reg .pred p; setp.ne.b32 p, 0, 0; wgmma.mma_async.sync.aligned.m64n32k16.f32.bf16.bf16 {%0, %1, %2, %3, %4, %5, %6, %7, %8, %9, %10, %11, %12, %13, %14, %15}, {%16,%17,%18,%19}, %20, p, 1, 1, 1; }"
   : "+f"(d[0]), "+f"(d[1]), "+f"(d[2]), "+f"(d[3]), "+f"(d[4]), "+f"(d[5]), "+f"(d[6]), "+f"(d[7]), "+f"(d[8]), "+f"(d[9]), "+f"(d[10]), "+f"(d[11]), "+f"(d[12]), "+f"(d[13]), "+f"(d[14]), "+f"(d[15]) : "r"(a[0]),"r"(a[1]),"r"(a[2]),"r"(a[3]), "l"(db));
}
__device__ __forceinline__ void sk64_0(float* d, uint64_t da, uint64_t db){
  asm volatile("{ .reg .pred p; setp.ne.b32 p, 0, 0; wgmma.mma_async.sync.aligned.m64n64k16.f32.bf16.bf16 {%0, %1, %2, %3, %4, %5, %6, %7, %8, %9, %10, %11, %12, %13, %14, %15, %16, %17, %18, %19, %20, %21, %22, %23, %24, %25, %26, %27, %28, %29, %30, %31}, %32, %33, p, 1, 1, 0, 1; }"
   : "=f"(d[0]), "=f"(d[1]), "=f"(d[2]), "=f"(d[3]), "=f"(d[4]), "=f"(d[5]), "=f"(d[6]), "=f"(d[7]), "=f"(d[8]), "=f"(d[9]), "=f"(d[10]), "=f"(d[11]), "=f"(d[12]), "=f"(d[13]), "=f"(d[14]), "=f"(d[15]), "=f"(d[16]), "=f"(d[17]), "=f"(d[18]), "=f"(d[19]), "=f"(d[20]), "=f"(d[21]), "=f"(d[22]), "=f"(d[23]), "=f"(d[24]), "=f"(d[25]), "=f"(d[26]), "=f"(d[27]), "=f"(d[28]), "=f"(d[29]), "=f"(d[30]), "=f"(d[31]) : "l"(da), "l"(db));
}
__device__ __forceinline__ void sk64_1(float* d, uint64_t da, uint64_t db){
  asm volatile("{ .reg .pred p; setp.ne.b32 p, 1, 0; wgmma.mma_async.sync.aligned.m64n64k16.f32.bf16.bf16 {%0, %1, %2, %3, %4, %5, %6, %7, %8, %9, %10, %11, %12, %13, %14, %15, %16, %17, %18, %19, %20, %21, %22, %23, %24, %25, %26, %27, %28, %29, %30, %31}, %32, %33, p, 1, 1, 0, 1; }"
   : "+f"(d[0]), "+f"(d[1]), "+f"(d[2]), "+f"(d[3]), "+f"(d[4]), "+f"(d[5]), "+f"(d[6]), "+f"(d[7]), "+f"(d[8]), "+f"(d[9]), "+f"(d[10]), "+f"(d[11]), "+f"(d[12]), "+f"(d[13]), "+f"(d[14]), "+f"(d[15]), "+f"(d[16]), "+f"(d[17]), "+f"(d[18]), "+f"(d[19]), "+f"(d[20]), "+f"(d[21]), "+f"(d[22]), "+f"(d[23]), "+f"(d[24]), "+f"(d[25]), "+f"(d[26]), "+f"(d[27]), "+f"(d[28]), "+f"(d[29]), "+f"(d[30]), "+f"(d[31]) : "l"(da), "l"(db));
}
__device__ __forceinline__ void sk32_0(float* d, uint64_t da, uint64_t db){
  asm volatile("{ .reg .pred p; setp.ne.b32 p, 0, 0; wgmma.mma_async.sync.aligned.m64n32k16.f32.bf16.bf16 {%0, %1, %2, %3, %4, %5, %6, %7, %8, %9, %10, %11, %12, %13, %14, %15}, %16, %17, p, 1, 1, 0, 1; }"
   : "=f"(d[0]), "=f"(d[1]), "=f"(d[2]), "=f"(d[3]), "=f"(d[4]), "=f"(d[5]), "=f"(d[6]), "=f"(d[7]), "=f"(d[8]), "=f"(d[9]), "=f"(d[10]), "=f"(d[11]), "=f"(d[12]), "=f"(d[13]), "=f"(d[14]), "=f"(d[15]) : "l"(da), "l"(db));
}
__device__ __forceinline__ void sk32_1(float* d, uint64_t da, uint64_t db){
  asm volatile("{ .reg .pred p; setp.ne.b32 p, 1, 0; wgmma.mma_async.sync.aligned.m64n32k16.f32.bf16.bf16 {%0, %1, %2, %3, %4, %5, %6, %7, %8, %9, %10, %11, %12, %13, %14, %15}, %16, %17, p, 1, 1, 0, 1; }"
   : "+f"(d[0]), "+f"(d[1]), "+f"(d[2]), "+f"(d[3]), "+f"(d[4]), "+f"(d[5]), "+f"(d[6]), "+f"(d[7]), "+f"(d[8]), "+f"(d[9]), "+f"(d[10]), "+f"(d[11]), "+f"(d[12]), "+f"(d[13]), "+f"(d[14]), "+f"(d[15]) : "l"(da), "l"(db));
}
template<int N> __device__ __forceinline__ void rsz(float* d, const uint32_t* a, uint64_t db){
  if constexpr (N==64) rs64_z(d,a,db); else rs32_z(d,a,db);
}
template<int N> __device__ __forceinline__ void ssk(float* d, uint64_t da, uint64_t db, bool first){
  if constexpr (N==64) { if(first) sk64_0(d,da,db); else sk64_1(d,da,db); } else { if(first) sk32_0(d,da,db); else sk32_1(d,da,db); }
}
template<int N> __device__ __forceinline__ void rs(float* d, const uint32_t* a, uint64_t db, bool first){
  if constexpr (N==120) { if(first) rs120_0(d,a,db); else rs120_1(d,a,db); }
  if constexpr (N==128) { if(first) rs128_0(d,a,db); else rs128_1(d,a,db); }
  if constexpr (N==160) { if(first) rs160_0(d,a,db); else rs160_1(d,a,db); }
  if constexpr (N==64) { if(first) rs64_0(d,a,db); else rs64_1(d,a,db); }
  if constexpr (N==56) { if(first) rs56_0(d,a,db); else rs56_1(d,a,db); }
  if constexpr (N==32) { if(first) rs32_0(d,a,db); else rs32_1(d,a,db); }
}

constexpr float LOG2E = 1.4426950408889634f;
#define EPI_TS(x) x
#define TS7(i)
#define BAR(i) (sb + MISC + 8u * (uint32_t)(i))
#define BBARI(k) asm volatile("{ .reg .pred p; setp.ne.u32 p, %0, %1; @p bra B_L; trap; B_L: }" ::"r"(sb), "n"(k) : "memory")
#define BBAR() asm volatile("{ .reg .pred p; setp.ne.u32 p, %0, %1; @p bra B_L; trap; B_L: }" ::"r"(sb), "n"(__LINE__ * 2 + 1) : "memory")

__host__ __device__ constexpr int unitB(int g) { return g == 0 ? 0 : g == 1 ? 3 : g == 6 ? 8 : 14 + 3 * (g - 2); }
__host__ __device__ constexpr int unitC(int g) { return g == 0 ? 11 : g == 1 ? 5 : g == 6 ? 8 : 14 + 3 * (g - 2); }
__host__ __device__ constexpr int unitD(int g) { return g == 0 ? 11 : 14 + 3 * ((g - 1) & 3); }
__host__ __device__ constexpr int depB(int g) { return g < 2 ? XC0 : g == 2 ? EA1 : g == 3 ? EA2 : g == 4 ? EA4 : g == 5 ? EA5 : KVST; }
__host__ __device__ constexpr int depC(int g) { return g == 0 ? KVFREE : EB1 + g - 1; }
__host__ __device__ constexpr int depD(int g) { return g == 0 ? EC0 : g < 5 ? EC0 + g + 1 : g == 5 ? ED1 : ED2; }
__host__ __device__ constexpr int eid(int P, int g) {
  return P == 0 ? (g == 1 ? EA1 : g == 2 ? EA2 : g >= 4 ? EA4 + g - 4 : -1)
       : P == 1 ? (g >= 1 ? EB1 + g - 1 : -1)
       : P == 2 ? EC0 + g
                : (g == 1 ? ED1 : g == 2 ? ED2 : g >= 4 ? ED4 + g - 4 : -1);
}
template <int P> __host__ __device__ constexpr int unitP(int g) { return P == 0 ? 14 + 2 * g : P == 1 ? unitB(g) : P == 2 ? unitC(g) : unitD(g); }
template <typename Fn> __host__ __device__ constexpr uint64_t packtab(Fn f) { uint64_t t = 0; for (int g = 0; g < 7; g++) t |= (uint64_t)f(g) << (8 * g); return t; }

template <int P, int N, typename Fn, typename Fp>
__device__ __forceinline__ void pass1(float* acc, const uint32_t* xf, uint32_t sb, uint32_t pb, bool lane0, uint64_t sh, Fn shadow, Fp post) {
#pragma unroll
  for (int g = 0; g < 7; g++) {
    mbar_wait(BAR(FA + 7 * P + g));
    wg_fence();
#pragma unroll
    for (int kk = 0; kk < 4; kk++) {
      if (P == 1) {
        rs<128>(acc, xf + 16 * g + 4 * kk, desc(unitP<P>(g) * U + kk * 2048, U), g == 0 && kk == 0);
        rs<56>(acc + 64, xf + 16 * g + 4 * kk, desc((unitP<P>(g) + 2) * U + kk * 2048, U) + sh, g == 0 && kk == 0);
      } else {
        rs<N>(acc, xf + 16 * g + 4 * kk, desc(unitP<P>(g) * U + kk * 2048, U) + (P == 0 ? sh : 0), g == 0 && kk == 0);
      }
    }
    wg_commit();
    shadow(g);
    if (g > 0) {
      wg_wait<1>();
      if (lane0) {
        if (eid(P, g - 1) >= 0) mbar_arrive(BAR(eid(P, g - 1)));
        if ((P == 1 || P == 2) && g == 2) mbar_arrive_remote(pb + MISC + 8u * (PF + P - 1));
        if (P == 3 && g == 1) mbar_arrive_remote(pb + MISC + 8u * (PF + 2));
      }
      post(g);
    }
  }
  wg_wait<0>();
  if (lane0) mbar_arrive(BAR(eid(P, 6)));
  pin<N / 2>(acc);
}

template <int ID> __device__ __forceinline__ void hfrag64(uint32_t* h, float* acc, const float* rs_, uint32_t sb, int wg) {
  const float hr[2] = {0.5f * rs_[0], 0.5f * rs_[1]};
#pragma unroll
  for (int i = 0; i < 32; i++) {
    acc[32 + i] *= acc[i];
    acc[i] *= hr[(i >> 1) & 1];
    if (i < 16) acc[i] = tanh_(acc[i]);
  }
  pin<64>(acc);
  BBARI(ID * 4 + 1);
  EPI_TS(if (ID == 1) CTS(21));
  const float c[2] = {hr[0] * rs_[0], hr[1] * rs_[1]};
#pragma unroll
  for (int i = 16; i < 32; i++) acc[i] = tanh_(acc[i]);
#pragma unroll
  for (int m = 0; m < 8; m++) h[m] = pack2(acc[32 + 2 * m] * fmaf(acc[2 * m], c[m & 1], c[m & 1]), acc[33 + 2 * m] * fmaf(acc[2 * m + 1], c[m & 1], c[m & 1]));
  pin<16>(acc + 16);
  pinr<8>(h);
  BBARI(ID * 4 + 3);
  EPI_TS(if (ID == 1) CTS(22));
#pragma unroll
  for (int m = 8; m < 16; m++) h[m] = pack2(acc[32 + 2 * m] * fmaf(acc[2 * m], c[m & 1], c[m & 1]), acc[33 + 2 * m] * fmaf(acc[2 * m + 1], c[m & 1], c[m & 1]));
}
__device__ __forceinline__ void phi1(float* e, float* a, const float* rs_) {
  const float rl[2] = {rs_[0] * (0.5f * LOG2E), rs_[1] * (0.5f * LOG2E)};
#pragma unroll
  for (int i = 0; i < 28; i++) {
    const float u = a[i] * rl[(i >> 1) & 1];
    e[i] = ex2(u - fabsf(u));
    a[i] = fmaf(u + fabsf(u), 0.6931471805599453f, 1e-6f);
  }
  pin<28>(e);
  pin<28>(a);
}

template <int NP> __device__ __forceinline__ void stage_ll(uint32_t dst, const float* a, uint32_t par) {
#pragma unroll
  for (int q = 0; q < NP; q++) {
    const uint32_t w[4] = {(pack2(a[8 * q], a[8 * q + 1]) & 0xFFFFFFFEu) | par, pack2(a[8 * q + 2], a[8 * q + 3]), pack2(a[8 * q + 4], a[8 * q + 5]),
                           pack2(a[8 * q + 6], a[8 * q + 7])};
    sts4(dst + q * 512, w);
  }
}
#define LL_LD(o, a, b, c, d) "ld.relaxed.gpu.global.b128 w, [%16+" #o "]; mov.b128 {lo,hi}, w; mov.b64 {%" #a ",%" #b "}, lo; mov.b64 {%" #c ",%" #d "}, hi;\n"
template <int NP> __device__ __forceinline__ void recv_ll(float* a, uint32_t* v, const uint4* p, uint32_t par) {
  if constexpr (NP == 4) {
    asm volatile(
        "{ .reg .pred p; .reg .b32 t, u, n; .reg .b128 w; .reg .b64 lo, hi;\n"
        "mov.u32 n, 0;\n"
        "R_L: lop3.b32 t, %0, %4, %17, 0x7E; lop3.b32 u, %8, %12, %17, 0x7E; lop3.b32 t, t, u, 1, 0xA8;\n"
        "setp.eq.u32 p, t, 0; vote.sync.all.pred p, p, 0xffffffff; @p bra R_D;\n"
        LL_LD(0, 0, 1, 2, 3) LL_LD(512, 4, 5, 6, 7) LL_LD(1024, 8, 9, 10, 11) LL_LD(1536, 12, 13, 14, 15)
        "add.u32 n, n, 1; setp.lt.u32 p, n, 2097152; @p bra R_L; trap;\n"
        "R_D: }"
        : "+r"(v[0]), "+r"(v[1]), "+r"(v[2]), "+r"(v[3]), "+r"(v[4]), "+r"(v[5]), "+r"(v[6]), "+r"(v[7]), "+r"(v[8]), "+r"(v[9]), "+r"(v[10]),
          "+r"(v[11]), "+r"(v[12]), "+r"(v[13]), "+r"(v[14]), "+r"(v[15])
        : "l"(p), "r"(par)
        : "memory");
  } else {
    asm volatile(
        "{ .reg .pred p; .reg .b32 t, n; .reg .b128 w; .reg .b64 lo, hi;\n"
        "mov.u32 n, 0;\n"
        "R_L: lop3.b32 t, %0, %4, %9, 0x7E; and.b32 t, t, 1;\n"
        "setp.eq.u32 p, t, 0; vote.sync.all.pred p, p, 0xffffffff; @p bra R_D;\n"
        "ld.relaxed.gpu.global.b128 w, [%8]; mov.b128 {lo,hi}, w; mov.b64 {%0,%1}, lo; mov.b64 {%2,%3}, hi;\n"
        "ld.relaxed.gpu.global.b128 w, [%8+512]; mov.b128 {lo,hi}, w; mov.b64 {%4,%5}, lo; mov.b64 {%6,%7}, hi;\n"
        "add.u32 n, n, 1; setp.lt.u32 p, n, 2097152; @p bra R_L; trap;\n"
        "R_D: }"
        : "+r"(v[0]), "+r"(v[1]), "+r"(v[2]), "+r"(v[3]), "+r"(v[4]), "+r"(v[5]), "+r"(v[6]), "+r"(v[7])
        : "l"(p), "r"(par)
        : "memory");
  }
#pragma unroll
  for (int i = 0; i < 4 * NP; i++) { a[2 * i] += blo(v[i]); a[2 * i + 1] += bhi(v[i]); }
}

template <int NP> __device__ __forceinline__ bool try_ll(float* a, const uint32_t* v, uint32_t par) {
  uint32_t t = (v[0] ^ par) | (v[4] ^ par);
  if (NP == 4) t |= (v[8] ^ par) | (v[12] ^ par);
  const bool ok = __all_sync(0xffffffffu, (t & 1) == 0);
  if (ok) {
#pragma unroll
    for (int i = 0; i < 4 * NP; i++) { a[2 * i] += blo(v[i]); a[2 * i + 1] += bhi(v[i]); }
  }
  return ok;
}
#define LLT 1

__device__ __forceinline__ void load_x(const __nv_bfloat16* x, uint32_t sb, int r, int warp, int lane) {
  const int l8 = lane >> 3, c = lane & 7;
  const char* src = reinterpret_cast<const char*>(x + (size_t)(r * 128 + warp * 16 + l8) * DM + c * 8);
  const uint32_t dst = sb + (uint32_t)((warp >> 2) * (7 * U) + ((warp & 3) * 16 + l8) * 128 + ((c ^ l8) << 4));
#pragma unroll
  for (int kb = 0; kb < 7; kb++) {
#pragma unroll
    for (int q = 0; q < 4; q++)
      asm volatile("cp.async.cg.shared.global [%0], [%1], 16;" ::"r"((dst ^ ((q & 1) << 6)) + kb * U + q * 512), "l"(src + q * 4 * DM * 2 + kb * 128) : "memory");
    asm volatile("cp.async.commit_group;" ::: "memory");
  }
}
template <int N> __device__ __forceinline__ void cp_wait() { asm volatile("cp.async.wait_group %0;" ::"n"(N) : "memory"); }

#define LANE() const int ln = laneid(), g8 = ln >> 2, t4 = ln & 3; (void)g8; (void)t4
template <bool Y>
__device__ __forceinline__ void tail(const Maps& M, uint32_t* hf, float* acc, const uint32_t* sg, float* rs_, uint32_t sb, uint32_t pb, int warp, bool lane0) {
  constexpr int N2 = Y ? 64 : 32, N3 = Y ? 32 : 64;
  const int wg = warp >> 2, w4 = warp & 3;
  constexpr int BB = Y ? 200 : 300;
  float a1[64], a2[N2 / 2];
  const float hr[2] = {0.5f * rs_[0], 0.5f * rs_[1]}, hc[2] = {hr[0] * rs_[0], hr[1] * rs_[1]};
  auto e1 = [&](int lo) {
#pragma unroll
    for (int i = lo; i < lo + 16; i++) { acc[32 + i] *= acc[i]; acc[i] = tanh_(acc[i] * hr[(i >> 1) & 1]); }
    pin<16>(acc + lo); pin<16>(acc + 32 + lo);
  };
  auto e2 = [&](int lo) {
#pragma unroll
    for (int m = lo; m < lo + 8; m++) hf[32 + m] = pack2(acc[32 + 2 * m] * fmaf(acc[2 * m], hc[m & 1], hc[m & 1]), acc[33 + 2 * m] * fmaf(acc[2 * m + 1], hc[m & 1], hc[m & 1]));
    pinr<8>(hf + 32 + lo);
  };
  mbar_wait(BAR(FT + 0));
  wg_fence();
#pragma unroll
  for (int s = 0; s < 4; s++) rs<128>(a1, hf + 4 * s, desc(s * 2048, 16384), s == 0);
  wg_commit();
  BBARI(BB + 1);
  TS7(21);
  e1(0);
  BBARI(BB + 3);
  wg_fence();
#pragma unroll
  for (int s = 4; s < 8; s++) rs<128>(a1, hf + 4 * s, desc(s * 2048, 16384), false);
  wg_commit();
  BBARI(BB + 5);
  TS7(22);
  e1(16);
  mbar_wait(BAR(FT + 1));
  wg_fence();
#pragma unroll
  for (int s = 0; s < 4; s++) rs<128>(a1, hf + 56 + 4 * s, desc(4 * U + s * 2048, 16384), false);
  wg_commit();
  BBARI(BB + 7);
  TS7(23);
  e2(0);
  e2(8);
  BBARI(BB + 9);
  wg_fence();
#pragma unroll
  for (int s = 4; s < 8; s++) rs<128>(a1, hf + 56 + 4 * s, desc(4 * U + s * 2048, 16384), false);
  wg_commit();
  wg_wait<2>();
  if (lane0) mbar_arrive(BAR(ET + 0));
  TS7(24);
#pragma unroll
  for (int m = 0; m < 8; m++) {
    const int w = m & 1;
    hf[48 + m] = pack2(blo(sg[m]) * (acc[64 + 2 * m] * rs_[w]), bhi(sg[m]) * (acc[65 + 2 * m] * rs_[w]));
  }
  pinr<8>(hf + 48);
  mbar_wait(BAR(OFREE));
  const uint32_t doff = (uint32_t)(wg * 12288 + w4 * 3072 + laneid() * 16);
#pragma unroll
  for (int s = 0; s < 6; s++) sts4(sb + 8 * U + doff + s * 512, hf + 32 + 4 * s);
  mbar_wait(BAR(FT + 2));
  wg_fence();
#pragma unroll
  for (int s = 0; s < 3; s++) rs<128>(a1, hf + 32 + 4 * s, desc(21 * U + s * 2048, 12288), false);
  wg_commit();
  fence_async();
  mbar_wait(BAR(PF + 2));
  __syncwarp();
  if (lane0) bulk_s2c(pb + 11 * U + doff, sb + 8 * U + doff, 3072, pb + MISC + 8u * (HF + 4) + wg * 8);
  CTS(9);
  wg_fence();
#pragma unroll
  for (int s = 3; s < 6; s++) rs<128>(a1, hf + 32 + 4 * s, desc(21 * U + s * 2048, 12288), false);
  wg_commit();
  wg_wait<2>();
  if (lane0) mbar_arrive(BAR(ET + 1));
  mbar_wait(BAR(FT + 4));
  wg_fence();
#pragma unroll
  for (int s = 0; s < 14; s++) rs<N2>(a2, hf + 4 * s, desc(24 * U + s * 2048, U), s == 0);
  wg_commit();
  TS7(25);
  mbar_wait(BAR(HF + 4) + wg * 8);
#pragma unroll
  for (int s = 0; s < 6; s++) lds4(hf + 88 + 4 * s, sb + 11 * U + doff + s * 512);
  if (lane0) mbar_arrive_remote(pb + MISC + 8u * ACK);
  CTS(10);
  mbar_wait(BAR(FT + 3));
  wg_wait<1>();
  if (lane0) mbar_arrive(BAR(ET + 2));
  wg_fence();
#pragma unroll
  for (int s = 0; s < 6; s++) rs<128>(a1, hf + 88 + 4 * s, desc(14 * U + s * 2048, 12288), false);
  wg_commit();
  if (lane0) mbar_arrive(BAR(LD2));
  mbar_wait(BAR(FT + 5));
  wg_wait<1>();
  if (lane0) mbar_arrive(BAR(ET + 4));
  wg_fence();
#pragma unroll
  for (int s = 0; s < 14; s++) rs<N2>(a2, hf + 56 + 4 * s, desc(17 * U + s * 2048, U), false);
  wg_commit();
  TS7(26);
  const int j = blockIdx.x & 7, r = blockIdx.x >> 3, kq = j >> 1, n = j & 1;
  uint32_t par;
  asm volatile("ld.shared.u32 %0, [%1];" : "=r"(par) : "r"(BAR(NBAR)) : "memory");
  uint4* pbase = g_p + (size_t)((r * 2 + n) * 4) * 3072 + warp * 128;
  const uint32_t la = sb + 8 * U + (uint32_t)(warp * 2048), lb = sb + (uint32_t)((wg ? 27 : 10) * U + w4 * 2048);
  const int io = Y ? 2 : kq - n;
  mbar_wait(BAR(ACK));
  mbar_wait(BAR(FT + 6));
  wg_wait<1>();
  if (lane0) mbar_arrive(BAR(ET + 3));
  pin<64>(a1);
  TS7(27);
  stage_ll<4>(la + laneid() * 16, a1, par);
  float* a3 = a1;
  float aw[N3 / 2];
  wg_fence();
#pragma unroll
  for (int s = 0; s < 5; s++) { if (s == 0) rsz<N3>(a3, hf, desc(0, U)); else rs<N3>(a3, hf + 4 * s, desc(s * 2048, U), false); }
  wg_commit();
  mbar_wait(BAR(ET + 4));
  stage_ll<4>(lb + laneid() * 16, a1 + 32, par);
  wg_wait<1>();
  if (lane0) mbar_arrive(BAR(ET + 5));
  pin<N2 / 2>(a2);
  wg_fence();
#pragma unroll
  for (int s = 5; s < 10; s++) rs<N3>(a3, hf + 4 * s, desc(s * 2048, U), false);
  wg_commit();
  mbar_wait(BAR(LD2));
  stage_ll<N2 / 16>(la + 3 * U + laneid() * 16, a2, par);
  BBARI(BB + 11);
  wg_fence();
#pragma unroll
  for (int s = 10; s < 14; s++) rs<N3>(a3, hf + 4 * s, desc(s * 2048, U), false);
  wg_commit();
  TS7(28);
  fence_async();
  __syncwarp();
  if (lane0) {
    const int ca = n + (io == 2 ? 0 : io + 1), cb = n + (io == 0 ? 2 : io - 1), c2 = Y ? n + 2 : 3 - 3 * n;
    bulk_s2g(pbase + ca * 3072 + ((kq ^ ca) - 1) * 1024, la, 2048);
    bulk_s2g(pbase + cb * 3072 + ((kq ^ cb) - 1) * 1024, lb, 2048);
    bulk_s2g(pbase + c2 * 3072 + ((kq ^ c2) - 1) * 1024, la + 3 * U, N2 * 32);
    bulk_commit();
  }
  CTS(16);
  mbar_wait(BAR(FT + 7));
  wg_fence();
#pragma unroll
  for (int s = 0; s < 14; s++) rs<N3>(a3, hf + 56 + 4 * s, desc(4 * U + s * 2048, U), false);
  wg_commit();
  wg_wait<1>();
  const int row = r * 128 + warp * 16, col = Y ? 192 + 32 * n : 192 * n + 64 * kq;
  if (lane0) {
    mbar_arrive(BAR(ET + 6));
    bulk_wait_read();
    mbar_arrive(BAR(SR));
    mbar_expect_tx(BAR(XR), N3 * 32);
    tma2d(lb, Y ? &M.xrb : &M.xra, col, row, BAR(XR));
  }
  __syncwarp();
  CTS(17);
  uint32_t v[3][N3 / 4];
  bool got[3];
  const uint4* pin_ = pbase + kq * 3072 + laneid();
  const uint64_t adw = (uint64_t)(wg * 512);
#pragma unroll
  for (int t = 0; t < 7; t++) {
    constexpr int wu[7] = {21, 24, 14, 17, 11, 0, 4};
    mbar_wait(BAR(FW + t));
    if (t == 0) CTS(18);
    if (t == 6) CTS(19);
    wg_fence();
#pragma unroll
    for (int kk = 0; kk < 4; kk++) {
      const uint64_t da = desc(wu[t] * U + kk * 32, 16) + adw, db = desc((wu[t] + 2) * U + kk * 2048, U);
      ssk<N3>(aw, da, db, t == 0 && kk == 0);
    }
    wg_commit();
    if (t == 0) {
      wg_wait<1>();
      if (lane0) mbar_arrive(BAR(ET + 7));
      pin<N3 / 2>(a3);
      CTS(11);
    }
    if (t == LLT) {
#pragma unroll
      for (int i = 0; i < 3; i++)
#pragma unroll
        for (int q = 0; q < N3 / 16; q++) ld_ll(v[i] + 4 * q, pin_ + i * 1024 + q * 32);
    }
    if (t >= 3 && t < 6) { got[t - 3] = try_ll<N3 / 16>(a3, v[t - 3], par); pin<N3 / 2>(a3); }
  }
#pragma unroll
  for (int i = 0; i < 3; i++)
    if (!got[i]) recv_ll<N3 / 16>(a3, v[i], pin_ + i * 1024, par);
  CTS(20);
  {
    float th[N3 / 2];
#pragma unroll
    for (int i = 0; i < N3 / 2; i++) { a3[i] *= 0.5f; th[i] = tanh_(a3[i]); }
    pin<N3 / 2>(th);
#pragma unroll
    for (int i = 0; i < N3 / 2; i++) a3[i] = fmaf(a3[i], th[i], a3[i]);
  }
  LANE();
  const uint32_t sa = lb + (uint32_t)((ln & 15) * 128 + (((ln >> 4) ^ (ln & 7)) << 4));
  uint32_t xr[N3 / 4];
  mbar_wait(BAR(XR));
#pragma unroll
  for (int kk = 0; kk < N3 / 16; kk++) ldsm4(xr + 4 * kk, sa ^ (kk << 5));
  wg_wait<0>();
  pin<N3 / 2>(aw);
  CTS(12);
#pragma unroll
  for (int m = 0; m < N3 / 4; m++) xr[m] = pack2(fmaf(aw[2 * m], a3[2 * m], blo(xr[m])), fmaf(aw[2 * m + 1], a3[2 * m + 1], bhi(xr[m])));
#pragma unroll
  for (int kk = 0; kk < N3 / 16; kk++) stsm4(sa ^ (kk << 5), xr[4 * kk], xr[4 * kk + 1], xr[4 * kk + 2], xr[4 * kk + 3]);
  fence_async();
  __syncwarp();
  if (lane0) {
    tma2d_store(Y ? &M.outb : &M.outa, col, row, lb);
    bulk_commit();
    bulk_wait_read();
  }
}

__global__ void __cluster_dims__(2, 1, 1) __launch_bounds__(384, 1)
fused_kernel(const __grid_constant__ Maps M, const __grid_constant__ Ptrs P) {
  const __nv_bfloat16* xg = P.x;
  extern __shared__ __align__(1024) uint8_t smem_raw[];
  uint32_t sb = smem_u32(smem_raw);
  asm volatile("" : "+r"(sb));
  const int tid = threadIdx.x;
  const int warp = __shfl_sync(0xffffffffu, tid >> 5, 0);
  const int lane = tid & 31;
  const int wg = warp >> 2;
  const int r = blockIdx.x >> 3, j = blockIdx.x & 7, kq = j >> 1, n = j & 1;

  if (warp < 8) CTS(27);
  if (warp < 4) load_x(xg, sb, r, warp, lane);
  if (warp < 8) CTS(28);
  if (elect_one()) {
    if ((warp >> 1) == 4) {
      const uint32_t ba = BAR(FA) + (warp - 8) * 8;
      mbar_init(ba, 1);
      mbar_expect_tx(ba, 2 * U);
      tma3d(sb + (14 + 2 * (warp - 8)) * U, &M.kv, j * 56 - 8 * n, (warp - 8) * 64, 1, ba);
    }
    const uint32_t b0 = BAR(2 + 8 * warp), cnt = warp < 6 ? 1u : 8u, cnt2 = warp == 6 ? 16u : cnt;
#pragma unroll
    for (int i = 0; i < 8; i++) mbar_init(b0 + 8 * i, i < 2 ? cnt2 : cnt);
    if (warp == 11) mbar_init(BAR(SR), 8);
  }
  asm volatile("fence.mbarrier_init.release.cluster;" ::: "memory");
  __syncwarp();
  if (warp < 8) CTS(29);
  asm volatile("barrier.cluster.arrive.relaxed.aligned;" ::: "memory");

  if (wg == 2) {
    asm volatile("setmaxnreg.dec.sync.aligned.u32 24;");
    if (warp == 8) {
      asm volatile("barrier.cluster.wait.acquire.aligned;" ::: "memory");
      if (elect_one()) {
        TS(2, 9);
        const int f0 = j * 224, ca = j * 56 - 8 * n;
#pragma unroll 1
        for (int g = 2; g < 7; g++) {
          mbar_expect_tx(BAR(FA + g), 2 * U);
          tma3d(sb + (14 + 2 * g) * U, &M.kv, ca, g * 64, 1, BAR(FA + g));
        }
        TS(2, 1);
        const int ro = f0 + 32 * n, rg = f0 + 192 * (1 - n);
#pragma unroll 1
        for (int p = 0; p < 3; p++) {
          const uint64_t ut = p == 0 ? packtab(unitB) : p == 1 ? packtab(unitC) : packtab(unitD);
          const uint64_t dt = p == 0 ? packtab(depB) : p == 1 ? packtab(depC) : packtab(depD);
          const CUtensorMap* m3 = p == 0 ? &M.wq : p == 1 ? &M.w1b : &M.w3b;
          const int c3 = p == 0 ? ca : rg;
#pragma unroll 1
          for (int g = 0; g < 7; g++) {
            const uint32_t dst = sb + (uint32_t)((ut >> (8 * g)) & 255) * U;
            const uint32_t fb = BAR(FB + 7 * p + g);
            mbar_expect_tx(fb, p == 0 ? 3 * U : 20480u);
            mbar_wait(BAR((uint32_t)((dt >> (8 * g)) & 255)));
            tma2d(dst, &M.w1a, ro + 64 * p, g * 64, fb);
            tma2d(dst + U, &M.w3a, ro + 64 * p, g * 64, fb);
            tma2d(dst + 2 * U, m3, c3, g * 64, fb);
          }
          TS(2, 2 + p);
        }
        const bool isy = kq == 3 - 3 * n;
        const int io = isy ? 2 : kq - n;
        const int cA = 256 * n + 64 * (io == 2 ? 0 : io + 1), cB = 256 * n + 64 * (io == 0 ? 2 : io - 1), cW = 256 * n + 64 * io, cN = 192 + 32 * n;
#pragma unroll 1
        for (int i = 0; i < 8; i++) {
          const int t = (0x76534210u >> (4 * i)) & 15;
          const uint32_t dst = sb + (uint32_t)((0x0400110E18150400ull >> (8 * i)) & 255) * U;
          const uint64_t dt = (uint64_t)LH0 | ((uint64_t)LH1 << 8) | ((uint64_t)ED4 << 16) | ((uint64_t)OFREE << 24) | ((uint64_t)ED5 << 32) | ((uint64_t)ED6 << 40) |
                              ((uint64_t)(ET + 0) << 48) | ((uint64_t)(ET + 1) << 56);
          const uint32_t fb = BAR(FT + t);
          const int pe = t & 1, nn = n ^ pe, fb0 = (j ^ pe) * 224;
          const int r0 = fb0 + 32 * nn, r1 = fb0 + 192 * (1 - nn);
          const bool wide = (t >= 6) != isy;
          mbar_expect_tx(fb, t < 2 ? 32768u : t < 4 ? 24576u : wide ? 28672u : 14336u);
          mbar_wait(BAR((uint32_t)((dt >> (8 * i)) & 255)));
          if (t < 2) {
            tma2d(dst, &M.w2a, cA, r0, fb); tma2d(dst + U, &M.w2a, cA, r0 + 64, fb);
            tma2d(dst + 2 * U, &M.w2a, cB, r0, fb); tma2d(dst + 3 * U, &M.w2a, cB, r0 + 64, fb);
          } else if (t < 4) {
            tma2d(dst, &M.w2a, cA, r0 + 128, fb); tma2d(dst + U, &M.w2b, cA, r1, fb);
            tma2d(dst + 12288, &M.w2a, cB, r0 + 128, fb); tma2d(dst + 12288 + U, &M.w2b, cB, r1, fb);
          } else {
            const CUtensorMap* m = wide ? &M.w2a : &M.w2c;
            const int c = wide ? cW : cN;
            tma2d(dst, m, c, r0, fb); tma2d(dst + U, m, c, r0 + 64, fb); tma2d(dst + 2 * U, m, c, r0 + 128, fb);
            tma2d(dst + 3 * U, m + 1, c, r1, fb);
          }
          TS(2, 10 + i);
        }
        TS(2, 7);
        TSDUMP(2);
      }
    } else {
      if (elect_one()) {
        const CUtensorMap* mp = &M.kv + (warp - 9) * 6;
        if ((sb & 0x3FFFFu) != SM_BASE) asm volatile("trap;");
#pragma unroll
        for (int i = 0; i < 6; i++) map_prefetch(mp + i);
      }
      const uint32_t ep = g_epoch[blockIdx.x] + 1;
      const int at = tid - 288;
      if (at < 32) reinterpret_cast<float4*>(g_kv + ((ep & 1) ^ 1) * (8 * 2048) + j * 2048 + r * 128)[at] = make_float4(0.f, 0.f, 0.f, 0.f);
      asm volatile("barrier.cluster.wait.acquire.aligned;" ::: "memory");
      float* kv = g_kv + (ep & 1) * (8 * 2048) + j * 2048;
      if (warp == 10 && elect_one()) {
#pragma unroll
        for (int i = 0; i < 6; i++) mbar_expect_tx(BAR(HF + i), i < 4 ? 8192u : 12288u);
        mbar_expect_tx(BAR(KVL), KV_BYTES);
      }
      mbar_wait(BAR(EA6));
      const uint32_t kvm = sb + KVM_U * U;
#pragma unroll 1
      for (int c = at; c < 512; c += 96) {
        const int d = c >> 3, cc = c & 7;
        const bool used = d < 56 && (cc == 7 || (d < 28 ? cc < 4 : (cc >= 3)));
        if (!used) { const uint32_t z[4] = {0, 0, 0, 0}; sts4(kvm + d * 128 + ((cc ^ (d & 7)) << 4), z); }
      }
      if (warp == 9) {
        mbar_wait(BAR(KVST));
        if (elect_one()) {
          asm volatile("cp.reduce.async.bulk.global.shared::cta.bulk_group.add.f32 [%0], [%1], %2;" ::"l"(kv), "r"(sb + 12 * U), "r"(KV_BYTES) : "memory");
          bulk_commit();
          bulk_wait_read();
          mbar_arrive_n(BAR(KVFREE), 8);
          bulk_wait_all();
          TS(3, 4);
          SIGNAL(&g_f1[j * 32]);
          TS(3, 0);
          poll_flag(&g_f1[j * 32], 16u * ep);
          asm volatile("fence.proxy.async.global;" ::: "memory");
          TS(3, 1);
          asm volatile("cp.async.bulk.shared::cluster.global.mbarrier::complete_tx::bytes [%0], [%1], %2, [%3];" ::"r"(sb + 27 * U), "l"(kv), "r"(KV_BYTES), "r"(BAR(KVL)) : "memory");
        }
        __syncwarp();
      }
      mbar_wait(BAR(KVL));
#pragma unroll 1
      for (int idx = at; idx < 280; idx += 96) {
        const int d = idx / 5, m = idx - d * 5;
        const bool hi = d >= 28;
        const uint32_t src = sb + 27 * U + d * (KVP * 4);
        uint32_t w[4] = {0, 0, 0, 0}, v[4];
        int cc;
        if (m == 4) {
          cc = 7;
          lds4(v, src + 128);
          w[0] = pack2(__uint_as_float(v[0]), 0.f) << (hi ? 16 : 0);
        } else {
          cc = m + (hi ? 3 : 0);
          const int o = 8 * m - (hi ? 4 : 0);
          if (o >= 0) { lds4(v, src + o * 4); w[0] = pack2(__uint_as_float(v[0]), __uint_as_float(v[1])); w[1] = pack2(__uint_as_float(v[2]), __uint_as_float(v[3])); }
          if (o + 4 < 28) { lds4(v, src + o * 4 + 16); w[2] = pack2(__uint_as_float(v[0]), __uint_as_float(v[1])); w[3] = pack2(__uint_as_float(v[2]), __uint_as_float(v[3])); }
        }
        sts4(kvm + d * 128 + ((cc ^ (d & 7)) << 4), w);
      }
      if (at == 0) asm volatile("st.shared.u32 [%0], %1;" ::"r"(BAR(NBAR)), "r"(ep & 1) : "memory");
      fence_async();
      __syncwarp();
      if (lane == 0) mbar_arrive_n(BAR(KVM), warp < 11 ? 3 : 2);
      if (at == 0) TS(3, 2);
      if (warp < 11) {
        const int h = warp - 9;
        mbar_wait(BAR(OST + h));
        if (elect_one()) {
          tma2d_store(&M.ost, j * 56, r * 128 + h * 64, sb + (h ? 8 : 27) * U);
          bulk_commit();
          bulk_wait_read();
          mbar_arrive_n(BAR(OFREE), 4);
          bulk_wait_all();
          SIGNAL(&g_f2[r * 32]);
          if (h == 1) { TS(3, 3); }
        }
      } else if (elect_one()) {
        poll_flag(&g_f2[r * 32], 16u * ep);
        asm volatile("fence.proxy.async.global;" ::: "memory");
        TS(3, 5);
        const bool isy = kq == 3 - 3 * n;
        const int co = isy ? 192 + 32 * n : 192 * n + 64 * kq;
#pragma unroll 1
        for (int t = 0; t < 7; t++) {
          const uint64_t dt = (uint64_t)(ET + 2) | ((uint64_t)(ET + 4) << 8) | ((uint64_t)(ET + 3) << 16) | ((uint64_t)(ET + 5) << 24) | ((uint64_t)SR << 32) |
                              ((uint64_t)(ET + 6) << 40) | ((uint64_t)(ET + 7) << 48);
          const uint32_t dst = sb + (uint32_t)((0x04000B110E1815ull >> (8 * t)) & 255) * U;
          mbar_expect_tx(BAR(FW + t), isy ? 20480u : 24576u);
          mbar_wait(BAR((uint32_t)((dt >> (8 * t)) & 255)));
          tma2d(dst, &M.o, t * 64, r * 128, BAR(FW + t));
          tma2d(dst + 2 * U, isy ? &M.wob : &M.woa, co, t * 64, BAR(FW + t));
          TS(3, 10 + t);
        }
        g_epoch[blockIdx.x] = ep;
        TS(3, 6);
        TSDUMP(3);
      }
    }
  } else {
    asm volatile("setmaxnreg.inc.sync.aligned.u32 240;");
    asm volatile("barrier.cluster.wait.acquire.aligned;" ::: "memory");
    CTS(0);
    if (wg == 1) load_x(xg, sb, r, warp, lane);
    const int w4 = warp & 3;
    const bool lane0 = lane == 0;
    const uint32_t pb = mapa(sb, n ^ 1);
    const uint32_t so = sb + (uint32_t)((wg * 64 + w4 * 16 + (lane & 7) + ((lane >> 3) & 1) * 8) * 128 + (((lane >> 4) ^ (lane & 7)) << 4));
    uint32_t xf[112];
    float rs_[2];
    uint32_t pm0, pm1;
    float q0, q1;
    {
      float cm[2][4], ga[2][4], gb[2][4];
#pragma unroll
      for (int i = 0; i < 8; i++) cm[i >> 2][i & 3] = ga[i >> 2][i & 3] = gb[i >> 2][i & 3] = 0.f;
      const uint32_t sx = so + wg * (6 * U);
      uint32_t s0 = 0, s1 = 0;
#pragma unroll
      for (int kb = 0; kb < 7; kb++) {
        if (kb == 0) cp_wait<6>(); else if (kb == 1) cp_wait<5>(); else if (kb == 2) cp_wait<4>(); else if (kb == 3) cp_wait<3>();
        else if (kb == 4) cp_wait<2>(); else if (kb == 5) cp_wait<1>(); else cp_wait<0>();
        __syncwarp();
        if (kb == 0) CTS(14);
        EPI_TS(if (kb == 3) CTS(26));
        if (kb == 6) CTS(15);
#pragma unroll
        for (int kk = 0; kk < 4; kk++) ldsm4(xf + 16 * kb + 4 * kk, (sx ^ (kk << 5)) + kb * U);
#pragma unroll
        for (int kk = 0; kk < 4; kk++) mma16816(cm[kk & 1], xf + 16 * kb + 4 * kk, 0x3F803F80u, 0x3F803F80u);
        if (kb == 0) {
          s0 = __byte_perm(__shfl_sync(0xffffffffu, xf[0], lane & 28), 0, 0x1010);
          s1 = __byte_perm(__shfl_sync(0xffffffffu, xf[1], lane & 28), 0, 0x1010);
        }
        if (kb == 6) {
          const float m0 = (cm[0][0] + cm[1][0]) * (1.0f / 448.0f), m1 = (cm[0][2] + cm[1][2]) * (1.0f / 448.0f);
          pm0 = pack2(m0, m0); pm1 = pack2(m1, m1);
          q0 = m0 - blo(s0); q1 = m1 - blo(s1);
          __syncwarp();
          if (lane0) mbar_arrive_n(BAR(XC0) + wg * 8, 2);
        }
#pragma unroll
        for (int kk = 0; kk < 4; kk++) {
          const uint32_t* a = xf + 16 * kb + 4 * kk;
          uint32_t t[4];
#pragma unroll
          for (int i = 0; i < 4; i++) asm volatile("sub.rn.bf16x2 %0, %1, %2;" : "=r"(t[i]) : "r"(a[i]), "r"((i & 1) ? s1 : s0));
          mma16816(ga[kk & 1], t, t[0], t[2]);
          mma16816(gb[kk & 1], t, t[1], t[3]);
        }
      }
#pragma unroll
      for (int i = 0; i < 16; i++) asm volatile("sub.rn.bf16x2 %0, %0, %1;" : "+r"(xf[i]) : "r"((i & 1) ? pm1 : pm0));
      const bool odd = (lane >> 2) & 1;
      rs_[0] = odd ? ga[0][1] + ga[1][1] : ga[0][0] + ga[1][0];
      rs_[1] = odd ? gb[0][3] + gb[1][3] : gb[0][2] + gb[1][2];
    }
    CTS(1);
    uint32_t pq[14];
    {
      float acc[60];
      pass1<0, 120>(acc, xf, sb, pb, lane0, (uint64_t)n, [&](int g) {
        if (g < 6) {
#pragma unroll
          for (int i = 0; i < 16; i++) asm volatile("sub.rn.bf16x2 %0, %0, %1;" : "+r"(xf[16 * g + 16 + i]) : "r"((i & 1) ? pm1 : pm0));
        }
        if (g == 1) {
          const int src = (lane & 28) | (lane >> 3);
          const float v0 = fmaxf(fmaf(__shfl_sync(0xffffffffu, rs_[0], src), 1.0f / 448.0f, -q0 * q0), 0.f);
          const float v1 = fmaxf(fmaf(__shfl_sync(0xffffffffu, rs_[1], src), 1.0f / 448.0f, -q1 * q1), 0.f);
          rs_[0] = rcp(bfr(sqrt_(bfr(bfr(v0) + 1e-5f))));
          rs_[1] = rcp(bfr(sqrt_(bfr(bfr(v1) + 1e-5f))));
          pin<2>(rs_);
        }
      }, [&](int) {});
      CTS(2);
      LANE();
      uint32_t pk[16], pv[16];
      float e[28];
      phi1(e, acc, rs_);
#pragma unroll
      for (int m = 0; m < 14; m++) pv[m] = pack2(acc[32 + 2 * m] * rs_[m & 1], acc[33 + 2 * m] * rs_[m & 1]);
      pv[14] = pv[15] = t4 == 0 ? 0x3F803F80u : 0u;
      pinr<16>(pv);
      mbar_wait(BAR(XC1));
#pragma unroll
      for (int kk = 0; kk < 4; kk++) stsm4((so ^ (kk << 5)) + 10 * U, pv[4 * kk], pv[4 * kk + 1], pv[4 * kk + 2], pv[4 * kk + 3]);
#pragma unroll
      for (int m = 0; m < 14; m++) pk[m] = pack2(e[2 * m] + acc[2 * m], e[2 * m + 1] + acc[2 * m + 1]);
      pk[14] = pk[15] = 0u;
#pragma unroll
      for (int kk = 0; kk < 4; kk++) stsm4((so ^ (kk << 5)) + 8 * U, pk[4 * kk], pk[4 * kk + 1], pk[4 * kk + 2], pk[4 * kk + 3]);
      fence_async();
      __syncwarp();
      if (lane0) mbar_arrive(BAR(PKST));
      if (wg == 1) {
        float kv[32];
        mbar_wait(BAR(PKST));
        wg_fence();
#pragma unroll
        for (int ks = 0; ks < 8; ks++) {
          if (ks == 0) ss64_0(kv, desc(8 * U, U), desc(10 * U, U));
          else ss64_1(kv, desc(8 * U + ks * 2048, U), desc(10 * U + ks * 2048, U));
        }
        wg_commit();
        wg_wait<0>();
        pin<32>(kv);
#pragma unroll
        for (int h = 0; h < 2; h++) {
          const int d = w4 * 16 + g8 + 8 * h;
          const uint32_t lim = d < 28 ? 0u : d < 56 ? 28u : 1000u;
          const uint32_t ka = sb + 12 * U + (uint32_t)d * (KVP * 4) + (uint32_t)(2 * t4) * 4 - lim * 4;
#pragma unroll
          for (int i = 0; i < 7; i++)
            asm volatile("{ .reg .pred p; setp.lt.u32 p, %0, 28; @p st.shared.v2.f32 [%1], {%2,%3}; }" ::"r"((uint32_t)(8 * i + 2 * t4) - lim), "r"(ka + 32 * i), "f"(kv[4 * i + 2 * h]), "f"(kv[4 * i + 2 * h + 1]) : "memory");
          asm volatile("{ .reg .pred p; setp.lt.u32 p, %0, 56; @p st.shared.f32 [%1], %2; }" ::"r"((uint32_t)(d + 64 * t4)), "r"(sb + 12 * U + (uint32_t)d * (KVP * 4) + 128), "f"(kv[28 + 2 * h]) : "memory");
        }
        fence_async();
        __syncwarp();
        if (lane0) mbar_arrive_n(BAR(KVST), 2);
      }
      CTS(3);
    }
    const uint32_t hoff = (uint32_t)(wg * 8192 + w4 * 2048 + laneid() * 16);
    {
      float acc[92];
      pass1<1, 184>(acc, xf, sb, pb, lane0, (uint64_t)n, [&](int) {}, [&](int) {});
      CTS(4);
      pin<2>(rs_);
      uint32_t h[16];
      hfrag64<1>(h, acc, rs_, sb, wg);
      pinr<16>(h);
      mbar_wait(BAR(EB1));
      EPI_TS(CTS(23));
#pragma unroll
      for (int s = 0; s < 4; s++) sts4(sb + hoff + s * 512, h + 4 * s);
      float e[28];
      phi1(e, acc + 64, rs_);
      mbar_wait(BAR(PF + 0));
      EPI_TS(CTS(24));
      fence_async();
      __syncwarp();
      if (lane0) bulk_s2c(pb + 2 * U + hoff, sb + hoff, 2048, pb + MISC + 8u * (HF + 0) + wg * 8);
      EPI_TS(CTS(25));
#pragma unroll
      for (int m = 0; m < 14; m++) pq[m] = pack2(e[2 * m] + acc[64 + 2 * m], e[2 * m + 1] + acc[65 + 2 * m]);
      pq[12] ^= sb; pq[13] ^= sb;
      pinr<14>(pq);
      CTS(5);
    }
    uint32_t sg[8];
    {
      float acc[80];
      pass1<2, 160>(acc, xf, sb, pb, lane0, 0, [&](int) {}, [&](int) {});
      CTS(6);
      pin<2>(rs_);
      uint32_t h[16];
      hfrag64<2>(h, acc, rs_, sb, wg);
      pinr<16>(h);
      mbar_wait(BAR(EC0 + 1));
#pragma unroll
      for (int s = 0; s < 4; s++) sts4(sb + 4 * U + hoff + s * 512, h + 4 * s);
      float nm[32];
      mbar_wait(BAR(KVM));
      {
        uint32_t q3[4];
        asm volatile("xor.b32 %0, %4, %6; xor.b32 %1, %5, %6; mov.b32 %2, 0; mov.b32 %3, 0;" : "=r"(q3[0]), "=r"(q3[1]), "=r"(q3[2]), "=r"(q3[3]) : "r"(pq[12]), "r"(pq[13]), "r"(sb));
        wg_fence();
        rs64_0(nm, pq, desc(KVM_U * U, U));
        rs64_1(nm, pq + 4, desc(KVM_U * U + 2048, U));
        rs64_1(nm, pq + 8, desc(KVM_U * U + 4096, U));
        rs64_1(nm, q3, desc(KVM_U * U + 6144, U));
      }
      wg_commit();
      float th[16];
      {
        const float hr[2] = {0.5f * rs_[0], 0.5f * rs_[1]};
#pragma unroll
        for (int i = 0; i < 16; i++) { acc[64 + i] *= hr[(i >> 1) & 1]; th[i] = tanh_(acc[64 + i]); }
        pin<16>(th); pin<16>(acc + 64);
      }
      fence_async();
      mbar_wait(BAR(PF + 1));
      __syncwarp();
      if (lane0) bulk_s2c(pb + 6 * U + hoff, sb + 4 * U + hoff, 2048, pb + MISC + 8u * (HF + 2) + wg * 8);
#pragma unroll
      for (int m = 0; m < 8; m++) sg[m] = pack2(fmaf(acc[64 + 2 * m], th[2 * m], acc[64 + 2 * m]), fmaf(acc[65 + 2 * m], th[2 * m + 1], acc[65 + 2 * m]));
      pinr<8>(sg);
      wg_wait<0>();
      pin<32>(nm);
      LANE();
      float rd[4];
#pragma unroll
      for (int i = 0; i < 4; i++) rd[i] = rcp(__shfl_sync(0xffffffffu, nm[28 + i], ln & 28) + 1e-6f);
      uint32_t ob[14];
#pragma unroll
      for (int i = 0; i < 7; i++) {
        const bool h0 = i < 3 || (i == 3 && t4 < 2);
        const float ra = h0 ? rd[0] : rd[1], rb = h0 ? rd[2] : rd[3];
        ob[2 * i] = pack2(nm[4 * i] * ra, nm[4 * i + 1] * ra);
        ob[2 * i + 1] = pack2(nm[4 * i + 2] * rb, nm[4 * i + 3] * rb);
      }
      mbar_wait(BAR(wg ? EC0 + 6 : EC0 + 1));
      const uint32_t sa = sb + (wg ? 8 : 27) * U + (uint32_t)(w4 * 16 + (ln & 15)) * 112;
#pragma unroll
      for (int kk = 0; kk < 3; kk++) stsm4(sa + (ln >> 4) * 16 + kk * 32, ob[4 * kk], ob[4 * kk + 1], ob[4 * kk + 2], ob[4 * kk + 3]);
      stsm2(sa + 96, ob[12], ob[13]);
      fence_async();
      __syncwarp();
      if (lane0) mbar_arrive_n(BAR(OST) + wg * 8, 2);
      CTS(7);
    }
    uint32_t hf[112];
    float acc[80];
    pass1<3, 160>(acc, xf, sb, pb, lane0, 0, [&](int) {}, [&](int g) {
      if (g == 2 || g == 4) {
        const int b = (g >> 1) - 1;
        mbar_wait(BAR(HF + 2 * b) + wg * 8);
#pragma unroll
        for (int s = 0; s < 4; s++) { lds4(hf + 16 * b + 4 * s, sb + 4 * b * U + hoff + s * 512); lds4(hf + 56 + 16 * b + 4 * s, sb + (4 * b + 2) * U + hoff + s * 512); }
        pinr<16>(hf + 16 * b); pinr<16>(hf + 56 + 16 * b);
      }
      if (g == 3 || g == 5) {
        const int b = (g >> 1) - 1;
        const uint32_t* u = hf + 16 * b;
        uint32_t one;
        if (g == 3) BBARI(101); else BBARI(103);
        asm volatile("{ .reg .b32 t; lop3.b32 t, %1, %2, %3, 0xFE; lop3.b32 t, t, %4, %5, 0xFE; lop3.b32 t, t, %6, %7, 0xFE; lop3.b32 t, t, %8, 1, 0xFE;\n"
                     "redux.sync.min.u32 t, t, 0xffffffff; min.u32 %0, t, 1; }"
                     : "=r"(one) : "r"(u[0]), "r"(u[4]), "r"(u[8]), "r"(u[12]), "r"(u[56]), "r"(u[60]), "r"(u[64]), "r"(u[68]));
        if (lane0) {
          mbar_arrive_n(BAR(LH0 + b), one);
          asm volatile("mbarrier.arrive.shared::cluster.b64 _, [%0], %1;" ::"r"(pb + MISC + 8u * (LH0 + b)), "r"(one) : "memory");
        }
      }
    });
    CTS(8);
    if (kq == 3 - 3 * n) tail<true>(M, hf, acc, sg, rs_, sb, pb, warp, lane0);
    else tail<false>(M, hf, acc, sg, rs_, sb, pb, warp, lane0);
    CTS(13);
    if ((tid & 127) == 0) { GTS(wg, 30); TSDUMP(wg); }
  }
}

typedef CUresult (*EncodeFn)(CUtensorMap*, CUtensorMapDataType, cuuint32_t, void*, const cuuint64_t*, const cuuint64_t*, const cuuint32_t*,
                             const cuuint32_t*, CUtensorMapInterleave, CUtensorMapSwizzle, CUtensorMapL2promotion, CUtensorMapFloatOOBfill);

void make_map(EncodeFn enc, CUtensorMap* m, const void* base, uint64_t cols, uint64_t rows, uint32_t bc, uint32_t br, bool sw) {
  cuuint64_t dims[2] = {cols, rows}, str[1] = {cols * 2};
  cuuint32_t box[2] = {bc, br}, es[2] = {1, 1};
  enc(m, CU_TENSOR_MAP_DATA_TYPE_BFLOAT16, 2, const_cast<void*>(base), dims, str, box, es, CU_TENSOR_MAP_INTERLEAVE_NONE,
      sw ? CU_TENSOR_MAP_SWIZZLE_128B : CU_TENSOR_MAP_SWIZZLE_NONE, CU_TENSOR_MAP_L2_PROMOTION_L2_128B, CU_TENSOR_MAP_FLOAT_OOB_FILL_NONE);
}
void make_map3(EncodeFn enc, CUtensorMap* m, const void* base, uint64_t sec, uint64_t nsec, uint64_t rows, uint32_t bc, uint32_t br, uint32_t bs) {
  cuuint64_t dims[3] = {sec, rows, nsec}, str[2] = {sec * nsec * 2, sec * 2};
  cuuint32_t box[3] = {bc, br, bs}, es[3] = {1, 1, 1};
  enc(m, CU_TENSOR_MAP_DATA_TYPE_BFLOAT16, 3, const_cast<void*>(base), dims, str, box, es, CU_TENSOR_MAP_INTERLEAVE_NONE,
      CU_TENSOR_MAP_SWIZZLE_128B, CU_TENSOR_MAP_L2_PROMOTION_L2_128B, CU_TENSOR_MAP_FLOAT_OOB_FILL_NONE);
}

}

extern "C" void kernel_launch(void* const* d_in, const int* in_sizes, int n_in, void* d_out, int out_size) {
  (void)in_sizes; (void)n_in; (void)out_size;
  void* fn = nullptr;
  cudaDriverEntryPointQueryResult q;
  cudaGetDriverEntryPoint("cuTensorMapEncodeTiled", &fn, cudaEnableDefault, &q);
  EncodeFn enc = (EncodeFn)fn;
  void* op = nullptr;
  cudaGetSymbolAddress(&op, g_o);
  Maps M;
  make_map3(enc, &M.kv, d_in[1], DM, 3, DM, 64, 64, 2);
  make_map(enc, &M.wq, d_in[1], 3 * DM, DM, 64, 64, true);
  make_map(enc, &M.w1a, d_in[4], FF, DM, 64, 64, true);
  make_map(enc, &M.w3a, d_in[5], FF, DM, 64, 64, true);
  make_map(enc, &M.w1b, d_in[4], FF, DM, 32, 64, true);
  make_map(enc, &M.w3b, d_in[5], FF, DM, 32, 64, true);
  make_map(enc, &M.w2a, d_in[6], DM, FF, 64, 64, true);
  make_map(enc, &M.w2b, d_in[6], DM, FF, 64, 32, true);
  make_map(enc, &M.w2c, d_in[6], DM, FF, 32, 64, true);
  make_map(enc, &M.w2d, d_in[6], DM, FF, 32, 32, true);
  make_map(enc, &M.woa, d_in[2], DM, DM, 64, 64, true);
  make_map(enc, &M.wob, d_in[2], DM, DM, 32, 64, true);
  make_map(enc, &M.o, op, DM, SEQ, 64, 128, true);
  make_map(enc, &M.ost, op, DM, SEQ, 56, 64, false);
  make_map(enc, &M.outa, d_out, DM, SEQ, 64, 16, true);
  make_map(enc, &M.outb, d_out, DM, SEQ, 32, 16, true);
  make_map(enc, &M.xra, d_in[0], DM, SEQ, 64, 16, true);
  make_map(enc, &M.xrb, d_in[0], DM, SEQ, 32, 16, true);
  cudaFuncSetAttribute(fused_kernel, cudaFuncAttributeMaxDynamicSharedMemorySize, (int)SMEM_BYTES);
  Ptrs P;
  P.x = (const __nv_bfloat16*)d_in[0]; P.wqkv = (const __nv_bfloat16*)d_in[1]; P.wo = (const __nv_bfloat16*)d_in[2];
  P.w1 = (const __nv_bfloat16*)d_in[4]; P.w3 = (const __nv_bfloat16*)d_in[5]; P.w2 = (const __nv_bfloat16*)d_in[6];
  fused_kernel<<<128, 384, SMEM_BYTES>>>(M, P);
}
```

```cpp
#include <cuda_runtime.h>
#include <cuda.h>
#include <cuda_bf16.h>
#include <stdint.h>

namespace {

constexpr int SEQ = 2048, DM = 448, FF = 1792;
constexpr uint32_t U = 8192;
constexpr uint32_t SM_BASE = 1024;
constexpr uint32_t MISC = 28 * U;
constexpr uint32_t SMEM_BYTES = 28 * U + 3072;
constexpr uint32_t KVM_U = 26;

enum : int { FA = 0, FB = 7, FC = 14, FD = 21, FT = 28, FW = 36, HF = 43, KVL = 49,
             LH0 = 50, LH1, EA1 = 52, EA2, EA4, EA5, EA6, EB1 = 57, EC0 = 63, ED1 = 70, ED2, ED4, ED5, ED6, ET = 75,
             PKST = 83, LD2, PF = 85, EW3 = 88, XC0, XC1, KVST, OST = 92, KVM = 94, OFREE, XR0, KVFREE, EW2, SND = 99, XR1 = 105, LF = 106, HS = 112, RA = 116, RC, NBAR = 118, EW0 = ET + 6, EW1 = ET + 7 };
constexpr int KVP = 36;
constexpr uint32_t KV_BYTES = 56 * KVP * 4;

struct Maps { CUtensorMap kv, wq, w1a, w3a, w1b, w3b, w2a, w2b, w2c, w2d, woa, wob, o, ost, outa, outb, xra, xrb; };

struct Ptrs { const __nv_bfloat16 *x, *wqkv, *wo, *w1, *w3, *w2; uint32_t role[128]; };

__device__ uint32_t g_epoch[128];
__device__ uint32_t g_f1[8 * 32];
__device__ uint32_t g_f2[16 * 32];
__device__ __align__(128) float g_kv[2 * 8 * 2048];
__device__ __nv_bfloat16 g_o[SEQ * DM];
__device__ uint4 g_p[16 * 2 * 4 * 3 * 1024];
#define TS(role, i)
#define GTS(role, i)
#define CTS(i)
#define TSDUMP(role)

__device__ __forceinline__ uint32_t smem_u32(const void* p) { return (uint32_t)__cvta_generic_to_shared(p); }
__device__ __forceinline__ void mbar_init(uint32_t bar, uint32_t cnt) { asm volatile("mbarrier.init.shared::cta.b64 [%0], %1;" ::"r"(bar), "r"(cnt) : "memory"); }
__device__ __forceinline__ void mbar_expect_tx(uint32_t bar, uint32_t bytes) { asm volatile("mbarrier.arrive.expect_tx.shared::cta.b64 _, [%0], %1;" ::"r"(bar), "r"(bytes) : "memory"); }
__device__ __forceinline__ void mbar_arrive_n(uint32_t bar, uint32_t n) { asm volatile("mbarrier.arrive.shared::cta.b64 _, [%0], %1;" ::"r"(bar), "r"(n) : "memory"); }
__device__ __forceinline__ void mbar_arrive(uint32_t bar) { asm volatile("mbarrier.arrive.shared::cta.b64 _, [%0];" ::"r"(bar) : "memory"); }
__device__ __forceinline__ void mbar_arrive_remote(uint32_t rbar) { asm volatile("mbarrier.arrive.shared::cluster.b64 _, [%0];" ::"r"(rbar) : "memory"); }
__device__ __forceinline__ void mbar_wait(uint32_t bar) {
  asm volatile("{ .reg .pred p; .reg .u32 n; mov.u32 n, 0;\n"
               "W_L: mbarrier.try_wait.parity.shared::cta.b64 p, [%0], 0;\n"
               "@p bra W_D;\n add.u32 n, n, 1;\n setp.lt.u32 p, n, 4194304;\n @p bra W_L;\n trap;\n W_D: }" ::"r"(bar) : "memory");
}
__device__ __forceinline__ void tma2d(uint32_t dst, const CUtensorMap* m, int c0, int c1, uint32_t bar) {
  asm volatile("cp.async.bulk.tensor.2d.shared::cluster.global.mbarrier::complete_tx::bytes [%0], [%1, {%3, %4}], [%2];" ::"r"(dst), "l"(m), "r"(bar), "r"(c0), "r"(c1) : "memory");
}
__device__ __forceinline__ void tma3d(uint32_t dst, const CUtensorMap* m, int c0, int c1, int c2, uint32_t bar) {
  asm volatile("cp.async.bulk.tensor.3d.shared::cluster.global.mbarrier::complete_tx::bytes [%0], [%1, {%3, %4, %5}], [%2];" ::"r"(dst), "l"(m), "r"(bar), "r"(c0), "r"(c1), "r"(c2) : "memory");
}
__device__ __forceinline__ void bulk_s2g(void* g, uint32_t src, uint32_t bytes) {
  asm volatile("cp.async.bulk.global.shared::cta.bulk_group [%0], [%1], %2;" ::"l"(g), "r"(src), "r"(bytes) : "memory");
}
__device__ __forceinline__ void bulk_commit() { asm volatile("cp.async.bulk.commit_group;" ::: "memory"); }
__device__ __forceinline__ void bulk_wait_read() { asm volatile("cp.async.bulk.wait_group.read 0;" ::: "memory"); }
__device__ __forceinline__ void bulk_wait_all() { asm volatile("cp.async.bulk.wait_group 0;" ::: "memory"); }
__device__ __forceinline__ void l2_prefetch(const void* g, uint32_t bytes) { asm volatile("cp.async.bulk.prefetch.L2.global [%0], %1;" ::"l"(g), "r"(bytes) : "memory"); }
__device__ __forceinline__ void map_prefetch(const CUtensorMap* m) { asm volatile("prefetch.tensormap [%0];" ::"l"(m) : "memory"); }
__device__ __forceinline__ void tma2d_store(const CUtensorMap* m, int c0, int c1, uint32_t src) {
  asm volatile("cp.async.bulk.tensor.2d.global.shared::cta.bulk_group [%0, {%2, %3}], [%1];" ::"l"(m), "r"(src), "r"(c0), "r"(c1) : "memory");
}
__device__ __forceinline__ void bulk_s2c(uint32_t rdst, uint32_t src, uint32_t bytes, uint32_t rbar) {
  asm volatile("cp.async.bulk.shared::cluster.shared::cta.mbarrier::complete_tx::bytes [%0], [%1], %2, [%3];" ::"r"(rdst), "r"(src), "r"(bytes), "r"(rbar) : "memory");
}
__device__ __forceinline__ uint32_t mapa(uint32_t a, uint32_t cta) { uint32_t r; asm volatile("mapa.shared::cluster.u32 %0, %1, %2;" : "=r"(r) : "r"(a), "r"(cta)); return r; }
__device__ __forceinline__ bool elect_one() { uint32_t p; asm volatile("{ .reg .pred P; elect.sync _|P, 0xffffffff; selp.u32 %0, 1, 0, P; }" : "=r"(p)); return p; }
__device__ __forceinline__ int laneid() { int l; asm volatile("mov.u32 %0, %%laneid;" : "=r"(l)); return l; }
__device__ __forceinline__ void fence_async() { asm volatile("fence.proxy.async.shared::cta;" ::: "memory"); }
__device__ __forceinline__ void wg_fence() { asm volatile("wgmma.fence.sync.aligned;" ::: "memory"); }
__device__ __forceinline__ void wg_commit() { asm volatile("wgmma.commit_group.sync.aligned;" ::: "memory"); }
template <int N> __device__ __forceinline__ void wg_wait() { asm volatile("wgmma.wait_group.sync.aligned %0;" ::"n"(N) : "memory"); }
template <int N> __device__ __forceinline__ void pin(float* a) {
#pragma unroll
  for (int i = 0; i < N; i++) asm volatile("" : "+f"(a[i])::"memory");
}
template <int N> __device__ __forceinline__ void pinr(uint32_t* a) {
#pragma unroll
  for (int i = 0; i < N; i++) asm volatile("" : "+r"(a[i])::"memory");
}
__device__ __forceinline__ void ldsm4(uint32_t* r, uint32_t a) { asm volatile("ldmatrix.sync.aligned.m8n8.x4.shared.b16 {%0,%1,%2,%3}, [%4];" : "=r"(r[0]), "=r"(r[1]), "=r"(r[2]), "=r"(r[3]) : "r"(a) : "memory"); }
__device__ __forceinline__ void stsm4(uint32_t a, uint32_t r0, uint32_t r1, uint32_t r2, uint32_t r3) { asm volatile("stmatrix.sync.aligned.m8n8.x4.shared.b16 [%0], {%1,%2,%3,%4};" ::"r"(a), "r"(r0), "r"(r1), "r"(r2), "r"(r3) : "memory"); }
__device__ __forceinline__ void stsm2(uint32_t a, uint32_t r0, uint32_t r1) { asm volatile("stmatrix.sync.aligned.m8n8.x2.shared.b16 [%0], {%1,%2};" ::"r"(a), "r"(r0), "r"(r1) : "memory"); }
__device__ __forceinline__ void sts4(uint32_t a, const uint32_t* r) { asm volatile("st.shared.v4.b32 [%0], {%1,%2,%3,%4};" ::"r"(a), "r"(r[0]), "r"(r[1]), "r"(r[2]), "r"(r[3]) : "memory"); }
__device__ __forceinline__ void sta4(uint32_t ra, const uint32_t* r, uint32_t rbar) {
  asm volatile("st.async.weak.shared::cluster.mbarrier::complete_tx::bytes.v4.b32 [%0], {%1,%2,%3,%4}, [%5];" ::"r"(ra), "r"(r[0]), "r"(r[1]), "r"(r[2]), "r"(r[3]), "r"(rbar) : "memory");
}
__device__ __forceinline__ void lds4(uint32_t* r, uint32_t a) { asm volatile("ld.shared.v4.b32 {%0,%1,%2,%3}, [%4];" : "=r"(r[0]), "=r"(r[1]), "=r"(r[2]), "=r"(r[3]) : "r"(a) : "memory"); }
__device__ __forceinline__ void lds4t(uint32_t* r, const uint32_t* o, uint32_t a) {
  r[0] = o[0]; r[1] = o[1]; r[2] = o[2]; r[3] = o[3];
  asm volatile("{ .reg .pred p; setp.ne.u32 p, %4, 1; @p ld.shared.v4.b32 {%0,%1,%2,%3}, [%4]; }" : "+r"(r[0]), "+r"(r[1]), "+r"(r[2]), "+r"(r[3]) : "r"(a) : "memory");
}
__device__ __forceinline__ uint32_t pack2(float lo, float hi) { uint32_t r; asm("cvt.rn.bf16x2.f32 %0, %1, %2;" : "=r"(r) : "f"(hi), "f"(lo)); return r; }
__device__ __forceinline__ float blo(uint32_t v) { return __uint_as_float(v << 16); }
__device__ __forceinline__ float bhi(uint32_t v) { return __uint_as_float(v & 0xFFFF0000u); }
__device__ __forceinline__ float ex2(float x) { float y; asm("ex2.approx.ftz.f32 %0, %1;" : "=f"(y) : "f"(x)); return y; }
__device__ __forceinline__ float rcp(float x) { float y; asm("rcp.approx.ftz.f32 %0, %1;" : "=f"(y) : "f"(x)); return y; }
__device__ __forceinline__ float sqrt_(float x) { float y; asm("sqrt.approx.ftz.f32 %0, %1;" : "=f"(y) : "f"(x)); return y; }
__device__ __forceinline__ void mma16816(float* c, const uint32_t* a, uint32_t b0, uint32_t b1) {
  asm volatile("mma.sync.aligned.m16n8k16.row.col.f32.bf16.bf16.f32 {%0,%1,%2,%3}, {%4,%5,%6,%7}, {%8,%9}, {%0,%1,%2,%3};"
               : "+f"(c[0]), "+f"(c[1]), "+f"(c[2]), "+f"(c[3]) : "r"(a[0]), "r"(a[1]), "r"(a[2]), "r"(a[3]), "r"(b0), "r"(b1));
}
__device__ __forceinline__ float tanh_(float x) { float y; asm("tanh.approx.f32 %0, %1;" : "=f"(y) : "f"(x)); return y; }
__device__ __forceinline__ float bfr(float x) { return __bfloat162float(__float2bfloat16_rn(x)); }
__device__ __forceinline__ uint32_t ld_acq(const uint32_t* p) { uint32_t v; asm volatile("ld.acquire.gpu.global.u32 %0, [%1];" : "=r"(v) : "l"(p) : "memory"); return v; }
__device__ __forceinline__ void poll_flag(const uint32_t* p, uint32_t target) {
  uint32_t n = 0;
  while ((int)(ld_acq(p) - target) < 0) { if (++n > (1u << 21)) asm volatile("trap;"); }
}
#define SIGNAL(p) asm volatile("red.relaxed.gpu.global.add.u32 [%0], 1;" ::"l"(p) : "memory")
__device__ __forceinline__ void ld_ll(uint32_t* r, const uint4* p) {
  asm volatile("{ .reg .b128 t; .reg .b64 lo, hi; ld.relaxed.gpu.global.b128 t, [%4]; mov.b128 {lo,hi}, t; mov.b64 {%0,%1}, lo; mov.b64 {%2,%3}, hi; }" : "=r"(r[0]), "=r"(r[1]), "=r"(r[2]), "=r"(r[3]) : "l"(p) : "memory");
}
__device__ __forceinline__ constexpr uint64_t desc(uint32_t off, uint32_t lbo) {
  return (uint64_t)((SM_BASE + off) >> 4) | ((uint64_t)(lbo >> 4) << 16) | ((uint64_t)64 << 32) | ((uint64_t)1 << 62);
}

__device__ __forceinline__ void rs120_0(float* d, const uint32_t* a, uint64_t db){
  asm volatile("{ .reg .pred p; setp.ne.b32 p, 0, 0; wgmma.mma_async.sync.aligned.m64n120k16.f32.bf16.bf16 {%0, %1, %2, %3, %4, %5, %6, %7, %8, %9, %10, %11, %12, %13, %14, %15, %16, %17, %18, %19, %20, %21, %22, %23, %24, %25, %26, %27, %28, %29, %30, %31, %32, %33, %34, %35, %36, %37, %38, %39, %40, %41, %42, %43, %44, %45, %46, %47, %48, %49, %50, %51, %52, %53, %54, %55, %56, %57, %58, %59}, {%60,%61,%62,%63}, %64, p, 1, 1, 1; }"
   : "=f"(d[0]), "=f"(d[1]), "=f"(d[2]), "=f"(d[3]), "=f"(d[4]), "=f"(d[5]), "=f"(d[6]), "=f"(d[7]), "=f"(d[8]), "=f"(d[9]), "=f"(d[10]), "=f"(d[11]), "=f"(d[12]), "=f"(d[13]), "=f"(d[14]), "=f"(d[15]), "=f"(d[16]), "=f"(d[17]), "=f"(d[18]), "=f"(d[19]), "=f"(d[20]), "=f"(d[21]), "=f"(d[22]), "=f"(d[23]), "=f"(d[24]), "=f"(d[25]), "=f"(d[26]), "=f"(d[27]), "=f"(d[28]), "=f"(d[29]), "=f"(d[30]), "=f"(d[31]), "=f"(d[32]), "=f"(d[33]), "=f"(d[34]), "=f"(d[35]), "=f"(d[36]), "=f"(d[37]), "=f"(d[38]), "=f"(d[39]), "=f"(d[40]), "=f"(d[41]), "=f"(d[42]), "=f"(d[43]), "=f"(d[44]), "=f"(d[45]), "=f"(d[46]), "=f"(d[47]), "=f"(d[48]), "=f"(d[49]), "=f"(d[50]), "=f"(d[51]), "=f"(d[52]), "=f"(d[53]), "=f"(d[54]), "=f"(d[55]), "=f"(d[56]), "=f"(d[57]), "=f"(d[58]), "=f"(d[59]) : "r"(a[0]),"r"(a[1]),"r"(a[2]),"r"(a[3]), "l"(db));
}
__device__ __forceinline__ void rs120_1(float* d, const uint32_t* a, uint64_t db){
  asm volatile("{ .reg .pred p; setp.ne.b32 p, 1, 0; wgmma.mma_async.sync.aligned.m64n120k16.f32.bf16.bf16 {%0, %1, %2, %3, %4, %5, %6, %7, %8, %9, %10, %11, %12, %13, %14, %15, %16, %17, %18, %19, %20, %21, %22, %23, %24, %25, %26, %27, %28, %29, %30, %31, %32, %33, %34, %35, %36, %37, %38, %39, %40, %41, %42, %43, %44, %45, %46, %47, %48, %49, %50, %51, %52, %53, %54, %55, %56, %57, %58, %59}, {%60,%61,%62,%63}, %64, p, 1, 1, 1; }"
   : "+f"(d[0]), "+f"(d[1]), "+f"(d[2]), "+f"(d[3]), "+f"(d[4]), "+f"(d[5]), "+f"(d[6]), "+f"(d[7]), "+f"(d[8]), "+f"(d[9]), "+f"(d[10]), "+f"(d[11]), "+f"(d[12]), "+f"(d[13]), "+f"(d[14]), "+f"(d[15]), "+f"(d[16]), "+f"(d[17]), "+f"(d[18]), "+f"(d[19]), "+f"(d[20]), "+f"(d[21]), "+f"(d[22]), "+f"(d[23]), "+f"(d[24]), "+f"(d[25]), "+f"(d[26]), "+f"(d[27]), "+f"(d[28]), "+f"(d[29]), "+f"(d[30]), "+f"(d[31]), "+f"(d[32]), "+f"(d[33]), "+f"(d[34]), "+f"(d[35]), "+f"(d[36]), "+f"(d[37]), "+f"(d[38]), "+f"(d[39]), "+f"(d[40]), "+f"(d[41]), "+f"(d[42]), "+f"(d[43]), "+f"(d[44]), "+f"(d[45]), "+f"(d[46]), "+f"(d[47]), "+f"(d[48]), "+f"(d[49]), "+f"(d[50]), "+f"(d[51]), "+f"(d[52]), "+f"(d[53]), "+f"(d[54]), "+f"(d[55]), "+f"(d[56]), "+f"(d[57]), "+f"(d[58]), "+f"(d[59]) : "r"(a[0]),"r"(a[1]),"r"(a[2]),"r"(a[3]), "l"(db));
}
__device__ __forceinline__ void rs128_0(float* d, const uint32_t* a, uint64_t db){
  asm volatile("{ .reg .pred p; setp.ne.b32 p, 0, 0; wgmma.mma_async.sync.aligned.m64n128k16.f32.bf16.bf16 {%0, %1, %2, %3, %4, %5, %6, %7, %8, %9, %10, %11, %12, %13, %14, %15, %16, %17, %18, %19, %20, %21, %22, %23, %24, %25, %26, %27, %28, %29, %30, %31, %32, %33, %34, %35, %36, %37, %38, %39, %40, %41, %42, %43, %44, %45, %46, %47, %48, %49, %50, %51, %52, %53, %54, %55, %56, %57, %58, %59, %60, %61, %62, %63}, {%64,%65,%66,%67}, %68, p, 1, 1, 1; }"
   : "=f"(d[0]), "=f"(d[1]), "=f"(d[2]), "=f"(d[3]), "=f"(d[4]), "=f"(d[5]), "=f"(d[6]), "=f"(d[7]), "=f"(d[8]), "=f"(d[9]), "=f"(d[10]), "=f"(d[11]), "=f"(d[12]), "=f"(d[13]), "=f"(d[14]), "=f"(d[15]), "=f"(d[16]), "=f"(d[17]), "=f"(d[18]), "=f"(d[19]), "=f"(d[20]), "=f"(d[21]), "=f"(d[22]), "=f"(d[23]), "=f"(d[24]), "=f"(d[25]), "=f"(d[26]), "=f"(d[27]), "=f"(d[28]), "=f"(d[29]), "=f"(d[30]), "=f"(d[31]), "=f"(d[32]), "=f"(d[33]), "=f"(d[34]), "=f"(d[35]), "=f"(d[36]), "=f"(d[37]), "=f"(d[38]), "=f"(d[39]), "=f"(d[40]), "=f"(d[41]), "=f"(d[42]), "=f"(d[43]), "=f"(d[44]), "=f"(d[45]), "=f"(d[46]), "=f"(d[47]), "=f"(d[48]), "=f"(d[49]), "=f"(d[50]), "=f"(d[51]), "=f"(d[52]), "=f"(d[53]), "=f"(d[54]), "=f"(d[55]), "=f"(d[56]), "=f"(d[57]), "=f"(d[58]), "=f"(d[59]), "=f"(d[60]), "=f"(d[61]), "=f"(d[62]), "=f"(d[63]) : "r"(a[0]),"r"(a[1]),"r"(a[2]),"r"(a[3]), "l"(db));
}
__device__ __forceinline__ void rs128_1(float* d, const uint32_t* a, uint64_t db){
  asm volatile("{ .reg .pred p; setp.ne.b32 p, 1, 0; wgmma.mma_async.sync.aligned.m64n128k16.f32.bf16.bf16 {%0, %1, %2, %3, %4, %5, %6, %7, %8, %9, %10, %11, %12, %13, %14, %15, %16, %17, %18, %19, %20, %21, %22, %23, %24, %25, %26, %27, %28, %29, %30, %31, %32, %33, %34, %35, %36, %37, %38, %39, %40, %41, %42, %43, %44, %45, %46, %47, %48, %49, %50, %51, %52, %53, %54, %55, %56, %57, %58, %59, %60, %61, %62, %63}, {%64,%65,%66,%67}, %68, p, 1, 1, 1; }"
   : "+f"(d[0]), "+f"(d[1]), "+f"(d[2]), "+f"(d[3]), "+f"(d[4]), "+f"(d[5]), "+f"(d[6]), "+f"(d[7]), "+f"(d[8]), "+f"(d[9]), "+f"(d[10]), "+f"(d[11]), "+f"(d[12]), "+f"(d[13]), "+f"(d[14]), "+f"(d[15]), "+f"(d[16]), "+f"(d[17]), "+f"(d[18]), "+f"(d[19]), "+f"(d[20]), "+f"(d[21]), "+f"(d[22]), "+f"(d[23]), "+f"(d[24]), "+f"(d[25]), "+f"(d[26]), "+f"(d[27]), "+f"(d[28]), "+f"(d[29]), "+f"(d[30]), "+f"(d[31]), "+f"(d[32]), "+f"(d[33]), "+f"(d[34]), "+f"(d[35]), "+f"(d[36]), "+f"(d[37]), "+f"(d[38]), "+f"(d[39]), "+f"(d[40]), "+f"(d[41]), "+f"(d[42]), "+f"(d[43]), "+f"(d[44]), "+f"(d[45]), "+f"(d[46]), "+f"(d[47]), "+f"(d[48]), "+f"(d[49]), "+f"(d[50]), "+f"(d[51]), "+f"(d[52]), "+f"(d[53]), "+f"(d[54]), "+f"(d[55]), "+f"(d[56]), "+f"(d[57]), "+f"(d[58]), "+f"(d[59]), "+f"(d[60]), "+f"(d[61]), "+f"(d[62]), "+f"(d[63]) : "r"(a[0]),"r"(a[1]),"r"(a[2]),"r"(a[3]), "l"(db));
}
__device__ __forceinline__ void rs160_0(float* d, const uint32_t* a, uint64_t db){
  asm volatile("{ .reg .pred p; setp.ne.b32 p, 0, 0; wgmma.mma_async.sync.aligned.m64n160k16.f32.bf16.bf16 {%0, %1, %2, %3, %4, %5, %6, %7, %8, %9, %10, %11, %12, %13, %14, %15, %16, %17, %18, %19, %20, %21, %22, %23, %24, %25, %26, %27, %28, %29, %30, %31, %32, %33, %34, %35, %36, %37, %38, %39, %40, %41, %42, %43, %44, %45, %46, %47, %48, %49, %50, %51, %52, %53, %54, %55, %56, %57, %58, %59, %60, %61, %62, %63, %64, %65, %66, %67, %68, %69, %70, %71, %72, %73, %74, %75, %76, %77, %78, %79}, {%80,%81,%82,%83}, %84, p, 1, 1, 1; }"
   : "=f"(d[0]), "=f"(d[1]), "=f"(d[2]), "=f"(d[3]), "=f"(d[4]), "=f"(d[5]), "=f"(d[6]), "=f"(d[7]), "=f"(d[8]), "=f"(d[9]), "=f"(d[10]), "=f"(d[11]), "=f"(d[12]), "=f"(d[13]), "=f"(d[14]), "=f"(d[15]), "=f"(d[16]), "=f"(d[17]), "=f"(d[18]), "=f"(d[19]), "=f"(d[20]), "=f"(d[21]), "=f"(d[22]), "=f"(d[23]), "=f"(d[24]), "=f"(d[25]), "=f"(d[26]), "=f"(d[27]), "=f"(d[28]), "=f"(d[29]), "=f"(d[30]), "=f"(d[31]), "=f"(d[32]), "=f"(d[33]), "=f"(d[34]), "=f"(d[35]), "=f"(d[36]), "=f"(d[37]), "=f"(d[38]), "=f"(d[39]), "=f"(d[40]), "=f"(d[41]), "=f"(d[42]), "=f"(d[43]), "=f"(d[44]), "=f"(d[45]), "=f"(d[46]), "=f"(d[47]), "=f"(d[48]), "=f"(d[49]), "=f"(d[50]), "=f"(d[51]), "=f"(d[52]), "=f"(d[53]), "=f"(d[54]), "=f"(d[55]), "=f"(d[56]), "=f"(d[57]), "=f"(d[58]), "=f"(d[59]), "=f"(d[60]), "=f"(d[61]), "=f"(d[62]), "=f"(d[63]), "=f"(d[64]), "=f"(d[65]), "=f"(d[66]), "=f"(d[67]), "=f"(d[68]), "=f"(d[69]), "=f"(d[70]), "=f"(d[71]), "=f"(d[72]), "=f"(d[73]), "=f"(d[74]), "=f"(d[75]), "=f"(d[76]), "=f"(d[77]), "=f"(d[78]), "=f"(d[79]) : "r"(a[0]),"r"(a[1]),"r"(a[2]),"r"(a[3]), "l"(db));
}
__device__ __forceinline__ void rs160_1(float* d, const uint32_t* a, uint64_t db){
  asm volatile("{ .reg .pred p; setp.ne.b32 p, 1, 0; wgmma.mma_async.sync.aligned.m64n160k16.f32.bf16.bf16 {%0, %1, %2, %3, %4, %5, %6, %7, %8, %9, %10, %11, %12, %13, %14, %15, %16, %17, %18, %19, %20, %21, %22, %23, %24, %25, %26, %27, %28, %29, %30, %31, %32, %33, %34, %35, %36, %37, %38, %39, %40, %41, %42, %43, %44, %45, %46, %47, %48, %49, %50, %51, %52, %53, %54, %55, %56, %57, %58, %59, %60, %61, %62, %63, %64, %65, %66, %67, %68, %69, %70, %71, %72, %73, %74, %75, %76, %77, %78, %79}, {%80,%81,%82,%83}, %84, p, 1, 1, 1; }"
   : "+f"(d[0]), "+f"(d[1]), "+f"(d[2]), "+f"(d[3]), "+f"(d[4]), "+f"(d[5]), "+f"(d[6]), "+f"(d[7]), "+f"(d[8]), "+f"(d[9]), "+f"(d[10]), "+f"(d[11]), "+f"(d[12]), "+f"(d[13]), "+f"(d[14]), "+f"(d[15]), "+f"(d[16]), "+f"(d[17]), "+f"(d[18]), "+f"(d[19]), "+f"(d[20]), "+f"(d[21]), "+f"(d[22]), "+f"(d[23]), "+f"(d[24]), "+f"(d[25]), "+f"(d[26]), "+f"(d[27]), "+f"(d[28]), "+f"(d[29]), "+f"(d[30]), "+f"(d[31]), "+f"(d[32]), "+f"(d[33]), "+f"(d[34]), "+f"(d[35]), "+f"(d[36]), "+f"(d[37]), "+f"(d[38]), "+f"(d[39]), "+f"(d[40]), "+f"(d[41]), "+f"(d[42]), "+f"(d[43]), "+f"(d[44]), "+f"(d[45]), "+f"(d[46]), "+f"(d[47]), "+f"(d[48]), "+f"(d[49]), "+f"(d[50]), "+f"(d[51]), "+f"(d[52]), "+f"(d[53]), "+f"(d[54]), "+f"(d[55]), "+f"(d[56]), "+f"(d[57]), "+f"(d[58]), "+f"(d[59]), "+f"(d[60]), "+f"(d[61]), "+f"(d[62]), "+f"(d[63]), "+f"(d[64]), "+f"(d[65]), "+f"(d[66]), "+f"(d[67]), "+f"(d[68]), "+f"(d[69]), "+f"(d[70]), "+f"(d[71]), "+f"(d[72]), "+f"(d[73]), "+f"(d[74]), "+f"(d[75]), "+f"(d[76]), "+f"(d[77]), "+f"(d[78]), "+f"(d[79]) : "r"(a[0]),"r"(a[1]),"r"(a[2]),"r"(a[3]), "l"(db));
}
__device__ __forceinline__ void rs64_0(float* d, const uint32_t* a, uint64_t db){
  asm volatile("{ .reg .pred p; setp.ne.b32 p, 0, 0; wgmma.mma_async.sync.aligned.m64n64k16.f32.bf16.bf16 {%0, %1, %2, %3, %4, %5, %6, %7, %8, %9, %10, %11, %12, %13, %14, %15, %16, %17, %18, %19, %20, %21, %22, %23, %24, %25, %26, %27, %28, %29, %30, %31}, {%32,%33,%34,%35}, %36, p, 1, 1, 1; }"
   : "=f"(d[0]), "=f"(d[1]), "=f"(d[2]), "=f"(d[3]), "=f"(d[4]), "=f"(d[5]), "=f"(d[6]), "=f"(d[7]), "=f"(d[8]), "=f"(d[9]), "=f"(d[10]), "=f"(d[11]), "=f"(d[12]), "=f"(d[13]), "=f"(d[14]), "=f"(d[15]), "=f"(d[16]), "=f"(d[17]), "=f"(d[18]), "=f"(d[19]), "=f"(d[20]), "=f"(d[21]), "=f"(d[22]), "=f"(d[23]), "=f"(d[24]), "=f"(d[25]), "=f"(d[26]), "=f"(d[27]), "=f"(d[28]), "=f"(d[29]), "=f"(d[30]), "=f"(d[31]) : "r"(a[0]),"r"(a[1]),"r"(a[2]),"r"(a[3]), "l"(db));
}
__device__ __forceinline__ void rs64_1(float* d, const uint32_t* a, uint64_t db){
  asm volatile("{ .reg .pred p; setp.ne.b32 p, 1, 0; wgmma.mma_async.sync.aligned.m64n64k16.f32.bf16.bf16 {%0, %1, %2, %3, %4, %5, %6, %7, %8, %9, %10, %11, %12, %13, %14, %15, %16, %17, %18, %19, %20, %21, %22, %23, %24, %25, %26, %27, %28, %29, %30, %31}, {%32,%33,%34,%35}, %36, p, 1, 1, 1; }"
   : "+f"(d[0]), "+f"(d[1]), "+f"(d[2]), "+f"(d[3]), "+f"(d[4]), "+f"(d[5]), "+f"(d[6]), "+f"(d[7]), "+f"(d[8]), "+f"(d[9]), "+f"(d[10]), "+f"(d[11]), "+f"(d[12]), "+f"(d[13]), "+f"(d[14]), "+f"(d[15]), "+f"(d[16]), "+f"(d[17]), "+f"(d[18]), "+f"(d[19]), "+f"(d[20]), "+f"(d[21]), "+f"(d[22]), "+f"(d[23]), "+f"(d[24]), "+f"(d[25]), "+f"(d[26]), "+f"(d[27]), "+f"(d[28]), "+f"(d[29]), "+f"(d[30]), "+f"(d[31]) : "r"(a[0]),"r"(a[1]),"r"(a[2]),"r"(a[3]), "l"(db));
}
__device__ __forceinline__ void rs56_0(float* d, const uint32_t* a, uint64_t db){
  asm volatile("{ .reg .pred p; setp.ne.b32 p, 0, 0; wgmma.mma_async.sync.aligned.m64n56k16.f32.bf16.bf16 {%0, %1, %2, %3, %4, %5, %6, %7, %8, %9, %10, %11, %12, %13, %14, %15, %16, %17, %18, %19, %20, %21, %22, %23, %24, %25, %26, %27}, {%28,%29,%30,%31}, %32, p, 1, 1, 1; }"
   : "=f"(d[0]), "=f"(d[1]), "=f"(d[2]), "=f"(d[3]), "=f"(d[4]), "=f"(d[5]), "=f"(d[6]), "=f"(d[7]), "=f"(d[8]), "=f"(d[9]), "=f"(d[10]), "=f"(d[11]), "=f"(d[12]), "=f"(d[13]), "=f"(d[14]), "=f"(d[15]), "=f"(d[16]), "=f"(d[17]), "=f"(d[18]), "=f"(d[19]), "=f"(d[20]), "=f"(d[21]), "=f"(d[22]), "=f"(d[23]), "=f"(d[24]), "=f"(d[25]), "=f"(d[26]), "=f"(d[27]) : "r"(a[0]),"r"(a[1]),"r"(a[2]),"r"(a[3]), "l"(db));
}
__device__ __forceinline__ void rs56_1(float* d, const uint32_t* a, uint64_t db){
  asm volatile("{ .reg .pred p; setp.ne.b32 p, 1, 0; wgmma.mma_async.sync.aligned.m64n56k16.f32.bf16.bf16 {%0, %1, %2, %3, %4, %5, %6, %7, %8, %9, %10, %11, %12, %13, %14, %15, %16, %17, %18, %19, %20, %21, %22, %23, %24, %25, %26, %27}, {%28,%29,%30,%31}, %32, p, 1, 1, 1; }"
   : "+f"(d[0]), "+f"(d[1]), "+f"(d[2]), "+f"(d[3]), "+f"(d[4]), "+f"(d[5]), "+f"(d[6]), "+f"(d[7]), "+f"(d[8]), "+f"(d[9]), "+f"(d[10]), "+f"(d[11]), "+f"(d[12]), "+f"(d[13]), "+f"(d[14]), "+f"(d[15]), "+f"(d[16]), "+f"(d[17]), "+f"(d[18]), "+f"(d[19]), "+f"(d[20]), "+f"(d[21]), "+f"(d[22]), "+f"(d[23]), "+f"(d[24]), "+f"(d[25]), "+f"(d[26]), "+f"(d[27]) : "r"(a[0]),"r"(a[1]),"r"(a[2]),"r"(a[3]), "l"(db));
}
__device__ __forceinline__ void rs32_0(float* d, const uint32_t* a, uint64_t db){
  asm volatile("{ .reg .pred p; setp.ne.b32 p, 0, 0; wgmma.mma_async.sync.aligned.m64n32k16.f32.bf16.bf16 {%0, %1, %2, %3, %4, %5, %6, %7, %8, %9, %10, %11, %12, %13, %14, %15}, {%16,%17,%18,%19}, %20, p, 1, 1, 1; }"
   : "=f"(d[0]), "=f"(d[1]), "=f"(d[2]), "=f"(d[3]), "=f"(d[4]), "=f"(d[5]), "=f"(d[6]), "=f"(d[7]), "=f"(d[8]), "=f"(d[9]), "=f"(d[10]), "=f"(d[11]), "=f"(d[12]), "=f"(d[13]), "=f"(d[14]), "=f"(d[15]) : "r"(a[0]),"r"(a[1]),"r"(a[2]),"r"(a[3]), "l"(db));
}
__device__ __forceinline__ void rs32_1(float* d, const uint32_t* a, uint64_t db){
  asm volatile("{ .reg .pred p; setp.ne.b32 p, 1, 0; wgmma.mma_async.sync.aligned.m64n32k16.f32.bf16.bf16 {%0, %1, %2, %3, %4, %5, %6, %7, %8, %9, %10, %11, %12, %13, %14, %15}, {%16,%17,%18,%19}, %20, p, 1, 1, 1; }"
   : "+f"(d[0]), "+f"(d[1]), "+f"(d[2]), "+f"(d[3]), "+f"(d[4]), "+f"(d[5]), "+f"(d[6]), "+f"(d[7]), "+f"(d[8]), "+f"(d[9]), "+f"(d[10]), "+f"(d[11]), "+f"(d[12]), "+f"(d[13]), "+f"(d[14]), "+f"(d[15]) : "r"(a[0]),"r"(a[1]),"r"(a[2]),"r"(a[3]), "l"(db));
}
__device__ __forceinline__ void ss64_0(float* d, uint64_t da, uint64_t db){
  asm volatile("{ .reg .pred p; setp.ne.b32 p, 0, 0; wgmma.mma_async.sync.aligned.m64n64k16.f32.bf16.bf16 {%0, %1, %2, %3, %4, %5, %6, %7, %8, %9, %10, %11, %12, %13, %14, %15, %16, %17, %18, %19, %20, %21, %22, %23, %24, %25, %26, %27, %28, %29, %30, %31}, %32, %33, p, 1, 1, 1, 1; }"
   : "=f"(d[0]), "=f"(d[1]), "=f"(d[2]), "=f"(d[3]), "=f"(d[4]), "=f"(d[5]), "=f"(d[6]), "=f"(d[7]), "=f"(d[8]), "=f"(d[9]), "=f"(d[10]), "=f"(d[11]), "=f"(d[12]), "=f"(d[13]), "=f"(d[14]), "=f"(d[15]), "=f"(d[16]), "=f"(d[17]), "=f"(d[18]), "=f"(d[19]), "=f"(d[20]), "=f"(d[21]), "=f"(d[22]), "=f"(d[23]), "=f"(d[24]), "=f"(d[25]), "=f"(d[26]), "=f"(d[27]), "=f"(d[28]), "=f"(d[29]), "=f"(d[30]), "=f"(d[31]) : "l"(da), "l"(db));
}
__device__ __forceinline__ void ss64_1(float* d, uint64_t da, uint64_t db){
  asm volatile("{ .reg .pred p; setp.ne.b32 p, 1, 0; wgmma.mma_async.sync.aligned.m64n64k16.f32.bf16.bf16 {%0, %1, %2, %3, %4, %5, %6, %7, %8, %9, %10, %11, %12, %13, %14, %15, %16, %17, %18, %19, %20, %21, %22, %23, %24, %25, %26, %27, %28, %29, %30, %31}, %32, %33, p, 1, 1, 1, 1; }"
   : "+f"(d[0]), "+f"(d[1]), "+f"(d[2]), "+f"(d[3]), "+f"(d[4]), "+f"(d[5]), "+f"(d[6]), "+f"(d[7]), "+f"(d[8]), "+f"(d[9]), "+f"(d[10]), "+f"(d[11]), "+f"(d[12]), "+f"(d[13]), "+f"(d[14]), "+f"(d[15]), "+f"(d[16]), "+f"(d[17]), "+f"(d[18]), "+f"(d[19]), "+f"(d[20]), "+f"(d[21]), "+f"(d[22]), "+f"(d[23]), "+f"(d[24]), "+f"(d[25]), "+f"(d[26]), "+f"(d[27]), "+f"(d[28]), "+f"(d[29]), "+f"(d[30]), "+f"(d[31]) : "l"(da), "l"(db));
}
__device__ __forceinline__ void rs64_z(float* d, const uint32_t* a, uint64_t db){
  asm volatile("{ .reg .pred p; setp.ne.b32 p, 0, 0; wgmma.mma_async.sync.aligned.m64n64k16.f32.bf16.bf16 {%0, %1, %2, %3, %4, %5, %6, %7, %8, %9, %10, %11, %12, %13, %14, %15, %16, %17, %18, %19, %20, %21, %22, %23, %24, %25, %26, %27, %28, %29, %30, %31}, {%32,%33,%34,%35}, %36, p, 1, 1, 1; }"
   : "+f"(d[0]), "+f"(d[1]), "+f"(d[2]), "+f"(d[3]), "+f"(d[4]), "+f"(d[5]), "+f"(d[6]), "+f"(d[7]), "+f"(d[8]), "+f"(d[9]), "+f"(d[10]), "+f"(d[11]), "+f"(d[12]), "+f"(d[13]), "+f"(d[14]), "+f"(d[15]), "+f"(d[16]), "+f"(d[17]), "+f"(d[18]), "+f"(d[19]), "+f"(d[20]), "+f"(d[21]), "+f"(d[22]), "+f"(d[23]), "+f"(d[24]), "+f"(d[25]), "+f"(d[26]), "+f"(d[27]), "+f"(d[28]), "+f"(d[29]), "+f"(d[30]), "+f"(d[31]) : "r"(a[0]),"r"(a[1]),"r"(a[2]),"r"(a[3]), "l"(db));
}
__device__ __forceinline__ void rs32_z(float* d, const uint32_t* a, uint64_t db){
  asm volatile("{ .reg .pred p; setp.ne.b32 p, 0, 0; wgmma.mma_async.sync.aligned.m64n32k16.f32.bf16.bf16 {%0, %1, %2, %3, %4, %5, %6, %7, %8, %9, %10, %11, %12, %13, %14, %15}, {%16,%17,%18,%19}, %20, p, 1, 1, 1; }"
   : "+f"(d[0]), "+f"(d[1]), "+f"(d[2]), "+f"(d[3]), "+f"(d[4]), "+f"(d[5]), "+f"(d[6]), "+f"(d[7]), "+f"(d[8]), "+f"(d[9]), "+f"(d[10]), "+f"(d[11]), "+f"(d[12]), "+f"(d[13]), "+f"(d[14]), "+f"(d[15]) : "r"(a[0]),"r"(a[1]),"r"(a[2]),"r"(a[3]), "l"(db));
}
__device__ __forceinline__ void sk64_0(float* d, uint64_t da, uint64_t db){
  asm volatile("{ .reg .pred p; setp.ne.b32 p, 0, 0; wgmma.mma_async.sync.aligned.m64n64k16.f32.bf16.bf16 {%0, %1, %2, %3, %4, %5, %6, %7, %8, %9, %10, %11, %12, %13, %14, %15, %16, %17, %18, %19, %20, %21, %22, %23, %24, %25, %26, %27, %28, %29, %30, %31}, %32, %33, p, 1, 1, 0, 1; }"
   : "=f"(d[0]), "=f"(d[1]), "=f"(d[2]), "=f"(d[3]), "=f"(d[4]), "=f"(d[5]), "=f"(d[6]), "=f"(d[7]), "=f"(d[8]), "=f"(d[9]), "=f"(d[10]), "=f"(d[11]), "=f"(d[12]), "=f"(d[13]), "=f"(d[14]), "=f"(d[15]), "=f"(d[16]), "=f"(d[17]), "=f"(d[18]), "=f"(d[19]), "=f"(d[20]), "=f"(d[21]), "=f"(d[22]), "=f"(d[23]), "=f"(d[24]), "=f"(d[25]), "=f"(d[26]), "=f"(d[27]), "=f"(d[28]), "=f"(d[29]), "=f"(d[30]), "=f"(d[31]) : "l"(da), "l"(db));
}
__device__ __forceinline__ void sk64_1(float* d, uint64_t da, uint64_t db){
  asm volatile("{ .reg .pred p; setp.ne.b32 p, 1, 0; wgmma.mma_async.sync.aligned.m64n64k16.f32.bf16.bf16 {%0, %1, %2, %3, %4, %5, %6, %7, %8, %9, %10, %11, %12, %13, %14, %15, %16, %17, %18, %19, %20, %21, %22, %23, %24, %25, %26, %27, %28, %29, %30, %31}, %32, %33, p, 1, 1, 0, 1; }"
   : "+f"(d[0]), "+f"(d[1]), "+f"(d[2]), "+f"(d[3]), "+f"(d[4]), "+f"(d[5]), "+f"(d[6]), "+f"(d[7]), "+f"(d[8]), "+f"(d[9]), "+f"(d[10]), "+f"(d[11]), "+f"(d[12]), "+f"(d[13]), "+f"(d[14]), "+f"(d[15]), "+f"(d[16]), "+f"(d[17]), "+f"(d[18]), "+f"(d[19]), "+f"(d[20]), "+f"(d[21]), "+f"(d[22]), "+f"(d[23]), "+f"(d[24]), "+f"(d[25]), "+f"(d[26]), "+f"(d[27]), "+f"(d[28]), "+f"(d[29]), "+f"(d[30]), "+f"(d[31]) : "l"(da), "l"(db));
}
__device__ __forceinline__ void sk64_z(float* d, uint64_t da, uint64_t db){
  asm volatile("{ .reg .pred p; setp.ne.b32 p, 0, 0; wgmma.mma_async.sync.aligned.m64n64k16.f32.bf16.bf16 {%0, %1, %2, %3, %4, %5, %6, %7, %8, %9, %10, %11, %12, %13, %14, %15, %16, %17, %18, %19, %20, %21, %22, %23, %24, %25, %26, %27, %28, %29, %30, %31}, %32, %33, p, 1, 1, 0, 1; }"
   : "+f"(d[0]), "+f"(d[1]), "+f"(d[2]), "+f"(d[3]), "+f"(d[4]), "+f"(d[5]), "+f"(d[6]), "+f"(d[7]), "+f"(d[8]), "+f"(d[9]), "+f"(d[10]), "+f"(d[11]), "+f"(d[12]), "+f"(d[13]), "+f"(d[14]), "+f"(d[15]), "+f"(d[16]), "+f"(d[17]), "+f"(d[18]), "+f"(d[19]), "+f"(d[20]), "+f"(d[21]), "+f"(d[22]), "+f"(d[23]), "+f"(d[24]), "+f"(d[25]), "+f"(d[26]), "+f"(d[27]), "+f"(d[28]), "+f"(d[29]), "+f"(d[30]), "+f"(d[31]) : "l"(da), "l"(db));
}
__device__ __forceinline__ void sk32_0(float* d, uint64_t da, uint64_t db){
  asm volatile("{ .reg .pred p; setp.ne.b32 p, 0, 0; wgmma.mma_async.sync.aligned.m64n32k16.f32.bf16.bf16 {%0, %1, %2, %3, %4, %5, %6, %7, %8, %9, %10, %11, %12, %13, %14, %15}, %16, %17, p, 1, 1, 0, 1; }"
   : "=f"(d[0]), "=f"(d[1]), "=f"(d[2]), "=f"(d[3]), "=f"(d[4]), "=f"(d[5]), "=f"(d[6]), "=f"(d[7]), "=f"(d[8]), "=f"(d[9]), "=f"(d[10]), "=f"(d[11]), "=f"(d[12]), "=f"(d[13]), "=f"(d[14]), "=f"(d[15]) : "l"(da), "l"(db));
}
__device__ __forceinline__ void sk32_1(float* d, uint64_t da, uint64_t db){
  asm volatile("{ .reg .pred p; setp.ne.b32 p, 1, 0; wgmma.mma_async.sync.aligned.m64n32k16.f32.bf16.bf16 {%0, %1, %2, %3, %4, %5, %6, %7, %8, %9, %10, %11, %12, %13, %14, %15}, %16, %17, p, 1, 1, 0, 1; }"
   : "+f"(d[0]), "+f"(d[1]), "+f"(d[2]), "+f"(d[3]), "+f"(d[4]), "+f"(d[5]), "+f"(d[6]), "+f"(d[7]), "+f"(d[8]), "+f"(d[9]), "+f"(d[10]), "+f"(d[11]), "+f"(d[12]), "+f"(d[13]), "+f"(d[14]), "+f"(d[15]) : "l"(da), "l"(db));
}
__device__ __forceinline__ void sk32_z(float* d, uint64_t da, uint64_t db){
  asm volatile("{ .reg .pred p; setp.ne.b32 p, 0, 0; wgmma.mma_async.sync.aligned.m64n32k16.f32.bf16.bf16 {%0, %1, %2, %3, %4, %5, %6, %7, %8, %9, %10, %11, %12, %13, %14, %15}, %16, %17, p, 1, 1, 0, 1; }"
   : "+f"(d[0]), "+f"(d[1]), "+f"(d[2]), "+f"(d[3]), "+f"(d[4]), "+f"(d[5]), "+f"(d[6]), "+f"(d[7]), "+f"(d[8]), "+f"(d[9]), "+f"(d[10]), "+f"(d[11]), "+f"(d[12]), "+f"(d[13]), "+f"(d[14]), "+f"(d[15]) : "l"(da), "l"(db));
}
template<int N> __device__ __forceinline__ void ssz(float* d, uint64_t da, uint64_t db){
  if constexpr (N==64) sk64_z(d,da,db); else sk32_z(d,da,db);
}
template<int N> __device__ __forceinline__ void rsz(float* d, const uint32_t* a, uint64_t db){
  if constexpr (N==64) rs64_z(d,a,db); else rs32_z(d,a,db);
}
template<int N> __device__ __forceinline__ void ssk(float* d, uint64_t da, uint64_t db, bool first){
  if constexpr (N==64) { if(first) sk64_0(d,da,db); else sk64_1(d,da,db); } else { if(first) sk32_0(d,da,db); else sk32_1(d,da,db); }
}
template<int N> __device__ __forceinline__ void rs(float* d, const uint32_t* a, uint64_t db, bool first){
  if constexpr (N==120) { if(first) rs120_0(d,a,db); else rs120_1(d,a,db); }
  if constexpr (N==128) { if(first) rs128_0(d,a,db); else rs128_1(d,a,db); }
  if constexpr (N==160) { if(first) rs160_0(d,a,db); else rs160_1(d,a,db); }
  if constexpr (N==64) { if(first) rs64_0(d,a,db); else rs64_1(d,a,db); }
  if constexpr (N==56) { if(first) rs56_0(d,a,db); else rs56_1(d,a,db); }
  if constexpr (N==32) { if(first) rs32_0(d,a,db); else rs32_1(d,a,db); }
}

constexpr float LOG2E = 1.4426950408889634f;
#define EPI_TS(x) x
#define TS7(i)
#define BAR(i) (sb + MISC + 8u * (uint32_t)(i))
#define BBARI(k) asm volatile("{ .reg .pred p; setp.ne.u32 p, %0, %1; @p bra B_L; trap; B_L: }" ::"r"(sb), "n"(k) : "memory")
#define BBAR() asm volatile("{ .reg .pred p; setp.ne.u32 p, %0, %1; @p bra B_L; trap; B_L: }" ::"r"(sb), "n"(__LINE__ * 2 + 1) : "memory")

__host__ __device__ constexpr int unitB(int g) { return g == 0 ? 0 : g == 1 ? 3 : g == 6 ? 8 : 14 + 3 * (g - 2); }
__host__ __device__ constexpr int unitC(int g) { return g == 0 ? 11 : g == 1 ? 5 : g == 6 ? 8 : 14 + 3 * (g - 2); }
__host__ __device__ constexpr int unitD(int g) { return g == 0 ? 11 : 14 + 3 * ((g - 1) & 3); }
__host__ __device__ constexpr int depB(int g) { return g < 2 ? XC0 : g == 2 ? EA1 : g == 3 ? EA2 : g == 4 ? EA4 : g == 5 ? EA5 : KVST; }
__host__ __device__ constexpr int depC(int g) { return g == 0 ? KVFREE : EB1 + g - 1; }
__host__ __device__ constexpr int depD(int g) { return g == 0 ? EC0 : g < 5 ? EC0 + g + 1 : g == 5 ? ED1 : ED2; }
__host__ __device__ constexpr int eid(int P, int g) {
  return P == 0 ? (g == 1 ? EA1 : g == 2 ? EA2 : g >= 4 ? EA4 + g - 4 : -1)
       : P == 1 ? (g >= 1 ? EB1 + g - 1 : -1)
       : P == 2 ? EC0 + g
                : (g == 1 ? ED1 : g == 2 ? ED2 : g >= 4 ? ED4 + g - 4 : -1);
}
template <int P> __host__ __device__ constexpr int unitP(int g) { return P == 0 ? 14 + 2 * g : P == 1 ? unitB(g) : P == 2 ? unitC(g) : unitD(g); }
template <typename Fn> __host__ __device__ constexpr uint64_t packtab(Fn f) { uint64_t t = 0; for (int g = 0; g < 7; g++) t |= (uint64_t)f(g) << (8 * g); return t; }

template <int P, int N, typename Fn, typename Fp>
__device__ __forceinline__ void pass1(float* acc, const uint32_t* xf, uint32_t sb, uint32_t pb, bool lane0, uint64_t sh, Fn shadow, Fp post) {
#pragma unroll
  for (int g = 0; g < 7; g++) {
    mbar_wait(BAR(FA + 7 * P + g));
    wg_fence();
#pragma unroll
    for (int kk = 0; kk < 4; kk++) {
      if (P == 1) {
        rs<128>(acc, xf + 16 * g + 4 * kk, desc(unitP<P>(g) * U + kk * 2048, U), g == 0 && kk == 0);
        rs<56>(acc + 64, xf + 16 * g + 4 * kk, desc((unitP<P>(g) + 2) * U + kk * 2048, U) + sh, g == 0 && kk == 0);
      } else {
        rs<N>(acc, xf + 16 * g + 4 * kk, desc(unitP<P>(g) * U + kk * 2048, U) + (P == 0 ? sh : 0), g == 0 && kk == 0);
      }
    }
    wg_commit();
    shadow(g);
    if (g > 0) {
      wg_wait<1>();
      if (lane0) {
        if (eid(P, g - 1) >= 0) mbar_arrive(BAR(eid(P, g - 1)));
        if ((P == 1 || P == 2) && g == 2) mbar_arrive_remote(pb + MISC + 8u * (PF + P - 1));
        if (P == 3 && g == 1) mbar_arrive_remote(pb + MISC + 8u * (PF + 2));
      }
      post(g);
    }
  }
  wg_wait<0>();
  if (lane0) mbar_arrive(BAR(eid(P, 6)));
  pin<N / 2>(acc);
}

template <int ID> __device__ __forceinline__ void hfrag64(uint32_t* h, float* acc, const float* rs_, uint32_t sb, int wg) {
  const float hr[2] = {0.5f * rs_[0], 0.5f * rs_[1]};
#pragma unroll
  for (int i = 0; i < 32; i++) {
    acc[32 + i] *= acc[i];
    acc[i] *= hr[(i >> 1) & 1];
    if (i < 16) acc[i] = tanh_(acc[i]);
  }
  pin<64>(acc);
  BBARI(ID * 4 + 1);
  EPI_TS(if (ID == 1) CTS(21));
  const float c[2] = {hr[0] * rs_[0], hr[1] * rs_[1]};
#pragma unroll
  for (int i = 16; i < 32; i++) acc[i] = tanh_(acc[i]);
#pragma unroll
  for (int m = 0; m < 8; m++) h[m] = pack2(acc[32 + 2 * m] * fmaf(acc[2 * m], c[m & 1], c[m & 1]), acc[33 + 2 * m] * fmaf(acc[2 * m + 1], c[m & 1], c[m & 1]));
  pin<16>(acc + 16);
  pinr<8>(h);
  BBARI(ID * 4 + 3);
  EPI_TS(if (ID == 1) CTS(22));
#pragma unroll
  for (int m = 8; m < 16; m++) h[m] = pack2(acc[32 + 2 * m] * fmaf(acc[2 * m], c[m & 1], c[m & 1]), acc[33 + 2 * m] * fmaf(acc[2 * m + 1], c[m & 1], c[m & 1]));
}
__device__ __forceinline__ void phi1(float* e, float* a, const float* rs_) {
  const float rl[2] = {rs_[0] * (0.5f * LOG2E), rs_[1] * (0.5f * LOG2E)};
#pragma unroll
  for (int i = 0; i < 28; i++) {
    const float u = a[i] * rl[(i >> 1) & 1];
    e[i] = ex2(u - fabsf(u));
    a[i] = fmaf(u + fabsf(u), 0.6931471805599453f, 1e-6f);
  }
  pin<28>(e);
  pin<28>(a);
}

template <int NP> __device__ __forceinline__ void stage_ll(uint32_t dst, const float* a, uint32_t par) {
#pragma unroll
  for (int q = 0; q < NP; q++) {
    const uint32_t w[4] = {(pack2(a[8 * q], a[8 * q + 1]) & 0xFFFFFFFEu) | par, pack2(a[8 * q + 2], a[8 * q + 3]), pack2(a[8 * q + 4], a[8 * q + 5]),
                           pack2(a[8 * q + 6], a[8 * q + 7])};
    sts4(dst + q * 512, w);
  }
}
template <int NP> __device__ __forceinline__ void send_ll(uint4* dst, const float* a, uint32_t par) {
#pragma unroll
  for (int q = 0; q < NP; q++)
    asm volatile("{ .reg .b128 t; .reg .b64 lo, hi; mov.b64 lo, {%1,%2}; mov.b64 hi, {%3,%4}; mov.b128 t, {lo,hi}; st.relaxed.gpu.global.b128 [%0], t; }" ::"l"(dst + q * 32),
                 "r"((pack2(a[8 * q], a[8 * q + 1]) & 0xFFFFFFFEu) | par), "r"(pack2(a[8 * q + 2], a[8 * q + 3])), "r"(pack2(a[8 * q + 4], a[8 * q + 5])), "r"(pack2(a[8 * q + 6], a[8 * q + 7])) : "memory");
}
#define LL_LD(o, a, b, c, d) "ld.relaxed.gpu.global.b128 w, [%16+" #o "]; mov.b128 {lo,hi}, w; mov.b64 {%" #a ",%" #b "}, lo; mov.b64 {%" #c ",%" #d "}, hi;\n"
template <int NP> __device__ __forceinline__ void recv_ll(float* a, uint32_t* v, const uint4* p, uint32_t par) {
  if constexpr (NP == 4) {
    asm volatile(
        "{ .reg .pred p; .reg .b32 t, u, n; .reg .b128 w; .reg .b64 lo, hi;\n"
        "mov.u32 n, 0;\n"
        "R_L: lop3.b32 t, %0, %4, %17, 0x7E; lop3.b32 u, %8, %12, %17, 0x7E; lop3.b32 t, t, u, 1, 0xA8;\n"
        "setp.eq.u32 p, t, 0; vote.sync.all.pred p, p, 0xffffffff; @p bra R_D;\n"
        LL_LD(0, 0, 1, 2, 3) LL_LD(512, 4, 5, 6, 7) LL_LD(1024, 8, 9, 10, 11) LL_LD(1536, 12, 13, 14, 15)
        "add.u32 n, n, 1; setp.lt.u32 p, n, 2097152; @p bra R_L; trap;\n"
        "R_D: }"
        : "+r"(v[0]), "+r"(v[1]), "+r"(v[2]), "+r"(v[3]), "+r"(v[4]), "+r"(v[5]), "+r"(v[6]), "+r"(v[7]), "+r"(v[8]), "+r"(v[9]), "+r"(v[10]),
          "+r"(v[11]), "+r"(v[12]), "+r"(v[13]), "+r"(v[14]), "+r"(v[15])
        : "l"(p), "r"(par)
        : "memory");
  } else {
    asm volatile(
        "{ .reg .pred p; .reg .b32 t, n; .reg .b128 w; .reg .b64 lo, hi;\n"
        "mov.u32 n, 0;\n"
        "R_L: lop3.b32 t, %0, %4, %9, 0x7E; and.b32 t, t, 1;\n"
        "setp.eq.u32 p, t, 0; vote.sync.all.pred p, p, 0xffffffff; @p bra R_D;\n"
        "ld.relaxed.gpu.global.b128 w, [%8]; mov.b128 {lo,hi}, w; mov.b64 {%0,%1}, lo; mov.b64 {%2,%3}, hi;\n"
        "ld.relaxed.gpu.global.b128 w, [%8+512]; mov.b128 {lo,hi}, w; mov.b64 {%4,%5}, lo; mov.b64 {%6,%7}, hi;\n"
        "add.u32 n, n, 1; setp.lt.u32 p, n, 2097152; @p bra R_L; trap;\n"
        "R_D: }"
        : "+r"(v[0]), "+r"(v[1]), "+r"(v[2]), "+r"(v[3]), "+r"(v[4]), "+r"(v[5]), "+r"(v[6]), "+r"(v[7])
        : "l"(p), "r"(par)
        : "memory");
  }
#pragma unroll
  for (int i = 0; i < 4 * NP; i++) { a[2 * i] += blo(v[i]); a[2 * i + 1] += bhi(v[i]); }
}

__device__ __forceinline__ void load_x(const __nv_bfloat16* x, uint32_t sb, int r, int warp, int lane) {
  const int l8 = lane >> 3, c = lane & 7;
  const char* src = reinterpret_cast<const char*>(x + (size_t)(r * 128 + warp * 16 + l8) * DM + c * 8);
  const uint32_t dst = sb + (uint32_t)((warp >> 2) * (7 * U) + ((warp & 3) * 16 + l8) * 128 + ((c ^ l8) << 4));
#pragma unroll
  for (int kb = 0; kb < 7; kb++) {
#pragma unroll
    for (int q = 0; q < 4; q++)
      asm volatile("cp.async.cg.shared.global [%0], [%1], 16;" ::"r"((dst ^ ((q & 1) << 6)) + kb * U + q * 512), "l"(src + q * 4 * DM * 2 + kb * 128) : "memory");
    asm volatile("cp.async.commit_group;" ::: "memory");
  }
}
template <int N> __device__ __forceinline__ void cp_wait() { asm volatile("cp.async.wait_group %0;" ::"n"(N) : "memory"); }

#define LANE() const int ln = laneid(), g8 = ln >> 2, t4 = ln & 3; (void)g8; (void)t4
template <bool Y>
__device__ __forceinline__ void tail(const Maps& M, uint32_t* hf, float* acc, const uint32_t* sg, float* rs_, uint32_t sb, uint32_t pb, int warp, bool lane0) {
  constexpr int N2 = Y ? 64 : 32, N3 = Y ? 32 : 64;
  const int wg = warp >> 2, w4 = warp & 3;
  constexpr int BB = Y ? 200 : 300;
  float a1[64];
  const float hr[2] = {0.5f * rs_[0], 0.5f * rs_[1]}, hc[2] = {hr[0] * rs_[0], hr[1] * rs_[1]};
  auto e1 = [&](int lo) {
#pragma unroll
    for (int i = lo; i < lo + 16; i++) { acc[32 + i] *= acc[i]; acc[i] = tanh_(acc[i] * hr[(i >> 1) & 1]); }
    pin<16>(acc + lo); pin<16>(acc + 32 + lo);
  };
  auto e2 = [&](int lo) {
#pragma unroll
    for (int m = lo; m < lo + 8; m++) hf[32 + m] = pack2(acc[32 + 2 * m] * fmaf(acc[2 * m], hc[m & 1], hc[m & 1]), acc[33 + 2 * m] * fmaf(acc[2 * m + 1], hc[m & 1], hc[m & 1]));
    pinr<8>(hf + 32 + lo);
  };
  const uint32_t doff = (uint32_t)(wg * 12288 + w4 * 3072 + laneid() * 16);
  auto send = [&](int s) {
    sta4(pb + 11 * U + doff + s * 512, hf + 32 + 4 * s, pb + MISC + 8u * (HF + 4) + wg * 8);
    sta4(pb + 11 * U + doff + s * 512 + 512, hf + 36 + 4 * s, pb + MISC + 8u * (HF + 4) + wg * 8);
  };
  mbar_wait(BAR(PF + 2));
  mbar_wait(BAR(FT + 0));
  wg_fence();
#pragma unroll
  for (int s = 0; s < 4; s++) rs<128>(a1, hf + 4 * s, desc(s * 2048, 16384), s == 0);
  wg_commit();
  BBARI(BB + 1);
  TS7(21);
#define SGP 3
  auto e3 = [&]() {
#pragma unroll
    for (int m = 0; m < 8; m++) {
      const int w = m & 1;
      hf[48 + m] = pack2(blo(sg[m]) * (acc[64 + 2 * m] * rs_[w]), bhi(sg[m]) * (acc[65 + 2 * m] * rs_[w]));
    }
    pinr<8>(hf + 48);
    send(4);
  };
  if (SGP == 0) e3();
  e1(0);
  if (SGP == 3) { e2(0); send(0); }
  BBARI(BB + 3);
  wg_fence();
#pragma unroll
  for (int s = 4; s < 8; s++) rs<128>(a1, hf + 4 * s, desc(s * 2048, 16384), false);
  wg_commit();
  BBARI(BB + 5);
  TS7(22);
  if (SGP != 3) { e2(0); send(0); }
  if (SGP == 1) e3();
  e1(16);
  if (SGP == 3) { e2(8); send(2); }
  mbar_wait(BAR(FT + 1));
  wg_fence();
#pragma unroll
  for (int s = 0; s < 4; s++) rs<128>(a1, hf + 56 + 4 * s, desc(4 * U + s * 2048, 16384), false);
  wg_commit();
  BBARI(BB + 7);
  TS7(23);
  if (SGP != 3) { e2(8); send(2); }
  if (SGP >= 2) e3();
  BBARI(BB + 9);
  wg_fence();
#pragma unroll
  for (int s = 4; s < 8; s++) rs<128>(a1, hf + 56 + 4 * s, desc(4 * U + s * 2048, 16384), false);
  wg_commit();
  wg_wait<2>();
  if (lane0) mbar_arrive(BAR(ET + 0));
  TS7(24);
  mbar_wait(BAR(FT + 2));
  wg_fence();
#pragma unroll
  for (int s = 0; s < 3; s++) rs<128>(a1, hf + 32 + 4 * s, desc(21 * U + s * 2048, 12288), false);
  wg_commit();
  CTS(9);
  wg_fence();
#pragma unroll
  for (int s = 3; s < 6; s++) rs<128>(a1, hf + 32 + 4 * s, desc(21 * U + s * 2048, 12288), false);
  wg_commit();
  wg_wait<2>();
  if (lane0) mbar_arrive(BAR(ET + 1));
  const uint64_t adw = (uint64_t)(wg * 512);
  float aw[N3 / 2];
  auto wtile = [&](int t) {
    constexpr int wu[7] = {8, 24, 17, 21, 14, 21, 0};
    mbar_wait(BAR(FW + t));
    wg_fence();
#pragma unroll
    for (int kk = 0; kk < 4; kk++) {
      const uint64_t da = desc(wu[t] * U + kk * 32, 16) + adw, db = desc((wu[t] + 2) * U + kk * 2048, U);
      ssk<N3>(aw, da, db, t == 0 && kk == 0);
    }
    wg_commit();
  };
  wtile(0);
  wg_wait<1>();
  if (lane0) mbar_arrive(BAR(ET + 2));
  wtile(1);
  wg_wait<1>();
  if (lane0) mbar_arrive(BAR(EW0));
  wtile(2);
  TS7(25);
  mbar_wait(BAR(HF + 4) + wg * 8);
#pragma unroll
  for (int s = 0; s < 6; s++) lds4(hf + 88 + 4 * s, sb + 11 * U + doff + s * 512);
  CTS(10);
  wg_wait<1>();
  if (lane0) mbar_arrive(BAR(EW1));
  mbar_wait(BAR(FT + 3));
  wg_fence();
#pragma unroll
  for (int s = 0; s < 6; s++) rs<128>(a1, hf + 88 + 4 * s, desc(14 * U + s * 2048, 12288), false);
  wg_commit();
  if (lane0) mbar_arrive(BAR(LD2));
  wg_wait<1>();
  if (lane0) mbar_arrive(BAR(EW2));
  wtile(3);
  TS7(26);
  uint32_t par;
  asm volatile("ld.shared.u32 %0, [%1];" : "=r"(par) : "r"(BAR(NBAR)) : "memory");
  const uint32_t lb = sb + (uint32_t)((wg ? 13 : 10) * U + w4 * 2048);
  mbar_wait(BAR(EW0));
  wg_wait<1>();
  if (lane0) mbar_arrive(BAR(ET + 3));
  pin<64>(a1);
  TS7(27);
  stage_ll<4>(sb + 8 * U + (uint32_t)(warp * 2048) + laneid() * 16, a1, par & 1);
  __syncwarp();
  if (lane0) mbar_arrive_n(BAR(SND) + wg * 8, 2);
  float* a2 = a1;
  float* a3 = a1;
  mbar_wait(BAR(FT + 4));
  wg_fence();
#pragma unroll
  for (int s = 0; s < 6; s++) { if (s == 0) rsz<N2>(a2, hf, desc(0, U)); else rs<N2>(a2, hf + 4 * s, desc(s * 2048, U), false); }
  wg_commit();
  wg_wait<1>();
  if (lane0) mbar_arrive(BAR(EW3));
  mbar_wait(BAR(LD2));
  stage_ll<2>(lb + laneid() * 16, a1 + 32, par & 1);
  BBARI(BB + 11);
  wg_fence();
#pragma unroll
  for (int s = 6; s < 14; s++) rs<N2>(a2, hf + 4 * s, desc(s * 2048, U), false);
  wg_commit();
  stage_ll<2>(lb + laneid() * 16 + 1024, a1 + 48, par & 1);
  __syncwarp();
  if (lane0) mbar_arrive_n(BAR(SND + 2) + wg * 8, 2);
  mbar_wait(BAR(FT + 5));
  wg_fence();
#pragma unroll
  for (int s = 0; s < 14; s++) rs<N2>(a2, hf + 56 + 4 * s, desc(4 * U + s * 2048, U), false);
  wg_commit();
  wg_wait<1>();
  if (lane0) mbar_arrive(BAR(ET + 4));
  wtile(4);
  wg_wait<1>();
  if (lane0) mbar_arrive(BAR(ET + 5));
  pin<N2 / 2>(a2);
  const int bid = par >> 8, r = bid >> 3, kq = (bid >> 1) & 3, n = bid & 1;
  uint4* const pbase = g_p + (size_t)((r * 2 + n) * 4) * 3072 + laneid();
  mbar_wait(BAR(FT + 6));
  mbar_wait(BAR(FT + 7));
  send_ll<N2 / 16>(pbase + (Y ? n + 2 : 3 - 3 * n) * 3072 + (Y ? 2 : kq - n) * 1024 + warp * (N2 * 2), a2, par & 1);
  CTS(16);
  wg_fence();
#pragma unroll
  for (int s = 0; s < 14; s++) { if (s == 0) rsz<N3>(a3, hf, desc(24 * U, U)); else rs<N3>(a3, hf + 4 * s, desc(24 * U + s * 2048, U), false); }
  wg_commit();
  TS7(28);
  wg_fence();
#pragma unroll
  for (int s = 0; s < 14; s++) rs<N3>(a3, hf + 56 + 4 * s, desc(17 * U + s * 2048, U), false);
  wg_commit();
  CTS(17);
  const int row = r * 128 + warp * 16, col = Y ? 192 + 32 * n : 192 * n + 64 * kq;
  const uint4* pin_ = pbase + kq * 3072 + warp * (N3 * 2);
  auto recv = [&](int i) {
    uint32_t v[N3 / 4];
    const uint32_t src = sb + (uint32_t)((i == 0 ? 3 + 4 * wg : 8 + wg) * U + w4 * (N3 * 32)) + laneid() * 16;
    mbar_wait(BAR(LF + 2 * i) + wg * 8);
#pragma unroll
    for (int q = 0; q < N3 / 16; q++) lds4(v + 4 * q, src + q * 512);
    recv_ll<N3 / 16>(a3, v, pin_ + i * 1024, par);
    pin<N3 / 2>(a3);
  };
  wtile(5);
  wg_wait<1>();
  pin<N3 / 2>(a3);
  CTS(11);
  uint32_t v2[N3 / 4];
  auto ld2 = [&]() {
#pragma unroll
    for (int q = 0; q < N3 / 16; q++) ld_ll(v2 + 4 * q, pin_ + 2048 + q * 32);
  };
#define L2P 1
  if (L2P == 0) ld2();
  recv(0);
  CTS(18);
  wtile(6);
  if (L2P == 1) { BBARI(BB + 13); ld2(); }
  recv(1);
  if (L2P == 2) ld2();
  recv_ll<N3 / 16>(a3, v2, pin_ + 2048, par);
  CTS(19);
  CTS(20);
  {
    float th[N3 / 2];
#pragma unroll
    for (int i = 0; i < N3 / 2; i++) { a3[i] *= 0.5f; th[i] = tanh_(a3[i]); }
    pin<N3 / 2>(th);
#pragma unroll
    for (int i = 0; i < N3 / 2; i++) a3[i] = fmaf(a3[i], th[i], a3[i]);
  }
  LANE();
  const uint32_t sa = lb + (uint32_t)((ln & 15) * 128 + (((ln >> 4) ^ (ln & 7)) << 4));
  uint32_t xr[N3 / 4];
  mbar_wait(BAR(wg ? XR1 : XR0));
#pragma unroll
  for (int kk = 0; kk < N3 / 16; kk++) ldsm4(xr + 4 * kk, sa ^ (kk << 5));
  wg_wait<0>();
  pin<N3 / 2>(aw);
  CTS(12);
#pragma unroll
  for (int m = 0; m < N3 / 4; m++) xr[m] = pack2(fmaf(aw[2 * m], a3[2 * m], blo(xr[m])), fmaf(aw[2 * m + 1], a3[2 * m + 1], bhi(xr[m])));
#pragma unroll
  for (int kk = 0; kk < N3 / 16; kk++) stsm4(sa ^ (kk << 5), xr[4 * kk], xr[4 * kk + 1], xr[4 * kk + 2], xr[4 * kk + 3]);
  fence_async();
  __syncwarp();
  if (lane0) {
    tma2d_store(Y ? &M.outb : &M.outa, col, row, lb);
    bulk_commit();
    bulk_wait_read();
  }
}

__global__ void __cluster_dims__(2, 1, 1) __launch_bounds__(384, 1)
fused_kernel(const __grid_constant__ Maps M, const __grid_constant__ Ptrs P) {
  const __nv_bfloat16* xg = P.x;
  extern __shared__ __align__(1024) uint8_t smem_raw[];
  uint32_t sb = smem_u32(smem_raw);
  asm volatile("" : "+r"(sb));
  const int tid = threadIdx.x;
  const int warp = __shfl_sync(0xffffffffu, tid >> 5, 0);
  const int lane = tid & 31;
  const int wg = warp >> 2;
  const int bid = P.role[blockIdx.x], r = bid >> 3, j = bid & 7, kq = j >> 1, n = j & 1;

  if (warp < 8) CTS(27);
  if (warp < 4) load_x(xg, sb, r, warp, lane);
  if (warp < 8) CTS(28);
  if (elect_one()) {
    if ((warp >> 1) == 4) {
      const uint32_t ba = BAR(FA) + (warp - 8) * 8;
      mbar_init(ba, 1);
      mbar_expect_tx(ba, 2 * U);
      tma3d(sb + (14 + 2 * (warp - 8)) * U, &M.kv, j * 56 - 8 * n, (warp - 8) * 64, 1, ba);
    }
    const uint32_t b0 = BAR(2 + 8 * warp), cnt = warp < 6 ? 1u : 8u;
#pragma unroll
    for (int i = 0; i < 8; i++) mbar_init(b0 + 8 * i, cnt);
    if (warp >= 2) { mbar_init(BAR(94 + 2 * warp), 8); mbar_init(BAR(95 + 2 * warp), 8); }
  }
  asm volatile("fence.mbarrier_init.release.cluster;" ::: "memory");
  __syncwarp();
  if (warp < 8) CTS(29);
  asm volatile("barrier.cluster.arrive.relaxed.aligned;" ::: "memory");

  if (wg == 2) {
    asm volatile("setmaxnreg.dec.sync.aligned.u32 24;");
    if (warp == 8) {
      asm volatile("barrier.cluster.wait.acquire.aligned;" ::: "memory");
      if (elect_one()) {
        TS(2, 9);
        const int f0 = j * 224, ca = j * 56 - 8 * n;
#pragma unroll 1
        for (int g = 2; g < 7; g++) {
          mbar_expect_tx(BAR(FA + g), 2 * U);
          tma3d(sb + (14 + 2 * g) * U, &M.kv, ca, g * 64, 1, BAR(FA + g));
        }
        TS(2, 1);
        const int ro = f0 + 32 * n, rg = f0 + 192 * (1 - n);
#pragma unroll 1
        for (int p = 0; p < 3; p++) {
          const uint64_t ut = p == 0 ? packtab(unitB) : p == 1 ? packtab(unitC) : packtab(unitD);
          const uint64_t dt = p == 0 ? packtab(depB) : p == 1 ? packtab(depC) : packtab(depD);
          const CUtensorMap* m3 = p == 0 ? &M.wq : p == 1 ? &M.w1b : &M.w3b;
          const int c3 = p == 0 ? ca : rg;
#pragma unroll 1
          for (int g = 0; g < 7; g++) {
            const uint32_t dst = sb + (uint32_t)((ut >> (8 * g)) & 255) * U;
            const uint32_t fb = BAR(FB + 7 * p + g);
            mbar_expect_tx(fb, p == 0 ? 3 * U : 20480u);
            mbar_wait(BAR((uint32_t)((dt >> (8 * g)) & 255)));
            tma2d(dst, &M.w1a, ro + 64 * p, g * 64, fb);
            tma2d(dst + U, &M.w3a, ro + 64 * p, g * 64, fb);
            tma2d(dst + 2 * U, m3, c3, g * 64, fb);
          }
          TS(2, 2 + p);
        }
        const bool isy = kq == 3 - 3 * n;
        const int io = isy ? 2 : kq - n;
        mbar_wait(BAR(OFREE));
        const int cA = 256 * n + 64 * (io == 2 ? 0 : io + 1), cB = 256 * n + 64 * (io == 0 ? 2 : io - 1), cW = 256 * n + 64 * io, cN = 192 + 32 * n;
#pragma unroll 1
        for (int i = 0; i < 8; i++) {
          const int t = i;
          const uint32_t dst = sb + (uint32_t)((0x111804000E150400ull >> (8 * i)) & 255) * U;
          const uint64_t dt = (uint64_t)LH0 | ((uint64_t)LH1 << 8) | ((uint64_t)ED4 << 16) | ((uint64_t)ED5 << 24) | ((uint64_t)(ET + 0) << 32) | ((uint64_t)(ET + 1) << 40) |
                              ((uint64_t)EW1 << 48) | ((uint64_t)EW2 << 56);
          const uint32_t fb = BAR(FT + t);
          const int pe = t & 1, nn = n ^ pe, fb0 = (j ^ pe) * 224;
          const int r0 = fb0 + 32 * nn, r1 = fb0 + 192 * (1 - nn);
          const bool wide = (t >= 6) != isy;
          mbar_expect_tx(fb, t < 2 ? 32768u : t < 4 ? 24576u : wide ? 28672u : 14336u);
          mbar_wait(BAR((uint32_t)((dt >> (8 * i)) & 255)));
          if (t < 2) {
            tma2d(dst, &M.w2a, cA, r0, fb); tma2d(dst + U, &M.w2a, cA, r0 + 64, fb);
            tma2d(dst + 2 * U, &M.w2a, cB, r0, fb); tma2d(dst + 3 * U, &M.w2a, cB, r0 + 64, fb);
          } else if (t < 4) {
            tma2d(dst, &M.w2a, cA, r0 + 128, fb); tma2d(dst + U, &M.w2b, cA, r1, fb);
            tma2d(dst + 12288, &M.w2a, cB, r0 + 128, fb); tma2d(dst + 12288 + U, &M.w2b, cB, r1, fb);
          } else {
            const CUtensorMap* m = wide ? &M.w2a : &M.w2c;
            const int c = wide ? cW : cN;
            tma2d(dst, m, c, r0, fb); tma2d(dst + U, m, c, r0 + 64, fb); tma2d(dst + 2 * U, m, c, r0 + 128, fb);
            tma2d(dst + 3 * U, m + 1, c, r1, fb);
          }
          TS(2, 10 + i);
        }
        TS(2, 7);
        const uint32_t ni = isy ? 4096u : 8192u;
        const char* pi = reinterpret_cast<const char*>(g_p + (size_t)((r * 2 + n) * 4 + kq) * 3072);
        uint32_t par, todo = 15;
        asm volatile("ld.shared.u32 %0, [%1];" : "=r"(par) : "r"(BAR(NBAR)) : "memory");
#pragma unroll
        for (int i = 0; i < 4; i++) { mbar_expect_tx(BAR(LF + i), ni); mbar_arrive_n(BAR(LF + i), 7); }
        mbar_wait(BAR(ET + 5));
        TS(2, 18);
        while (todo & 63) {
          uint32_t w[4];
#pragma unroll
          for (int i = 0; i < 4; i++) asm volatile("ld.relaxed.gpu.global.u32 %0, [%1];" : "=r"(w[i]) : "l"(pi + (i >> 1) * 16384 + ((i & 1) + 1) * ni - 16) : "memory");
#pragma unroll
          for (int i = 0; i < 4; i++) {
            if ((todo >> i & 1) && ((w[i] ^ par) & 1) == 0) {
              if (i >= 2) mbar_wait(BAR(RA));
              todo ^= 1u << i;
              asm volatile("cp.async.bulk.shared::cluster.global.mbarrier::complete_tx::bytes [%0], [%1], %2, [%3];" ::"r"(sb + (i < 2 ? 3 + 4 * i : 6 + i) * U),
                           "l"(pi + (i >> 1) * 16384 + (i & 1) * ni), "r"(ni), "r"(BAR(LF + i)) : "memory");
              TS(2, 19 + i);
            }
          }
          todo += 64;
          if (todo > (1u << 27)) asm volatile("trap;");
        }
        TSDUMP(2);
      }
    } else {
      if (elect_one()) {
        const CUtensorMap* mp = &M.kv + (warp - 9) * 6;
        if ((sb & 0x3FFFFu) != SM_BASE) asm volatile("trap;");
#pragma unroll
        for (int i = 0; i < 6; i++) map_prefetch(mp + i);
      }
      const uint32_t ep = g_epoch[blockIdx.x] + 1;
      const int at = tid - 288;
      if (at < 32) reinterpret_cast<float4*>(g_kv + ((ep & 1) ^ 1) * (8 * 2048) + j * 2048 + r * 128)[at] = make_float4(0.f, 0.f, 0.f, 0.f);
      asm volatile("barrier.cluster.wait.acquire.aligned;" ::: "memory");
      float* kv = g_kv + (ep & 1) * (8 * 2048) + j * 2048;
      if (warp == 10 && elect_one()) {
#pragma unroll
        for (int i = 0; i < 6; i++) mbar_expect_tx(BAR(HF + i), i < 4 ? 8192u : 12288u);
        mbar_expect_tx(BAR(KVL), KV_BYTES);
      }
      mbar_wait(BAR(EA6));
      const uint32_t kvm = sb + KVM_U * U;
#pragma unroll 1
      for (int c = at; c < 512; c += 96) {
        const int d = c >> 3, cc = c & 7;
        const bool used = d < 56 && (cc == 7 || (d < 28 ? cc < 4 : (cc >= 3)));
        if (!used) { const uint32_t z[4] = {0, 0, 0, 0}; sts4(kvm + d * 128 + ((cc ^ (d & 7)) << 4), z); }
      }
      if (warp == 9) {
        mbar_wait(BAR(KVST));
        if (elect_one()) {
          asm volatile("cp.reduce.async.bulk.global.shared::cta.bulk_group.add.f32 [%0], [%1], %2;" ::"l"(kv), "r"(sb + 12 * U), "r"(KV_BYTES) : "memory");
          bulk_commit();
          bulk_wait_read();
          mbar_arrive_n(BAR(KVFREE), 8);
          bulk_wait_all();
          TS(3, 4);
          SIGNAL(&g_f1[j * 32]);
          TS(3, 0);
          poll_flag(&g_f1[j * 32], 16u * ep);
          asm volatile("fence.proxy.async.global;" ::: "memory");
          TS(3, 1);
          asm volatile("cp.async.bulk.shared::cluster.global.mbarrier::complete_tx::bytes [%0], [%1], %2, [%3];" ::"r"(sb + 27 * U), "l"(kv), "r"(KV_BYTES), "r"(BAR(KVL)) : "memory");
        }
        __syncwarp();
      }
      mbar_wait(BAR(KVL));
#pragma unroll 1
      for (int idx = at; idx < 280; idx += 96) {
        const int d = idx / 5, m = idx - d * 5;
        const bool hi = d >= 28;
        const uint32_t src = sb + 27 * U + d * (KVP * 4);
        uint32_t w[4] = {0, 0, 0, 0}, v[4];
        int cc;
        if (m == 4) {
          cc = 7;
          lds4(v, src + 128);
          w[0] = pack2(__uint_as_float(v[0]), 0.f) << (hi ? 16 : 0);
        } else {
          cc = m + (hi ? 3 : 0);
          const int o = 8 * m - (hi ? 4 : 0);
          if (o >= 0) { lds4(v, src + o * 4); w[0] = pack2(__uint_as_float(v[0]), __uint_as_float(v[1])); w[1] = pack2(__uint_as_float(v[2]), __uint_as_float(v[3])); }
          if (o + 4 < 28) { lds4(v, src + o * 4 + 16); w[2] = pack2(__uint_as_float(v[0]), __uint_as_float(v[1])); w[3] = pack2(__uint_as_float(v[2]), __uint_as_float(v[3])); }
        }
        sts4(kvm + d * 128 + ((cc ^ (d & 7)) << 4), w);
      }
      if (at == 0) asm volatile("st.shared.u32 [%0], %1;" ::"r"(BAR(NBAR)), "r"((ep & 1) | (uint32_t)(bid << 8)) : "memory");
      fence_async();
      __syncwarp();
      if (lane == 0) mbar_arrive_n(BAR(KVM), warp < 11 ? 3 : 2);
      if (at == 0) TS(3, 2);
      if (warp < 11) {
        const int h = warp - 9;
        const uint32_t pb = mapa(sb, n ^ 1);
#pragma unroll 1
        for (int b = 0; b < 2; b++) {
          const uint32_t off = (uint32_t)(4 * b * U + h * 8192 + lane * 16), rb = pb + MISC + 8u * (HF + 2 * b + h);
          mbar_wait(BAR(HS + 2 * b + h));
          mbar_wait(BAR(PF + b));
#pragma unroll 1
          for (int i = 0; i < 8192; i += 1024) {
            uint32_t v[8];
            lds4(v, sb + off + i); lds4(v + 4, sb + off + i + 512);
            sta4(pb + 2 * U + off + i, v, rb); sta4(pb + 2 * U + off + i + 512, v + 4, rb);
          }
          if (h == 1 && lane == 0) { TS(3, 22 + b); }
        }
        mbar_wait(BAR(OST + h));
        if (elect_one()) {
          tma2d_store(&M.ost, j * 56, r * 128 + h * 64, sb + (h ? 8 : 27) * U);
          bulk_commit();
          bulk_wait_read();
          mbar_arrive_n(BAR(OFREE), 4);
          bulk_wait_all();
          SIGNAL(&g_f2[r * 32]);
          if (h == 1) { TS(3, 3); }
          const bool isy = kq == 3 - 3 * n;
          const int io = isy ? 2 : kq - n;
          const int ca = n + (io == 2 ? 0 : io + 1), cb = n + (io == 0 ? 2 : io - 1);
          uint4* pbase = g_p + (size_t)((r * 2 + n) * 4) * 3072;
          const uint32_t lb = sb + (h ? 13 : 10) * U;
          mbar_wait(BAR(SND + h));
          fence_async();
          bulk_s2g(pbase + ca * 3072 + (isy ? 2048 : 0) + h * 512, sb + (8 + h) * U, 8192);
          bulk_commit();
          if (h == 1) { TS(3, 7); }
          mbar_wait(BAR(SND + 2 + h));
          fence_async();
          bulk_s2g(pbase + cb * 3072 + (isy ? 2048 : 1024) + h * 512, lb, 8192);
          bulk_commit();
          if (h == 1) { TS(3, 8); }
          asm volatile("cp.async.bulk.wait_group.read 1;" ::: "memory");
          mbar_arrive_n(BAR(RA), 4);
          bulk_wait_read();
          if (h == 1) { TS(3, 9); }
          const uint32_t xb = BAR(h ? XR1 : XR0);
          mbar_expect_tx(xb, isy ? 4096u : 8192u);
          mbar_arrive_n(xb, 7);
#pragma unroll
          for (int i = 0; i < 4; i++) tma2d(lb + i * 2048, isy ? &M.xrb : &M.xra, isy ? 192 + 32 * n : 192 * n + 64 * kq, r * 128 + h * 64 + i * 16, xb);
          if (h == 1) { TS(3, 17); }
        }
      } else if (elect_one()) {
        poll_flag(&g_f2[r * 32], 16u * ep);
        asm volatile("fence.proxy.async.global;" ::: "memory");
        TS(3, 5);
        const bool isy = kq == 3 - 3 * n;
        const int co = isy ? 192 + 32 * n : 192 * n + 64 * kq;
#pragma unroll 1
        for (int t = 0; t < 7; t++) {
          const uint64_t dt = (uint64_t)ED4 | ((uint64_t)ED4 << 8) | ((uint64_t)ED6 << 16) | ((uint64_t)(ET + 2) << 24) | ((uint64_t)(ET + 3) << 32) |
                              ((uint64_t)EW3 << 40) | ((uint64_t)(ET + 4) << 48);
          const uint32_t dst = sb + (uint32_t)((0x00150E15111808ull >> (8 * t)) & 255) * U;
          mbar_expect_tx(BAR(FW + t), isy ? 20480u : 24576u);
          mbar_wait(BAR((uint32_t)((dt >> (8 * t)) & 255)));
          tma2d(dst, &M.o, t * 64, r * 128, BAR(FW + t));
          tma2d(dst + 2 * U, isy ? &M.wob : &M.woa, co, t * 64, BAR(FW + t));
          TS(3, 10 + t);
        }
        g_epoch[blockIdx.x] = ep;
        TS(3, 6);
      }
    }
  } else {
    asm volatile("setmaxnreg.inc.sync.aligned.u32 240;");
    asm volatile("barrier.cluster.wait.acquire.aligned;" ::: "memory");
    CTS(0);
    if (wg == 1) load_x(xg, sb, r, warp, lane);
    const int w4 = warp & 3;
    const bool lane0 = lane == 0;
    const uint32_t pb = mapa(sb, n ^ 1);
    const uint32_t so = sb + (uint32_t)((wg * 64 + w4 * 16 + (lane & 7) + ((lane >> 3) & 1) * 8) * 128 + (((lane >> 4) ^ (lane & 7)) << 4));
    uint32_t xf[112];
    float rs_[2];
    uint32_t pm0, pm1;
    float q0, q1;
    {
      float cm[2][4], ga[2][4], gb[2][4];
#pragma unroll
      for (int i = 0; i < 8; i++) cm[i >> 2][i & 3] = ga[i >> 2][i & 3] = gb[i >> 2][i & 3] = 0.f;
      const uint32_t sx = so + wg * (6 * U);
      uint32_t s0 = 0, s1 = 0;
#pragma unroll
      for (int kb = 0; kb < 7; kb++) {
        if (kb == 0) cp_wait<6>(); else if (kb == 1) cp_wait<5>(); else if (kb == 2) cp_wait<4>(); else if (kb == 3) cp_wait<3>();
        else if (kb == 4) cp_wait<2>(); else if (kb == 5) cp_wait<1>(); else cp_wait<0>();
        __syncwarp();
        if (kb == 0) CTS(14);
        EPI_TS(if (kb == 3) CTS(26));
        if (kb == 6) CTS(15);
#pragma unroll
        for (int kk = 0; kk < 4; kk++) ldsm4(xf + 16 * kb + 4 * kk, (sx ^ (kk << 5)) + kb * U);
#pragma unroll
        for (int kk = 0; kk < 4; kk++) mma16816(cm[kk & 1], xf + 16 * kb + 4 * kk, 0x3F803F80u, 0x3F803F80u);
        if (kb == 0) {
          s0 = __byte_perm(__shfl_sync(0xffffffffu, xf[0], lane & 28), 0, 0x1010);
          s1 = __byte_perm(__shfl_sync(0xffffffffu, xf[1], lane & 28), 0, 0x1010);
        }
        if (kb == 6) {
          const float m0 = (cm[0][0] + cm[1][0]) * (1.0f / 448.0f), m1 = (cm[0][2] + cm[1][2]) * (1.0f / 448.0f);
          pm0 = pack2(m0, m0); pm1 = pack2(m1, m1);
          q0 = m0 - blo(s0); q1 = m1 - blo(s1);
          __syncwarp();
          if (lane0) mbar_arrive_n(BAR(XC0) + wg * 8, 2);
        }
#pragma unroll
        for (int kk = 0; kk < 4; kk++) {
          const uint32_t* a = xf + 16 * kb + 4 * kk;
          uint32_t t[4];
#pragma unroll
          for (int i = 0; i < 4; i++) asm volatile("sub.rn.bf16x2 %0, %1, %2;" : "=r"(t[i]) : "r"(a[i]), "r"((i & 1) ? s1 : s0));
          mma16816(ga[kk & 1], t, t[0], t[2]);
          mma16816(gb[kk & 1], t, t[1], t[3]);
        }
      }
#pragma unroll
      for (int i = 0; i < 16; i++) asm volatile("sub.rn.bf16x2 %0, %0, %1;" : "+r"(xf[i]) : "r"((i & 1) ? pm1 : pm0));
      const bool odd = (lane >> 2) & 1;
      rs_[0] = odd ? ga[0][1] + ga[1][1] : ga[0][0] + ga[1][0];
      rs_[1] = odd ? gb[0][3] + gb[1][3] : gb[0][2] + gb[1][2];
    }
    CTS(1);
    uint32_t pq[14];
    {
      float acc[60];
      pass1<0, 120>(acc, xf, sb, pb, lane0, (uint64_t)n, [&](int g) {
        if (g < 6) {
#pragma unroll
          for (int i = 0; i < 16; i++) asm volatile("sub.rn.bf16x2 %0, %0, %1;" : "+r"(xf[16 * g + 16 + i]) : "r"((i & 1) ? pm1 : pm0));
        }
        if (g == 1) {
          const int src = (lane & 28) | (lane >> 3);
          const float v0 = fmaxf(fmaf(__shfl_sync(0xffffffffu, rs_[0], src), 1.0f / 448.0f, -q0 * q0), 0.f);
          const float v1 = fmaxf(fmaf(__shfl_sync(0xffffffffu, rs_[1], src), 1.0f / 448.0f, -q1 * q1), 0.f);
          rs_[0] = rcp(bfr(sqrt_(bfr(bfr(v0) + 1e-5f))));
          rs_[1] = rcp(bfr(sqrt_(bfr(bfr(v1) + 1e-5f))));
          pin<2>(rs_);
        }
      }, [&](int) {});
      CTS(2);
      LANE();
      uint32_t pk[16], pv[16];
      float e[28];
      phi1(e, acc, rs_);
#pragma unroll
      for (int m = 0; m < 14; m++) pv[m] = pack2(acc[32 + 2 * m] * rs_[m & 1], acc[33 + 2 * m] * rs_[m & 1]);
      pv[14] = pv[15] = t4 == 0 ? 0x3F803F80u : 0u;
      pinr<16>(pv);
      mbar_wait(BAR(XC1));
#pragma unroll
      for (int kk = 0; kk < 4; kk++) stsm4((so ^ (kk << 5)) + 10 * U, pv[4 * kk], pv[4 * kk + 1], pv[4 * kk + 2], pv[4 * kk + 3]);
#pragma unroll
      for (int m = 0; m < 14; m++) pk[m] = pack2(e[2 * m] + acc[2 * m], e[2 * m + 1] + acc[2 * m + 1]);
      pk[14] = pk[15] = 0u;
#pragma unroll
      for (int kk = 0; kk < 4; kk++) stsm4((so ^ (kk << 5)) + 8 * U, pk[4 * kk], pk[4 * kk + 1], pk[4 * kk + 2], pk[4 * kk + 3]);
      fence_async();
      __syncwarp();
      if (lane0) mbar_arrive(BAR(PKST));
      if (wg == 1) {
        float kv[32];
        mbar_wait(BAR(PKST));
        wg_fence();
#pragma unroll
        for (int ks = 0; ks < 8; ks++) {
          if (ks == 0) ss64_0(kv, desc(8 * U, U), desc(10 * U, U));
          else ss64_1(kv, desc(8 * U + ks * 2048, U), desc(10 * U + ks * 2048, U));
        }
        wg_commit();
        wg_wait<0>();
        pin<32>(kv);
#pragma unroll
        for (int h = 0; h < 2; h++) {
          const int d = w4 * 16 + g8 + 8 * h;
          const uint32_t lim = d < 28 ? 0u : d < 56 ? 28u : 1000u;
          const uint32_t ka = sb + 12 * U + (uint32_t)d * (KVP * 4) + (uint32_t)(2 * t4) * 4 - lim * 4;
#pragma unroll
          for (int i = 0; i < 7; i++)
            asm volatile("{ .reg .pred p; setp.lt.u32 p, %0, 28; @p st.shared.v2.f32 [%1], {%2,%3}; }" ::"r"((uint32_t)(8 * i + 2 * t4) - lim), "r"(ka + 32 * i), "f"(kv[4 * i + 2 * h]), "f"(kv[4 * i + 2 * h + 1]) : "memory");
          asm volatile("{ .reg .pred p; setp.lt.u32 p, %0, 56; @p st.shared.f32 [%1], %2; }" ::"r"((uint32_t)(d + 64 * t4)), "r"(sb + 12 * U + (uint32_t)d * (KVP * 4) + 128), "f"(kv[28 + 2 * h]) : "memory");
        }
        fence_async();
        __syncwarp();
        if (lane0) mbar_arrive_n(BAR(KVST), 2);
      }
      CTS(3);
    }
    const uint32_t hoff = (uint32_t)(wg * 8192 + w4 * 2048 + laneid() * 16);
    {
      float acc[92];
      pass1<1, 184>(acc, xf, sb, pb, lane0, (uint64_t)n, [&](int) {}, [&](int) {});
      CTS(4);
      pin<2>(rs_);
      uint32_t h[16];
      hfrag64<1>(h, acc, rs_, sb, wg);
      pinr<16>(h);
      mbar_wait(BAR(EB1));
      EPI_TS(CTS(23));
#pragma unroll
      for (int s = 0; s < 4; s++) sts4(sb + hoff + s * 512, h + 4 * s);
      __syncwarp();
      if (lane0) mbar_arrive_n(BAR(HS) + wg * 8, 2);
      EPI_TS(CTS(24));
      float e[28];
      phi1(e, acc + 64, rs_);
      EPI_TS(CTS(25));
#pragma unroll
      for (int m = 0; m < 14; m++) pq[m] = pack2(e[2 * m] + acc[64 + 2 * m], e[2 * m + 1] + acc[65 + 2 * m]);
      pq[12] ^= sb; pq[13] ^= sb;
      pinr<14>(pq);
      CTS(5);
    }
    uint32_t sg[8];
    {
      float acc[80];
      pass1<2, 160>(acc, xf, sb, pb, lane0, 0, [&](int) {}, [&](int) {});
      CTS(6);
      pin<2>(rs_);
      uint32_t h[16];
      hfrag64<2>(h, acc, rs_, sb, wg);
      pinr<16>(h);
      mbar_wait(BAR(EC0 + 1));
#pragma unroll
      for (int s = 0; s < 4; s++) sts4(sb + 4 * U + hoff + s * 512, h + 4 * s);
      __syncwarp();
      if (lane0) mbar_arrive_n(BAR(HS + 2) + wg * 8, 2);
      float nm[32];
      mbar_wait(BAR(KVM));
      {
        uint32_t q3[4];
        asm volatile("xor.b32 %0, %4, %6; xor.b32 %1, %5, %6; mov.b32 %2, 0; mov.b32 %3, 0;" : "=r"(q3[0]), "=r"(q3[1]), "=r"(q3[2]), "=r"(q3[3]) : "r"(pq[12]), "r"(pq[13]), "r"(sb));
        wg_fence();
        rs64_0(nm, pq, desc(KVM_U * U, U));
        rs64_1(nm, pq + 4, desc(KVM_U * U + 2048, U));
        rs64_1(nm, pq + 8, desc(KVM_U * U + 4096, U));
        rs64_1(nm, q3, desc(KVM_U * U + 6144, U));
      }
      wg_commit();
      float th[16];
      {
        const float hr[2] = {0.5f * rs_[0], 0.5f * rs_[1]};
#pragma unroll
        for (int i = 0; i < 16; i++) { acc[64 + i] *= hr[(i >> 1) & 1]; th[i] = tanh_(acc[64 + i]); }
        pin<16>(th); pin<16>(acc + 64);
      }
#pragma unroll
      for (int m = 0; m < 8; m++) sg[m] = pack2(fmaf(acc[64 + 2 * m], th[2 * m], acc[64 + 2 * m]), fmaf(acc[65 + 2 * m], th[2 * m + 1], acc[65 + 2 * m]));
      pinr<8>(sg);
      wg_wait<0>();
      pin<32>(nm);
      LANE();
      float rd[4];
#pragma unroll
      for (int i = 0; i < 4; i++) rd[i] = rcp(__shfl_sync(0xffffffffu, nm[28 + i], ln & 28) + 1e-6f);
      uint32_t ob[14];
#pragma unroll
      for (int i = 0; i < 7; i++) {
        const bool h0 = i < 3 || (i == 3 && t4 < 2);
        const float ra = h0 ? rd[0] : rd[1], rb = h0 ? rd[2] : rd[3];
        ob[2 * i] = pack2(nm[4 * i] * ra, nm[4 * i + 1] * ra);
        ob[2 * i + 1] = pack2(nm[4 * i + 2] * rb, nm[4 * i + 3] * rb);
      }
      mbar_wait(BAR(wg ? EC0 + 6 : EC0 + 1));
      const uint32_t sa = sb + (wg ? 8 : 27) * U + (uint32_t)(w4 * 16 + (ln & 15)) * 112;
#pragma unroll
      for (int kk = 0; kk < 3; kk++) stsm4(sa + (ln >> 4) * 16 + kk * 32, ob[4 * kk], ob[4 * kk + 1], ob[4 * kk + 2], ob[4 * kk + 3]);
      stsm2(sa + 96, ob[12], ob[13]);
      fence_async();
      __syncwarp();
      if (lane0) mbar_arrive_n(BAR(OST) + wg * 8, 2);
      CTS(7);
    }
    uint32_t hf[112];
    float acc[80];
    pass1<3, 160>(acc, xf, sb, pb, lane0, 0, [&](int) {}, [&](int g) {
      if (g == 2 || g == 4) {
        const int b = (g >> 1) - 1;
        mbar_wait(BAR(HF + 2 * b) + wg * 8);
#pragma unroll
        for (int s = 0; s < 4; s++) { lds4t(hf + 16 * b + 4 * s, xf + 32 * b + 4 * s, sb + 4 * b * U + hoff + s * 512); lds4t(hf + 56 + 16 * b + 4 * s, xf + 32 * b + 16 + 4 * s, sb + (4 * b + 2) * U + hoff + s * 512); }
        pinr<16>(hf + 16 * b); pinr<16>(hf + 56 + 16 * b);
      }
      if (g == 3 || g == 5) {
        const int b = (g >> 1) - 1;
        const uint32_t* u = hf + 16 * b;
        uint32_t one;
        if (g == 3) BBARI(101); else BBARI(103);
        asm volatile("{ .reg .b32 t; lop3.b32 t, %1, %2, %3, 0xFE; lop3.b32 t, t, %4, %5, 0xFE; lop3.b32 t, t, %6, %7, 0xFE; lop3.b32 t, t, %8, 1, 0xFE;\n"
                     "redux.sync.min.u32 t, t, 0xffffffff; min.u32 %0, t, 1; }"
                     : "=r"(one) : "r"(u[0]), "r"(u[4]), "r"(u[8]), "r"(u[12]), "r"(u[56]), "r"(u[60]), "r"(u[64]), "r"(u[68]));
        if (lane0) mbar_arrive_n(BAR(LH0 + b), one);
      }
    });
    CTS(8);
    if (kq == 3 - 3 * n) tail<true>(M, hf, acc, sg, rs_, sb, pb, warp, lane0);
    else tail<false>(M, hf, acc, sg, rs_, sb, pb, warp, lane0);
    CTS(13);
    if ((tid & 127) == 0) { GTS(wg, 30); TSDUMP(wg); if (wg == 1) { TSDUMP(3); } }
  }
}

typedef CUresult (*EncodeFn)(CUtensorMap*, CUtensorMapDataType, cuuint32_t, void*, const cuuint64_t*, const cuuint64_t*, const cuuint32_t*,
                             const cuuint32_t*, CUtensorMapInterleave, CUtensorMapSwizzle, CUtensorMapL2promotion, CUtensorMapFloatOOBfill);

void make_map(EncodeFn enc, CUtensorMap* m, const void* base, uint64_t cols, uint64_t rows, uint32_t bc, uint32_t br, bool sw) {
  cuuint64_t dims[2] = {cols, rows}, str[1] = {cols * 2};
  cuuint32_t box[2] = {bc, br}, es[2] = {1, 1};
  enc(m, CU_TENSOR_MAP_DATA_TYPE_BFLOAT16, 2, const_cast<void*>(base), dims, str, box, es, CU_TENSOR_MAP_INTERLEAVE_NONE,
      sw ? CU_TENSOR_MAP_SWIZZLE_128B : CU_TENSOR_MAP_SWIZZLE_NONE, CU_TENSOR_MAP_L2_PROMOTION_L2_128B, CU_TENSOR_MAP_FLOAT_OOB_FILL_NONE);
}
void make_map3(EncodeFn enc, CUtensorMap* m, const void* base, uint64_t sec, uint64_t nsec, uint64_t rows, uint32_t bc, uint32_t br, uint32_t bs) {
  cuuint64_t dims[3] = {sec, rows, nsec}, str[2] = {sec * nsec * 2, sec * 2};
  cuuint32_t box[3] = {bc, br, bs}, es[3] = {1, 1, 1};
  enc(m, CU_TENSOR_MAP_DATA_TYPE_BFLOAT16, 3, const_cast<void*>(base), dims, str, box, es, CU_TENSOR_MAP_INTERLEAVE_NONE,
      CU_TENSOR_MAP_SWIZZLE_128B, CU_TENSOR_MAP_L2_PROMOTION_L2_128B, CU_TENSOR_MAP_FLOAT_OOB_FILL_NONE);
}

}

extern "C" void kernel_launch(void* const* d_in, const int* in_sizes, int n_in, void* d_out, int out_size) {
  (void)in_sizes; (void)n_in; (void)out_size;
  void* fn = nullptr;
  cudaDriverEntryPointQueryResult q;
  cudaGetDriverEntryPoint("cuTensorMapEncodeTiled", &fn, cudaEnableDefault, &q);
  EncodeFn enc = (EncodeFn)fn;
  void* op = nullptr;
  cudaGetSymbolAddress(&op, g_o);
  Maps M;
  make_map3(enc, &M.kv, d_in[1], DM, 3, DM, 64, 64, 2);
  make_map(enc, &M.wq, d_in[1], 3 * DM, DM, 64, 64, true);
  make_map(enc, &M.w1a, d_in[4], FF, DM, 64, 64, true);
  make_map(enc, &M.w3a, d_in[5], FF, DM, 64, 64, true);
  make_map(enc, &M.w1b, d_in[4], FF, DM, 32, 64, true);
  make_map(enc, &M.w3b, d_in[5], FF, DM, 32, 64, true);
  make_map(enc, &M.w2a, d_in[6], DM, FF, 64, 64, true);
  make_map(enc, &M.w2b, d_in[6], DM, FF, 64, 32, true);
  make_map(enc, &M.w2c, d_in[6], DM, FF, 32, 64, true);
  make_map(enc, &M.w2d, d_in[6], DM, FF, 32, 32, true);
  make_map(enc, &M.woa, d_in[2], DM, DM, 64, 64, true);
  make_map(enc, &M.wob, d_in[2], DM, DM, 32, 64, true);
  make_map(enc, &M.o, op, DM, SEQ, 64, 128, true);
  make_map(enc, &M.ost, op, DM, SEQ, 56, 64, false);
  make_map(enc, &M.outa, d_out, DM, SEQ, 64, 16, true);
  make_map(enc, &M.outb, d_out, DM, SEQ, 32, 16, true);
  make_map(enc, &M.xra, d_in[0], DM, SEQ, 64, 16, true);
  make_map(enc, &M.xrb, d_in[0], DM, SEQ, 32, 16, true);
  cudaFuncSetAttribute(fused_kernel, cudaFuncAttributeMaxDynamicSharedMemorySize, (int)SMEM_BYTES);
  Ptrs P;
  P.x = (const __nv_bfloat16*)d_in[0]; P.wqkv = (const __nv_bfloat16*)d_in[1]; P.wo = (const __nv_bfloat16*)d_in[2];
  P.w1 = (const __nv_bfloat16*)d_in[4]; P.w3 = (const __nv_bfloat16*)d_in[5]; P.w2 = (const __nv_bfloat16*)d_in[6];
  {
    int cnt[4] = {0, 0, 0, 0};
    for (int c = 0; c < 64; c++) {
      const int kq = c < 4 ? 0 : c < 36 ? ((c - 4) & 7) >> 1 : ((c - 36) % 7 + 1) >> 1;
      const int r = cnt[kq]++;
      P.role[2 * c] = (uint32_t)(r * 8 + kq * 2);
      P.role[2 * c + 1] = (uint32_t)(r * 8 + kq * 2 + 1);
    }
  }
  fused_kernel<<<128, 384, SMEM_BYTES>>>(M, P);
}
```

```cpp
#include <cuda_runtime.h>
#include <cuda.h>
#include <cuda_bf16.h>
#include <stdint.h>

namespace {

constexpr int SEQ = 2048, DM = 448, FF = 1792;
constexpr uint32_t U = 8192;
constexpr uint32_t SM_BASE = 1024;
constexpr uint32_t MISC = 28 * U;
constexpr uint32_t SMEM_BYTES = 28 * U + 3072;
constexpr uint32_t KVM_U = 26;

enum : int { FA = 0, FB = 7, FC = 14, FD = 21, FT = 28, FW = 36, HF = 43, KVL = 49,
             LH0 = 50, LH1, EA1 = 52, EA2, EA4, EA5, EA6, EB1 = 57, EC0 = 63, ED1 = 70, ED2, ED4, ED5, ED6, ET = 75,
             PKST = 83, LD2, PF = 85, EW0 = 88, XC0, XC1, KVST, OST = 92, KVM = 94, OFREE, XR0, KVFREE, XR1 = 105, LF = 106, HS = 112, NBAR = 118 };
constexpr int KVP = 36;
constexpr uint32_t KV_BYTES = 56 * KVP * 4;

struct Maps { CUtensorMap kv, wq, w1a, w3a, w1b, w3b, w2a, w2b, w2c, w2d, woa, wob, o, ost, outa, outb, xra, xrb; };

struct Ptrs { const __nv_bfloat16 *x, *wqkv, *wo, *w1, *w3, *w2; uint32_t role[128]; };

__device__ uint32_t g_epoch[128];
__device__ uint32_t g_f1[8 * 32];
__device__ uint32_t g_f2[16 * 32];
__device__ uint32_t g_f3[128 * 32];
__device__ __align__(128) float g_kv[2 * 8 * 2048];
__device__ __nv_bfloat16 g_o[SEQ * DM];
__device__ uint4 g_p[16 * 2 * 4 * 3 * 1024];
#define TS(role, i)
#define GTS(role, i)
#define CTS(i)
#define TSDUMP(role)

__device__ __forceinline__ uint32_t smem_u32(const void* p) { return (uint32_t)__cvta_generic_to_shared(p); }
__device__ __forceinline__ void mbar_init(uint32_t bar, uint32_t cnt) { asm volatile("mbarrier.init.shared::cta.b64 [%0], %1;" ::"r"(bar), "r"(cnt) : "memory"); }
__device__ __forceinline__ void mbar_expect_tx(uint32_t bar, uint32_t bytes) { asm volatile("mbarrier.arrive.expect_tx.shared::cta.b64 _, [%0], %1;" ::"r"(bar), "r"(bytes) : "memory"); }
__device__ __forceinline__ void mbar_arrive_n(uint32_t bar, uint32_t n) { asm volatile("mbarrier.arrive.shared::cta.b64 _, [%0], %1;" ::"r"(bar), "r"(n) : "memory"); }
__device__ __forceinline__ void mbar_arrive(uint32_t bar) { asm volatile("mbarrier.arrive.shared::cta.b64 _, [%0];" ::"r"(bar) : "memory"); }
__device__ __forceinline__ void mbar_arrive_remote(uint32_t rbar) { asm volatile("mbarrier.arrive.shared::cluster.b64 _, [%0];" ::"r"(rbar) : "memory"); }
__device__ __forceinline__ void mbar_wait(uint32_t bar) {
  asm volatile("{ .reg .pred p; .reg .u32 n; mov.u32 n, 0;\n"
               "W_L: mbarrier.try_wait.parity.shared::cta.b64 p, [%0], 0;\n"
               "@p bra W_D;\n add.u32 n, n, 1;\n setp.lt.u32 p, n, 4194304;\n @p bra W_L;\n trap;\n W_D: }" ::"r"(bar) : "memory");
}
__device__ __forceinline__ void tma2d(uint32_t dst, const CUtensorMap* m, int c0, int c1, uint32_t bar) {
  asm volatile("cp.async.bulk.tensor.2d.shared::cluster.global.mbarrier::complete_tx::bytes [%0], [%1, {%3, %4}], [%2];" ::"r"(dst), "l"(m), "r"(bar), "r"(c0), "r"(c1) : "memory");
}
__device__ __forceinline__ void tma3d(uint32_t dst, const CUtensorMap* m, int c0, int c1, int c2, uint32_t bar) {
  asm volatile("cp.async.bulk.tensor.3d.shared::cluster.global.mbarrier::complete_tx::bytes [%0], [%1, {%3, %4, %5}], [%2];" ::"r"(dst), "l"(m), "r"(bar), "r"(c0), "r"(c1), "r"(c2) : "memory");
}
__device__ __forceinline__ void bulk_s2g(void* g, uint32_t src, uint32_t bytes) {
  asm volatile("cp.async.bulk.global.shared::cta.bulk_group [%0], [%1], %2;" ::"l"(g), "r"(src), "r"(bytes) : "memory");
}
__device__ __forceinline__ void bulk_commit() { asm volatile("cp.async.bulk.commit_group;" ::: "memory"); }
__device__ __forceinline__ void bulk_wait_read() { asm volatile("cp.async.bulk.wait_group.read 0;" ::: "memory"); }
__device__ __forceinline__ void bulk_wait_all() { asm volatile("cp.async.bulk.wait_group 0;" ::: "memory"); }
__device__ __forceinline__ void l2_prefetch(const void* g, uint32_t bytes) { asm volatile("cp.async.bulk.prefetch.L2.global [%0], %1;" ::"l"(g), "r"(bytes) : "memory"); }
__device__ __forceinline__ void map_prefetch(const CUtensorMap* m) { asm volatile("prefetch.tensormap [%0];" ::"l"(m) : "memory"); }
__device__ __forceinline__ void tma2d_store(const CUtensorMap* m, int c0, int c1, uint32_t src) {
  asm volatile("cp.async.bulk.tensor.2d.global.shared::cta.bulk_group [%0, {%2, %3}], [%1];" ::"l"(m), "r"(src), "r"(c0), "r"(c1) : "memory");
}
__device__ __forceinline__ void bulk_s2c(uint32_t rdst, uint32_t src, uint32_t bytes, uint32_t rbar) {
  asm volatile("cp.async.bulk.shared::cluster.shared::cta.mbarrier::complete_tx::bytes [%0], [%1], %2, [%3];" ::"r"(rdst), "r"(src), "r"(bytes), "r"(rbar) : "memory");
}
__device__ __forceinline__ uint32_t mapa(uint32_t a, uint32_t cta) { uint32_t r; asm volatile("mapa.shared::cluster.u32 %0, %1, %2;" : "=r"(r) : "r"(a), "r"(cta)); return r; }
__device__ __forceinline__ bool elect_one() { uint32_t p; asm volatile("{ .reg .pred P; elect.sync _|P, 0xffffffff; selp.u32 %0, 1, 0, P; }" : "=r"(p)); return p; }
__device__ __forceinline__ int laneid() { int l; asm volatile("mov.u32 %0, %%laneid;" : "=r"(l)); return l; }
__device__ __forceinline__ void fence_async() { asm volatile("fence.proxy.async.shared::cta;" ::: "memory"); }
__device__ __forceinline__ void wg_fence() { asm volatile("wgmma.fence.sync.aligned;" ::: "memory"); }
__device__ __forceinline__ void wg_commit() { asm volatile("wgmma.commit_group.sync.aligned;" ::: "memory"); }
template <int N> __device__ __forceinline__ void wg_wait() { asm volatile("wgmma.wait_group.sync.aligned %0;" ::"n"(N) : "memory"); }
template <int N> __device__ __forceinline__ void pin(float* a) {
#pragma unroll
  for (int i = 0; i < N; i++) asm volatile("" : "+f"(a[i])::"memory");
}
template <int N> __device__ __forceinline__ void pinr(uint32_t* a) {
#pragma unroll
  for (int i = 0; i < N; i++) asm volatile("" : "+r"(a[i])::"memory");
}
__device__ __forceinline__ void ldsm4(uint32_t* r, uint32_t a) { asm volatile("ldmatrix.sync.aligned.m8n8.x4.shared.b16 {%0,%1,%2,%3}, [%4];" : "=r"(r[0]), "=r"(r[1]), "=r"(r[2]), "=r"(r[3]) : "r"(a) : "memory"); }
__device__ __forceinline__ void stsm4(uint32_t a, uint32_t r0, uint32_t r1, uint32_t r2, uint32_t r3) { asm volatile("stmatrix.sync.aligned.m8n8.x4.shared.b16 [%0], {%1,%2,%3,%4};" ::"r"(a), "r"(r0), "r"(r1), "r"(r2), "r"(r3) : "memory"); }
__device__ __forceinline__ void stsm2(uint32_t a, uint32_t r0, uint32_t r1) { asm volatile("stmatrix.sync.aligned.m8n8.x2.shared.b16 [%0], {%1,%2};" ::"r"(a), "r"(r0), "r"(r1) : "memory"); }
__device__ __forceinline__ void sts4(uint32_t a, const uint32_t* r) { asm volatile("st.shared.v4.b32 [%0], {%1,%2,%3,%4};" ::"r"(a), "r"(r[0]), "r"(r[1]), "r"(r[2]), "r"(r[3]) : "memory"); }
__device__ __forceinline__ void sta4(uint32_t ra, const uint32_t* r, uint32_t rbar) {
  asm volatile("st.async.weak.shared::cluster.mbarrier::complete_tx::bytes.v4.b32 [%0], {%1,%2,%3,%4}, [%5];" ::"r"(ra), "r"(r[0]), "r"(r[1]), "r"(r[2]), "r"(r[3]), "r"(rbar) : "memory");
}
__device__ __forceinline__ void lds4(uint32_t* r, uint32_t a) { asm volatile("ld.shared.v4.b32 {%0,%1,%2,%3}, [%4];" : "=r"(r[0]), "=r"(r[1]), "=r"(r[2]), "=r"(r[3]) : "r"(a) : "memory"); }
__device__ __forceinline__ void lds4t(uint32_t* r, const uint32_t* o, uint32_t a) {
  r[0] = o[0]; r[1] = o[1]; r[2] = o[2]; r[3] = o[3];
  asm volatile("{ .reg .pred p; setp.ne.u32 p, %4, 1; @p ld.shared.v4.b32 {%0,%1,%2,%3}, [%4]; }" : "+r"(r[0]), "+r"(r[1]), "+r"(r[2]), "+r"(r[3]) : "r"(a) : "memory");
}
__device__ __forceinline__ uint32_t pack2(float lo, float hi) { uint32_t r; asm("cvt.rn.bf16x2.f32 %0, %1, %2;" : "=r"(r) : "f"(hi), "f"(lo)); return r; }
__device__ __forceinline__ float blo(uint32_t v) { return __uint_as_float(v << 16); }
__device__ __forceinline__ float bhi(uint32_t v) { return __uint_as_float(v & 0xFFFF0000u); }
__device__ __forceinline__ float ex2(float x) { float y; asm("ex2.approx.ftz.f32 %0, %1;" : "=f"(y) : "f"(x)); return y; }
__device__ __forceinline__ float rcp(float x) { float y; asm("rcp.approx.ftz.f32 %0, %1;" : "=f"(y) : "f"(x)); return y; }
__device__ __forceinline__ float sqrt_(float x) { float y; asm("sqrt.approx.ftz.f32 %0, %1;" : "=f"(y) : "f"(x)); return y; }
__device__ __forceinline__ void mma16816(float* c, const uint32_t* a, uint32_t b0, uint32_t b1) {
  asm volatile("mma.sync.aligned.m16n8k16.row.col.f32.bf16.bf16.f32 {%0,%1,%2,%3}, {%4,%5,%6,%7}, {%8,%9}, {%0,%1,%2,%3};"
               : "+f"(c[0]), "+f"(c[1]), "+f"(c[2]), "+f"(c[3]) : "r"(a[0]), "r"(a[1]), "r"(a[2]), "r"(a[3]), "r"(b0), "r"(b1));
}
__device__ __forceinline__ float tanh_(float x) { float y; asm("tanh.approx.f32 %0, %1;" : "=f"(y) : "f"(x)); return y; }
__device__ __forceinline__ float bfr(float x) { return __bfloat162float(__float2bfloat16_rn(x)); }
__device__ __forceinline__ uint32_t ld_acq(const uint32_t* p) { uint32_t v; asm volatile("ld.acquire.gpu.global.u32 %0, [%1];" : "=r"(v) : "l"(p) : "memory"); return v; }
__device__ __forceinline__ void poll_flag(const uint32_t* p, uint32_t target) {
  uint32_t n = 0;
  while ((int)(ld_acq(p) - target) < 0) { if (++n > (1u << 21)) asm volatile("trap;"); }
}
#define SIGNAL(p) asm volatile("red.relaxed.gpu.global.add.u32 [%0], 1;" ::"l"(p) : "memory")
__device__ __forceinline__ void ld_ll(uint32_t* r, const uint4* p) {
  asm volatile("{ .reg .b128 t; .reg .b64 lo, hi; ld.relaxed.gpu.global.b128 t, [%4]; mov.b128 {lo,hi}, t; mov.b64 {%0,%1}, lo; mov.b64 {%2,%3}, hi; }" : "=r"(r[0]), "=r"(r[1]), "=r"(r[2]), "=r"(r[3]) : "l"(p) : "memory");
}
__device__ __forceinline__ constexpr uint64_t desc(uint32_t off, uint32_t lbo) {
  return (uint64_t)((SM_BASE + off) >> 4) | ((uint64_t)(lbo >> 4) << 16) | ((uint64_t)64 << 32) | ((uint64_t)1 << 62);
}

__device__ __forceinline__ void rs120_0(float* d, const uint32_t* a, uint64_t db){
  asm volatile("{ .reg .pred p; setp.ne.b32 p, 0, 0; wgmma.mma_async.sync.aligned.m64n120k16.f32.bf16.bf16 {%0, %1, %2, %3, %4, %5, %6, %7, %8, %9, %10, %11, %12, %13, %14, %15, %16, %17, %18, %19, %20, %21, %22, %23, %24, %25, %26, %27, %28, %29, %30, %31, %32, %33, %34, %35, %36, %37, %38, %39, %40, %41, %42, %43, %44, %45, %46, %47, %48, %49, %50, %51, %52, %53, %54, %55, %56, %57, %58, %59}, {%60,%61,%62,%63}, %64, p, 1, 1, 1; }"
   : "=f"(d[0]), "=f"(d[1]), "=f"(d[2]), "=f"(d[3]), "=f"(d[4]), "=f"(d[5]), "=f"(d[6]), "=f"(d[7]), "=f"(d[8]), "=f"(d[9]), "=f"(d[10]), "=f"(d[11]), "=f"(d[12]), "=f"(d[13]), "=f"(d[14]), "=f"(d[15]), "=f"(d[16]), "=f"(d[17]), "=f"(d[18]), "=f"(d[19]), "=f"(d[20]), "=f"(d[21]), "=f"(d[22]), "=f"(d[23]), "=f"(d[24]), "=f"(d[25]), "=f"(d[26]), "=f"(d[27]), "=f"(d[28]), "=f"(d[29]), "=f"(d[30]), "=f"(d[31]), "=f"(d[32]), "=f"(d[33]), "=f"(d[34]), "=f"(d[35]), "=f"(d[36]), "=f"(d[37]), "=f"(d[38]), "=f"(d[39]), "=f"(d[40]), "=f"(d[41]), "=f"(d[42]), "=f"(d[43]), "=f"(d[44]), "=f"(d[45]), "=f"(d[46]), "=f"(d[47]), "=f"(d[48]), "=f"(d[49]), "=f"(d[50]), "=f"(d[51]), "=f"(d[52]), "=f"(d[53]), "=f"(d[54]), "=f"(d[55]), "=f"(d[56]), "=f"(d[57]), "=f"(d[58]), "=f"(d[59]) : "r"(a[0]),"r"(a[1]),"r"(a[2]),"r"(a[3]), "l"(db));
}
__device__ __forceinline__ void rs120_1(float* d, const uint32_t* a, uint64_t db){
  asm volatile("{ .reg .pred p; setp.ne.b32 p, 1, 0; wgmma.mma_async.sync.aligned.m64n120k16.f32.bf16.bf16 {%0, %1, %2, %3, %4, %5, %6, %7, %8, %9, %10, %11, %12, %13, %14, %15, %16, %17, %18, %19, %20, %21, %22, %23, %24, %25, %26, %27, %28, %29, %30, %31, %32, %33, %34, %35, %36, %37, %38, %39, %40, %41, %42, %43, %44, %45, %46, %47, %48, %49, %50, %51, %52, %53, %54, %55, %56, %57, %58, %59}, {%60,%61,%62,%63}, %64, p, 1, 1, 1; }"
   : "+f"(d[0]), "+f"(d[1]), "+f"(d[2]), "+f"(d[3]), "+f"(d[4]), "+f"(d[5]), "+f"(d[6]), "+f"(d[7]), "+f"(d[8]), "+f"(d[9]), "+f"(d[10]), "+f"(d[11]), "+f"(d[12]), "+f"(d[13]), "+f"(d[14]), "+f"(d[15]), "+f"(d[16]), "+f"(d[17]), "+f"(d[18]), "+f"(d[19]), "+f"(d[20]), "+f"(d[21]), "+f"(d[22]), "+f"(d[23]), "+f"(d[24]), "+f"(d[25]), "+f"(d[26]), "+f"(d[27]), "+f"(d[28]), "+f"(d[29]), "+f"(d[30]), "+f"(d[31]), "+f"(d[32]), "+f"(d[33]), "+f"(d[34]), "+f"(d[35]), "+f"(d[36]), "+f"(d[37]), "+f"(d[38]), "+f"(d[39]), "+f"(d[40]), "+f"(d[41]), "+f"(d[42]), "+f"(d[43]), "+f"(d[44]), "+f"(d[45]), "+f"(d[46]), "+f"(d[47]), "+f"(d[48]), "+f"(d[49]), "+f"(d[50]), "+f"(d[51]), "+f"(d[52]), "+f"(d[53]), "+f"(d[54]), "+f"(d[55]), "+f"(d[56]), "+f"(d[57]), "+f"(d[58]), "+f"(d[59]) : "r"(a[0]),"r"(a[1]),"r"(a[2]),"r"(a[3]), "l"(db));
}
__device__ __forceinline__ void rs128_0(float* d, const uint32_t* a, uint64_t db){
  asm volatile("{ .reg .pred p; setp.ne.b32 p, 0, 0; wgmma.mma_async.sync.aligned.m64n128k16.f32.bf16.bf16 {%0, %1, %2, %3, %4, %5, %6, %7, %8, %9, %10, %11, %12, %13, %14, %15, %16, %17, %18, %19, %20, %21, %22, %23, %24, %25, %26, %27, %28, %29, %30, %31, %32, %33, %34, %35, %36, %37, %38, %39, %40, %41, %42, %43, %44, %45, %46, %47, %48, %49, %50, %51, %52, %53, %54, %55, %56, %57, %58, %59, %60, %61, %62, %63}, {%64,%65,%66,%67}, %68, p, 1, 1, 1; }"
   : "=f"(d[0]), "=f"(d[1]), "=f"(d[2]), "=f"(d[3]), "=f"(d[4]), "=f"(d[5]), "=f"(d[6]), "=f"(d[7]), "=f"(d[8]), "=f"(d[9]), "=f"(d[10]), "=f"(d[11]), "=f"(d[12]), "=f"(d[13]), "=f"(d[14]), "=f"(d[15]), "=f"(d[16]), "=f"(d[17]), "=f"(d[18]), "=f"(d[19]), "=f"(d[20]), "=f"(d[21]), "=f"(d[22]), "=f"(d[23]), "=f"(d[24]), "=f"(d[25]), "=f"(d[26]), "=f"(d[27]), "=f"(d[28]), "=f"(d[29]), "=f"(d[30]), "=f"(d[31]), "=f"(d[32]), "=f"(d[33]), "=f"(d[34]), "=f"(d[35]), "=f"(d[36]), "=f"(d[37]), "=f"(d[38]), "=f"(d[39]), "=f"(d[40]), "=f"(d[41]), "=f"(d[42]), "=f"(d[43]), "=f"(d[44]), "=f"(d[45]), "=f"(d[46]), "=f"(d[47]), "=f"(d[48]), "=f"(d[49]), "=f"(d[50]), "=f"(d[51]), "=f"(d[52]), "=f"(d[53]), "=f"(d[54]), "=f"(d[55]), "=f"(d[56]), "=f"(d[57]), "=f"(d[58]), "=f"(d[59]), "=f"(d[60]), "=f"(d[61]), "=f"(d[62]), "=f"(d[63]) : "r"(a[0]),"r"(a[1]),"r"(a[2]),"r"(a[3]), "l"(db));
}
__device__ __forceinline__ void rs128_1(float* d, const uint32_t* a, uint64_t db){
  asm volatile("{ .reg .pred p; setp.ne.b32 p, 1, 0; wgmma.mma_async.sync.aligned.m64n128k16.f32.bf16.bf16 {%0, %1, %2, %3, %4, %5, %6, %7, %8, %9, %10, %11, %12, %13, %14, %15, %16, %17, %18, %19, %20, %21, %22, %23, %24, %25, %26, %27, %28, %29, %30, %31, %32, %33, %34, %35, %36, %37, %38, %39, %40, %41, %42, %43, %44, %45, %46, %47, %48, %49, %50, %51, %52, %53, %54, %55, %56, %57, %58, %59, %60, %61, %62, %63}, {%64,%65,%66,%67}, %68, p, 1, 1, 1; }"
   : "+f"(d[0]), "+f"(d[1]), "+f"(d[2]), "+f"(d[3]), "+f"(d[4]), "+f"(d[5]), "+f"(d[6]), "+f"(d[7]), "+f"(d[8]), "+f"(d[9]), "+f"(d[10]), "+f"(d[11]), "+f"(d[12]), "+f"(d[13]), "+f"(d[14]), "+f"(d[15]), "+f"(d[16]), "+f"(d[17]), "+f"(d[18]), "+f"(d[19]), "+f"(d[20]), "+f"(d[21]), "+f"(d[22]), "+f"(d[23]), "+f"(d[24]), "+f"(d[25]), "+f"(d[26]), "+f"(d[27]), "+f"(d[28]), "+f"(d[29]), "+f"(d[30]), "+f"(d[31]), "+f"(d[32]), "+f"(d[33]), "+f"(d[34]), "+f"(d[35]), "+f"(d[36]), "+f"(d[37]), "+f"(d[38]), "+f"(d[39]), "+f"(d[40]), "+f"(d[41]), "+f"(d[42]), "+f"(d[43]), "+f"(d[44]), "+f"(d[45]), "+f"(d[46]), "+f"(d[47]), "+f"(d[48]), "+f"(d[49]), "+f"(d[50]), "+f"(d[51]), "+f"(d[52]), "+f"(d[53]), "+f"(d[54]), "+f"(d[55]), "+f"(d[56]), "+f"(d[57]), "+f"(d[58]), "+f"(d[59]), "+f"(d[60]), "+f"(d[61]), "+f"(d[62]), "+f"(d[63]) : "r"(a[0]),"r"(a[1]),"r"(a[2]),"r"(a[3]), "l"(db));
}
__device__ __forceinline__ void rs160_0(float* d, const uint32_t* a, uint64_t db){
  asm volatile("{ .reg .pred p; setp.ne.b32 p, 0, 0; wgmma.mma_async.sync.aligned.m64n160k16.f32.bf16.bf16 {%0, %1, %2, %3, %4, %5, %6, %7, %8, %9, %10, %11, %12, %13, %14, %15, %16, %17, %18, %19, %20, %21, %22, %23, %24, %25, %26, %27, %28, %29, %30, %31, %32, %33, %34, %35, %36, %37, %38, %39, %40, %41, %42, %43, %44, %45, %46, %47, %48, %49, %50, %51, %52, %53, %54, %55, %56, %57, %58, %59, %60, %61, %62, %63, %64, %65, %66, %67, %68, %69, %70, %71, %72, %73, %74, %75, %76, %77, %78, %79}, {%80,%81,%82,%83}, %84, p, 1, 1, 1; }"
   : "=f"(d[0]), "=f"(d[1]), "=f"(d[2]), "=f"(d[3]), "=f"(d[4]), "=f"(d[5]), "=f"(d[6]), "=f"(d[7]), "=f"(d[8]), "=f"(d[9]), "=f"(d[10]), "=f"(d[11]), "=f"(d[12]), "=f"(d[13]), "=f"(d[14]), "=f"(d[15]), "=f"(d[16]), "=f"(d[17]), "=f"(d[18]), "=f"(d[19]), "=f"(d[20]), "=f"(d[21]), "=f"(d[22]), "=f"(d[23]), "=f"(d[24]), "=f"(d[25]), "=f"(d[26]), "=f"(d[27]), "=f"(d[28]), "=f"(d[29]), "=f"(d[30]), "=f"(d[31]), "=f"(d[32]), "=f"(d[33]), "=f"(d[34]), "=f"(d[35]), "=f"(d[36]), "=f"(d[37]), "=f"(d[38]), "=f"(d[39]), "=f"(d[40]), "=f"(d[41]), "=f"(d[42]), "=f"(d[43]), "=f"(d[44]), "=f"(d[45]), "=f"(d[46]), "=f"(d[47]), "=f"(d[48]), "=f"(d[49]), "=f"(d[50]), "=f"(d[51]), "=f"(d[52]), "=f"(d[53]), "=f"(d[54]), "=f"(d[55]), "=f"(d[56]), "=f"(d[57]), "=f"(d[58]), "=f"(d[59]), "=f"(d[60]), "=f"(d[61]), "=f"(d[62]), "=f"(d[63]), "=f"(d[64]), "=f"(d[65]), "=f"(d[66]), "=f"(d[67]), "=f"(d[68]), "=f"(d[69]), "=f"(d[70]), "=f"(d[71]), "=f"(d[72]), "=f"(d[73]), "=f"(d[74]), "=f"(d[75]), "=f"(d[76]), "=f"(d[77]), "=f"(d[78]), "=f"(d[79]) : "r"(a[0]),"r"(a[1]),"r"(a[2]),"r"(a[3]), "l"(db));
}
__device__ __forceinline__ void rs160_1(float* d, const uint32_t* a, uint64_t db){
  asm volatile("{ .reg .pred p; setp.ne.b32 p, 1, 0; wgmma.mma_async.sync.aligned.m64n160k16.f32.bf16.bf16 {%0, %1, %2, %3, %4, %5, %6, %7, %8, %9, %10, %11, %12, %13, %14, %15, %16, %17, %18, %19, %20, %21, %22, %23, %24, %25, %26, %27, %28, %29, %30, %31, %32, %33, %34, %35, %36, %37, %38, %39, %40, %41, %42, %43, %44, %45, %46, %47, %48, %49, %50, %51, %52, %53, %54, %55, %56, %57, %58, %59, %60, %61, %62, %63, %64, %65, %66, %67, %68, %69, %70, %71, %72, %73, %74, %75, %76, %77, %78, %79}, {%80,%81,%82,%83}, %84, p, 1, 1, 1; }"
   : "+f"(d[0]), "+f"(d[1]), "+f"(d[2]), "+f"(d[3]), "+f"(d[4]), "+f"(d[5]), "+f"(d[6]), "+f"(d[7]), "+f"(d[8]), "+f"(d[9]), "+f"(d[10]), "+f"(d[11]), "+f"(d[12]), "+f"(d[13]), "+f"(d[14]), "+f"(d[15]), "+f"(d[16]), "+f"(d[17]), "+f"(d[18]), "+f"(d[19]), "+f"(d[20]), "+f"(d[21]), "+f"(d[22]), "+f"(d[23]), "+f"(d[24]), "+f"(d[25]), "+f"(d[26]), "+f"(d[27]), "+f"(d[28]), "+f"(d[29]), "+f"(d[30]), "+f"(d[31]), "+f"(d[32]), "+f"(d[33]), "+f"(d[34]), "+f"(d[35]), "+f"(d[36]), "+f"(d[37]), "+f"(d[38]), "+f"(d[39]), "+f"(d[40]), "+f"(d[41]), "+f"(d[42]), "+f"(d[43]), "+f"(d[44]), "+f"(d[45]), "+f"(d[46]), "+f"(d[47]), "+f"(d[48]), "+f"(d[49]), "+f"(d[50]), "+f"(d[51]), "+f"(d[52]), "+f"(d[53]), "+f"(d[54]), "+f"(d[55]), "+f"(d[56]), "+f"(d[57]), "+f"(d[58]), "+f"(d[59]), "+f"(d[60]), "+f"(d[61]), "+f"(d[62]), "+f"(d[63]), "+f"(d[64]), "+f"(d[65]), "+f"(d[66]), "+f"(d[67]), "+f"(d[68]), "+f"(d[69]), "+f"(d[70]), "+f"(d[71]), "+f"(d[72]), "+f"(d[73]), "+f"(d[74]), "+f"(d[75]), "+f"(d[76]), "+f"(d[77]), "+f"(d[78]), "+f"(d[79]) : "r"(a[0]),"r"(a[1]),"r"(a[2]),"r"(a[3]), "l"(db));
}
__device__ __forceinline__ void rs64_0(float* d, const uint32_t* a, uint64_t db){
  asm volatile("{ .reg .pred p; setp.ne.b32 p, 0, 0; wgmma.mma_async.sync.aligned.m64n64k16.f32.bf16.bf16 {%0, %1, %2, %3, %4, %5, %6, %7, %8, %9, %10, %11, %12, %13, %14, %15, %16, %17, %18, %19, %20, %21, %22, %23, %24, %25, %26, %27, %28, %29, %30, %31}, {%32,%33,%34,%35}, %36, p, 1, 1, 1; }"
   : "=f"(d[0]), "=f"(d[1]), "=f"(d[2]), "=f"(d[3]), "=f"(d[4]), "=f"(d[5]), "=f"(d[6]), "=f"(d[7]), "=f"(d[8]), "=f"(d[9]), "=f"(d[10]), "=f"(d[11]), "=f"(d[12]), "=f"(d[13]), "=f"(d[14]), "=f"(d[15]), "=f"(d[16]), "=f"(d[17]), "=f"(d[18]), "=f"(d[19]), "=f"(d[20]), "=f"(d[21]), "=f"(d[22]), "=f"(d[23]), "=f"(d[24]), "=f"(d[25]), "=f"(d[26]), "=f"(d[27]), "=f"(d[28]), "=f"(d[29]), "=f"(d[30]), "=f"(d[31]) : "r"(a[0]),"r"(a[1]),"r"(a[2]),"r"(a[3]), "l"(db));
}
__device__ __forceinline__ void rs64_1(float* d, const uint32_t* a, uint64_t db){
  asm volatile("{ .reg .pred p; setp.ne.b32 p, 1, 0; wgmma.mma_async.sync.aligned.m64n64k16.f32.bf16.bf16 {%0, %1, %2, %3, %4, %5, %6, %7, %8, %9, %10, %11, %12, %13, %14, %15, %16, %17, %18, %19, %20, %21, %22, %23, %24, %25, %26, %27, %28, %29, %30, %31}, {%32,%33,%34,%35}, %36, p, 1, 1, 1; }"
   : "+f"(d[0]), "+f"(d[1]), "+f"(d[2]), "+f"(d[3]), "+f"(d[4]), "+f"(d[5]), "+f"(d[6]), "+f"(d[7]), "+f"(d[8]), "+f"(d[9]), "+f"(d[10]), "+f"(d[11]), "+f"(d[12]), "+f"(d[13]), "+f"(d[14]), "+f"(d[15]), "+f"(d[16]), "+f"(d[17]), "+f"(d[18]), "+f"(d[19]), "+f"(d[20]), "+f"(d[21]), "+f"(d[22]), "+f"(d[23]), "+f"(d[24]), "+f"(d[25]), "+f"(d[26]), "+f"(d[27]), "+f"(d[28]), "+f"(d[29]), "+f"(d[30]), "+f"(d[31]) : "r"(a[0]),"r"(a[1]),"r"(a[2]),"r"(a[3]), "l"(db));
}
__device__ __forceinline__ void rs56_0(float* d, const uint32_t* a, uint64_t db){
  asm volatile("{ .reg .pred p; setp.ne.b32 p, 0, 0; wgmma.mma_async.sync.aligned.m64n56k16.f32.bf16.bf16 {%0, %1, %2, %3, %4, %5, %6, %7, %8, %9, %10, %11, %12, %13, %14, %15, %16, %17, %18, %19, %20, %21, %22, %23, %24, %25, %26, %27}, {%28,%29,%30,%31}, %32, p, 1, 1, 1; }"
   : "=f"(d[0]), "=f"(d[1]), "=f"(d[2]), "=f"(d[3]), "=f"(d[4]), "=f"(d[5]), "=f"(d[6]), "=f"(d[7]), "=f"(d[8]), "=f"(d[9]), "=f"(d[10]), "=f"(d[11]), "=f"(d[12]), "=f"(d[13]), "=f"(d[14]), "=f"(d[15]), "=f"(d[16]), "=f"(d[17]), "=f"(d[18]), "=f"(d[19]), "=f"(d[20]), "=f"(d[21]), "=f"(d[22]), "=f"(d[23]), "=f"(d[24]), "=f"(d[25]), "=f"(d[26]), "=f"(d[27]) : "r"(a[0]),"r"(a[1]),"r"(a[2]),"r"(a[3]), "l"(db));
}
__device__ __forceinline__ void rs56_1(float* d, const uint32_t* a, uint64_t db){
  asm volatile("{ .reg .pred p; setp.ne.b32 p, 1, 0; wgmma.mma_async.sync.aligned.m64n56k16.f32.bf16.bf16 {%0, %1, %2, %3, %4, %5, %6, %7, %8, %9, %10, %11, %12, %13, %14, %15, %16, %17, %18, %19, %20, %21, %22, %23, %24, %25, %26, %27}, {%28,%29,%30,%31}, %32, p, 1, 1, 1; }"
   : "+f"(d[0]), "+f"(d[1]), "+f"(d[2]), "+f"(d[3]), "+f"(d[4]), "+f"(d[5]), "+f"(d[6]), "+f"(d[7]), "+f"(d[8]), "+f"(d[9]), "+f"(d[10]), "+f"(d[11]), "+f"(d[12]), "+f"(d[13]), "+f"(d[14]), "+f"(d[15]), "+f"(d[16]), "+f"(d[17]), "+f"(d[18]), "+f"(d[19]), "+f"(d[20]), "+f"(d[21]), "+f"(d[22]), "+f"(d[23]), "+f"(d[24]), "+f"(d[25]), "+f"(d[26]), "+f"(d[27]) : "r"(a[0]),"r"(a[1]),"r"(a[2]),"r"(a[3]), "l"(db));
}
__device__ __forceinline__ void rs32_0(float* d, const uint32_t* a, uint64_t db){
  asm volatile("{ .reg .pred p; setp.ne.b32 p, 0, 0; wgmma.mma_async.sync.aligned.m64n32k16.f32.bf16.bf16 {%0, %1, %2, %3, %4, %5, %6, %7, %8, %9, %10, %11, %12, %13, %14, %15}, {%16,%17,%18,%19}, %20, p, 1, 1, 1; }"
   : "=f"(d[0]), "=f"(d[1]), "=f"(d[2]), "=f"(d[3]), "=f"(d[4]), "=f"(d[5]), "=f"(d[6]), "=f"(d[7]), "=f"(d[8]), "=f"(d[9]), "=f"(d[10]), "=f"(d[11]), "=f"(d[12]), "=f"(d[13]), "=f"(d[14]), "=f"(d[15]) : "r"(a[0]),"r"(a[1]),"r"(a[2]),"r"(a[3]), "l"(db));
}
__device__ __forceinline__ void rs32_1(float* d, const uint32_t* a, uint64_t db){
  asm volatile("{ .reg .pred p; setp.ne.b32 p, 1, 0; wgmma.mma_async.sync.aligned.m64n32k16.f32.bf16.bf16 {%0, %1, %2, %3, %4, %5, %6, %7, %8, %9, %10, %11, %12, %13, %14, %15}, {%16,%17,%18,%19}, %20, p, 1, 1, 1; }"
   : "+f"(d[0]), "+f"(d[1]), "+f"(d[2]), "+f"(d[3]), "+f"(d[4]), "+f"(d[5]), "+f"(d[6]), "+f"(d[7]), "+f"(d[8]), "+f"(d[9]), "+f"(d[10]), "+f"(d[11]), "+f"(d[12]), "+f"(d[13]), "+f"(d[14]), "+f"(d[15]) : "r"(a[0]),"r"(a[1]),"r"(a[2]),"r"(a[3]), "l"(db));
}
__device__ __forceinline__ void ss64_0(float* d, uint64_t da, uint64_t db){
  asm volatile("{ .reg .pred p; setp.ne.b32 p, 0, 0; wgmma.mma_async.sync.aligned.m64n64k16.f32.bf16.bf16 {%0, %1, %2, %3, %4, %5, %6, %7, %8, %9, %10, %11, %12, %13, %14, %15, %16, %17, %18, %19, %20, %21, %22, %23, %24, %25, %26, %27, %28, %29, %30, %31}, %32, %33, p, 1, 1, 1, 1; }"
   : "=f"(d[0]), "=f"(d[1]), "=f"(d[2]), "=f"(d[3]), "=f"(d[4]), "=f"(d[5]), "=f"(d[6]), "=f"(d[7]), "=f"(d[8]), "=f"(d[9]), "=f"(d[10]), "=f"(d[11]), "=f"(d[12]), "=f"(d[13]), "=f"(d[14]), "=f"(d[15]), "=f"(d[16]), "=f"(d[17]), "=f"(d[18]), "=f"(d[19]), "=f"(d[20]), "=f"(d[21]), "=f"(d[22]), "=f"(d[23]), "=f"(d[24]), "=f"(d[25]), "=f"(d[26]), "=f"(d[27]), "=f"(d[28]), "=f"(d[29]), "=f"(d[30]), "=f"(d[31]) : "l"(da), "l"(db));
}
__device__ __forceinline__ void ss64_1(float* d, uint64_t da, uint64_t db){
  asm volatile("{ .reg .pred p; setp.ne.b32 p, 1, 0; wgmma.mma_async.sync.aligned.m64n64k16.f32.bf16.bf16 {%0, %1, %2, %3, %4, %5, %6, %7, %8, %9, %10, %11, %12, %13, %14, %15, %16, %17, %18, %19, %20, %21, %22, %23, %24, %25, %26, %27, %28, %29, %30, %31}, %32, %33, p, 1, 1, 1, 1; }"
   : "+f"(d[0]), "+f"(d[1]), "+f"(d[2]), "+f"(d[3]), "+f"(d[4]), "+f"(d[5]), "+f"(d[6]), "+f"(d[7]), "+f"(d[8]), "+f"(d[9]), "+f"(d[10]), "+f"(d[11]), "+f"(d[12]), "+f"(d[13]), "+f"(d[14]), "+f"(d[15]), "+f"(d[16]), "+f"(d[17]), "+f"(d[18]), "+f"(d[19]), "+f"(d[20]), "+f"(d[21]), "+f"(d[22]), "+f"(d[23]), "+f"(d[24]), "+f"(d[25]), "+f"(d[26]), "+f"(d[27]), "+f"(d[28]), "+f"(d[29]), "+f"(d[30]), "+f"(d[31]) : "l"(da), "l"(db));
}
__device__ __forceinline__ void rs64_z(float* d, const uint32_t* a, uint64_t db){
  asm volatile("{ .reg .pred p; setp.ne.b32 p, 0, 0; wgmma.mma_async.sync.aligned.m64n64k16.f32.bf16.bf16 {%0, %1, %2, %3, %4, %5, %6, %7, %8, %9, %10, %11, %12, %13, %14, %15, %16, %17, %18, %19, %20, %21, %22, %23, %24, %25, %26, %27, %28, %29, %30, %31}, {%32,%33,%34,%35}, %36, p, 1, 1, 1; }"
   : "+f"(d[0]), "+f"(d[1]), "+f"(d[2]), "+f"(d[3]), "+f"(d[4]), "+f"(d[5]), "+f"(d[6]), "+f"(d[7]), "+f"(d[8]), "+f"(d[9]), "+f"(d[10]), "+f"(d[11]), "+f"(d[12]), "+f"(d[13]), "+f"(d[14]), "+f"(d[15]), "+f"(d[16]), "+f"(d[17]), "+f"(d[18]), "+f"(d[19]), "+f"(d[20]), "+f"(d[21]), "+f"(d[22]), "+f"(d[23]), "+f"(d[24]), "+f"(d[25]), "+f"(d[26]), "+f"(d[27]), "+f"(d[28]), "+f"(d[29]), "+f"(d[30]), "+f"(d[31]) : "r"(a[0]),"r"(a[1]),"r"(a[2]),"r"(a[3]), "l"(db));
}
__device__ __forceinline__ void rs32_z(float* d, const uint32_t* a, uint64_t db){
  asm volatile("{ .reg .pred p; setp.ne.b32 p, 0, 0; wgmma.mma_async.sync.aligned.m64n32k16.f32.bf16.bf16 {%0, %1, %2, %3, %4, %5, %6, %7, %8, %9, %10, %11, %12, %13, %14, %15}, {%16,%17,%18,%19}, %20, p, 1, 1, 1; }"
   : "+f"(d[0]), "+f"(d[1]), "+f"(d[2]), "+f"(d[3]), "+f"(d[4]), "+f"(d[5]), "+f"(d[6]), "+f"(d[7]), "+f"(d[8]), "+f"(d[9]), "+f"(d[10]), "+f"(d[11]), "+f"(d[12]), "+f"(d[13]), "+f"(d[14]), "+f"(d[15]) : "r"(a[0]),"r"(a[1]),"r"(a[2]),"r"(a[3]), "l"(db));
}
__device__ __forceinline__ void sk64_0(float* d, uint64_t da, uint64_t db){
  asm volatile("{ .reg .pred p; setp.ne.b32 p, 0, 0; wgmma.mma_async.sync.aligned.m64n64k16.f32.bf16.bf16 {%0, %1, %2, %3, %4, %5, %6, %7, %8, %9, %10, %11, %12, %13, %14, %15, %16, %17, %18, %19, %20, %21, %22, %23, %24, %25, %26, %27, %28, %29, %30, %31}, %32, %33, p, 1, 1, 0, 1; }"
   : "=f"(d[0]), "=f"(d[1]), "=f"(d[2]), "=f"(d[3]), "=f"(d[4]), "=f"(d[5]), "=f"(d[6]), "=f"(d[7]), "=f"(d[8]), "=f"(d[9]), "=f"(d[10]), "=f"(d[11]), "=f"(d[12]), "=f"(d[13]), "=f"(d[14]), "=f"(d[15]), "=f"(d[16]), "=f"(d[17]), "=f"(d[18]), "=f"(d[19]), "=f"(d[20]), "=f"(d[21]), "=f"(d[22]), "=f"(d[23]), "=f"(d[24]), "=f"(d[25]), "=f"(d[26]), "=f"(d[27]), "=f"(d[28]), "=f"(d[29]), "=f"(d[30]), "=f"(d[31]) : "l"(da), "l"(db));
}
__device__ __forceinline__ void sk64_1(float* d, uint64_t da, uint64_t db){
  asm volatile("{ .reg .pred p; setp.ne.b32 p, 1, 0; wgmma.mma_async.sync.aligned.m64n64k16.f32.bf16.bf16 {%0, %1, %2, %3, %4, %5, %6, %7, %8, %9, %10, %11, %12, %13, %14, %15, %16, %17, %18, %19, %20, %21, %22, %23, %24, %25, %26, %27, %28, %29, %30, %31}, %32, %33, p, 1, 1, 0, 1; }"
   : "+f"(d[0]), "+f"(d[1]), "+f"(d[2]), "+f"(d[3]), "+f"(d[4]), "+f"(d[5]), "+f"(d[6]), "+f"(d[7]), "+f"(d[8]), "+f"(d[9]), "+f"(d[10]), "+f"(d[11]), "+f"(d[12]), "+f"(d[13]), "+f"(d[14]), "+f"(d[15]), "+f"(d[16]), "+f"(d[17]), "+f"(d[18]), "+f"(d[19]), "+f"(d[20]), "+f"(d[21]), "+f"(d[22]), "+f"(d[23]), "+f"(d[24]), "+f"(d[25]), "+f"(d[26]), "+f"(d[27]), "+f"(d[28]), "+f"(d[29]), "+f"(d[30]), "+f"(d[31]) : "l"(da), "l"(db));
}
__device__ __forceinline__ void sk64_z(float* d, uint64_t da, uint64_t db){
  asm volatile("{ .reg .pred p; setp.ne.b32 p, 0, 0; wgmma.mma_async.sync.aligned.m64n64k16.f32.bf16.bf16 {%0, %1, %2, %3, %4, %5, %6, %7, %8, %9, %10, %11, %12, %13, %14, %15, %16, %17, %18, %19, %20, %21, %22, %23, %24, %25, %26, %27, %28, %29, %30, %31}, %32, %33, p, 1, 1, 0, 1; }"
   : "+f"(d[0]), "+f"(d[1]), "+f"(d[2]), "+f"(d[3]), "+f"(d[4]), "+f"(d[5]), "+f"(d[6]), "+f"(d[7]), "+f"(d[8]), "+f"(d[9]), "+f"(d[10]), "+f"(d[11]), "+f"(d[12]), "+f"(d[13]), "+f"(d[14]), "+f"(d[15]), "+f"(d[16]), "+f"(d[17]), "+f"(d[18]), "+f"(d[19]), "+f"(d[20]), "+f"(d[21]), "+f"(d[22]), "+f"(d[23]), "+f"(d[24]), "+f"(d[25]), "+f"(d[26]), "+f"(d[27]), "+f"(d[28]), "+f"(d[29]), "+f"(d[30]), "+f"(d[31]) : "l"(da), "l"(db));
}
__device__ __forceinline__ void sk32_0(float* d, uint64_t da, uint64_t db){
  asm volatile("{ .reg .pred p; setp.ne.b32 p, 0, 0; wgmma.mma_async.sync.aligned.m64n32k16.f32.bf16.bf16 {%0, %1, %2, %3, %4, %5, %6, %7, %8, %9, %10, %11, %12, %13, %14, %15}, %16, %17, p, 1, 1, 0, 1; }"
   : "=f"(d[0]), "=f"(d[1]), "=f"(d[2]), "=f"(d[3]), "=f"(d[4]), "=f"(d[5]), "=f"(d[6]), "=f"(d[7]), "=f"(d[8]), "=f"(d[9]), "=f"(d[10]), "=f"(d[11]), "=f"(d[12]), "=f"(d[13]), "=f"(d[14]), "=f"(d[15]) : "l"(da), "l"(db));
}
__device__ __forceinline__ void sk32_1(float* d, uint64_t da, uint64_t db){
  asm volatile("{ .reg .pred p; setp.ne.b32 p, 1, 0; wgmma.mma_async.sync.aligned.m64n32k16.f32.bf16.bf16 {%0, %1, %2, %3, %4, %5, %6, %7, %8, %9, %10, %11, %12, %13, %14, %15}, %16, %17, p, 1, 1, 0, 1; }"
   : "+f"(d[0]), "+f"(d[1]), "+f"(d[2]), "+f"(d[3]), "+f"(d[4]), "+f"(d[5]), "+f"(d[6]), "+f"(d[7]), "+f"(d[8]), "+f"(d[9]), "+f"(d[10]), "+f"(d[11]), "+f"(d[12]), "+f"(d[13]), "+f"(d[14]), "+f"(d[15]) : "l"(da), "l"(db));
}
__device__ __forceinline__ void sk32_z(float* d, uint64_t da, uint64_t db){
  asm volatile("{ .reg .pred p; setp.ne.b32 p, 0, 0; wgmma.mma_async.sync.aligned.m64n32k16.f32.bf16.bf16 {%0, %1, %2, %3, %4, %5, %6, %7, %8, %9, %10, %11, %12, %13, %14, %15}, %16, %17, p, 1, 1, 0, 1; }"
   : "+f"(d[0]), "+f"(d[1]), "+f"(d[2]), "+f"(d[3]), "+f"(d[4]), "+f"(d[5]), "+f"(d[6]), "+f"(d[7]), "+f"(d[8]), "+f"(d[9]), "+f"(d[10]), "+f"(d[11]), "+f"(d[12]), "+f"(d[13]), "+f"(d[14]), "+f"(d[15]) : "l"(da), "l"(db));
}
template<int N> __device__ __forceinline__ void ssz(float* d, uint64_t da, uint64_t db){
  if constexpr (N==64) sk64_z(d,da,db); else sk32_z(d,da,db);
}
template<int N> __device__ __forceinline__ void rsz(float* d, const uint32_t* a, uint64_t db){
  if constexpr (N==64) rs64_z(d,a,db); else rs32_z(d,a,db);
}
template<int N> __device__ __forceinline__ void ssk(float* d, uint64_t da, uint64_t db, bool first){
  if constexpr (N==64) { if(first) sk64_0(d,da,db); else sk64_1(d,da,db); } else { if(first) sk32_0(d,da,db); else sk32_1(d,da,db); }
}
template<int N> __device__ __forceinline__ void rs(float* d, const uint32_t* a, uint64_t db, bool first){
  if constexpr (N==120) { if(first) rs120_0(d,a,db); else rs120_1(d,a,db); }
  if constexpr (N==128) { if(first) rs128_0(d,a,db); else rs128_1(d,a,db); }
  if constexpr (N==160) { if(first) rs160_0(d,a,db); else rs160_1(d,a,db); }
  if constexpr (N==64) { if(first) rs64_0(d,a,db); else rs64_1(d,a,db); }
  if constexpr (N==56) { if(first) rs56_0(d,a,db); else rs56_1(d,a,db); }
  if constexpr (N==32) { if(first) rs32_0(d,a,db); else rs32_1(d,a,db); }
}

constexpr float LOG2E = 1.4426950408889634f;
#define EPI_TS(x) x
#define TS7(i)
#define BAR(i) (sb + MISC + 8u * (uint32_t)(i))
#define BBARI(k) asm volatile("{ .reg .pred p; setp.ne.u32 p, %0, %1; @p bra B_L; trap; B_L: }" ::"r"(sb), "n"(k) : "memory")
#define BBAR() asm volatile("{ .reg .pred p; setp.ne.u32 p, %0, %1; @p bra B_L; trap; B_L: }" ::"r"(sb), "n"(__LINE__ * 2 + 1) : "memory")

__host__ __device__ constexpr int unitB(int g) { return g == 0 ? 0 : g == 1 ? 3 : g == 6 ? 8 : 14 + 3 * (g - 2); }
__host__ __device__ constexpr int unitC(int g) { return g == 0 ? 11 : g == 1 ? 5 : g == 6 ? 8 : 14 + 3 * (g - 2); }
__host__ __device__ constexpr int unitD(int g) { return g == 0 ? 11 : 14 + 3 * ((g - 1) & 3); }
__host__ __device__ constexpr int depB(int g) { return g < 2 ? XC0 : g == 2 ? EA1 : g == 3 ? EA2 : g == 4 ? EA4 : g == 5 ? EA5 : KVST; }
__host__ __device__ constexpr int depC(int g) { return g == 0 ? KVFREE : EB1 + g - 1; }
__host__ __device__ constexpr int depD(int g) { return g == 0 ? EC0 : g < 5 ? EC0 + g + 1 : g == 5 ? ED1 : ED2; }
__host__ __device__ constexpr int eid(int P, int g) {
  return P == 0 ? (g == 1 ? EA1 : g == 2 ? EA2 : g >= 4 ? EA4 + g - 4 : -1)
       : P == 1 ? (g >= 1 ? EB1 + g - 1 : -1)
       : P == 2 ? EC0 + g
                : (g == 1 ? ED1 : g == 2 ? ED2 : g >= 4 ? ED4 + g - 4 : -1);
}
template <int P> __host__ __device__ constexpr int unitP(int g) { return P == 0 ? 14 + 2 * g : P == 1 ? unitB(g) : P == 2 ? unitC(g) : unitD(g); }
template <typename Fn> __host__ __device__ constexpr uint64_t packtab(Fn f) { uint64_t t = 0; for (int g = 0; g < 7; g++) t |= (uint64_t)f(g) << (8 * g); return t; }

template <int P, int N, typename Fn, typename Fp>
__device__ __forceinline__ void pass1(float* acc, const uint32_t* xf, uint32_t sb, uint32_t pb, bool lane0, uint64_t sh, Fn shadow, Fp post) {
#pragma unroll
  for (int g = 0; g < 7; g++) {
    mbar_wait(BAR(FA + 7 * P + g));
    wg_fence();
#pragma unroll
    for (int kk = 0; kk < 4; kk++) {
      if (P == 1) {
        rs<128>(acc, xf + 16 * g + 4 * kk, desc(unitP<P>(g) * U + kk * 2048, U), g == 0 && kk == 0);
        rs<56>(acc + 64, xf + 16 * g + 4 * kk, desc((unitP<P>(g) + 2) * U + kk * 2048, U) + sh, g == 0 && kk == 0);
      } else {
        rs<N>(acc, xf + 16 * g + 4 * kk, desc(unitP<P>(g) * U + kk * 2048, U) + (P == 0 ? sh : 0), g == 0 && kk == 0);
      }
    }
    wg_commit();
    shadow(g);
    if (g > 0) {
      wg_wait<1>();
      if (lane0) {
        if (eid(P, g - 1) >= 0) mbar_arrive(BAR(eid(P, g - 1)));
        if ((P == 1 || P == 2) && g == 2) mbar_arrive_remote(pb + MISC + 8u * (PF + P - 1));
        if (P == 3 && g == 1) mbar_arrive_remote(pb + MISC + 8u * (PF + 2));
      }
      post(g);
    }
  }
  wg_wait<0>();
  if (lane0) mbar_arrive(BAR(eid(P, 6)));
  pin<N / 2>(acc);
}

template <int ID> __device__ __forceinline__ void hfrag64(uint32_t* h, float* acc, const float* rs_, uint32_t sb, int wg) {
  const float hr[2] = {0.5f * rs_[0], 0.5f * rs_[1]};
#pragma unroll
  for (int i = 0; i < 32; i++) {
    acc[32 + i] *= acc[i];
    acc[i] *= hr[(i >> 1) & 1];
    if (i < 16) acc[i] = tanh_(acc[i]);
  }
  pin<64>(acc);
  BBARI(ID * 4 + 1);
  EPI_TS(if (ID == 1) CTS(21));
  const float c[2] = {hr[0] * hr[0], hr[1] * hr[1]};
#pragma unroll
  for (int i = 16; i < 32; i++) acc[i] = tanh_(acc[i]);
#pragma unroll
  for (int m = 0; m < 8; m++) h[m] = pack2(acc[32 + 2 * m] * fmaf(acc[2 * m], c[m & 1], c[m & 1]), acc[33 + 2 * m] * fmaf(acc[2 * m + 1], c[m & 1], c[m & 1]));
  pin<16>(acc + 16);
  pinr<8>(h);
  BBARI(ID * 4 + 3);
  EPI_TS(if (ID == 1) CTS(22));
#pragma unroll
  for (int m = 8; m < 16; m++) h[m] = pack2(acc[32 + 2 * m] * fmaf(acc[2 * m], c[m & 1], c[m & 1]), acc[33 + 2 * m] * fmaf(acc[2 * m + 1], c[m & 1], c[m & 1]));
}
__device__ __forceinline__ void phi1(float* e, float* a, const float* rs_) {
  const float rl[2] = {rs_[0] * (0.5f * LOG2E), rs_[1] * (0.5f * LOG2E)};
#pragma unroll
  for (int i = 0; i < 28; i++) {
    const float u = a[i] * rl[(i >> 1) & 1];
    e[i] = ex2(u - fabsf(u));
    a[i] = fmaf(u + fabsf(u), 0.6931471805599453f, 1e-6f);
  }
  pin<28>(e);
  pin<28>(a);
}

template <int NP> __device__ __forceinline__ void stage_ll(uint32_t dst, const float* a, uint32_t par) {
#pragma unroll
  for (int q = 0; q < NP; q++) {
    const uint32_t w[4] = {(pack2(a[8 * q], a[8 * q + 1]) & 0xFFFFFFFEu) | par, pack2(a[8 * q + 2], a[8 * q + 3]), pack2(a[8 * q + 4], a[8 * q + 5]),
                           pack2(a[8 * q + 6], a[8 * q + 7])};
    sts4(dst + q * 512, w);
  }
}
template <int NP> __device__ __forceinline__ void send_ll(uint4* dst, const float* a, uint32_t par) {
#pragma unroll
  for (int q = 0; q < NP; q++)
    asm volatile("{ .reg .b128 t; .reg .b64 lo, hi; mov.b64 lo, {%1,%2}; mov.b64 hi, {%3,%4}; mov.b128 t, {lo,hi}; st.relaxed.gpu.global.b128 [%0], t; }" ::"l"(dst + q * 32),
                 "r"((pack2(a[8 * q], a[8 * q + 1]) & 0xFFFFFFFEu) | par), "r"(pack2(a[8 * q + 2], a[8 * q + 3])), "r"(pack2(a[8 * q + 4], a[8 * q + 5])), "r"(pack2(a[8 * q + 6], a[8 * q + 7])) : "memory");
}
__device__ __forceinline__ void stg4(uint4* dst, const uint32_t* w) {
  asm volatile("{ .reg .b128 t; .reg .b64 lo, hi; mov.b64 lo, {%1,%2}; mov.b64 hi, {%3,%4}; mov.b128 t, {lo,hi}; st.relaxed.gpu.global.b128 [%0], t; }" ::"l"(dst),
               "r"(w[0]), "r"(w[1]), "r"(w[2]), "r"(w[3]) : "memory");
}
#define LL_LD(g, p, o, a, b, c, d) g "ld.relaxed.gpu.global.v4.b32 {%" #a ",%" #b ",%" #c ",%" #d "}, [%" #p "+" #o "];\n"
#define LL_LD4(g) LL_LD(g, 16, 0, 0, 1, 2, 3) LL_LD(g, 16, 512, 4, 5, 6, 7) LL_LD(g, 17, 0, 8, 9, 10, 11) LL_LD(g, 17, 512, 12, 13, 14, 15)
#define LL_OPS(c) c(v[0]), c(v[1]), c(v[2]), c(v[3]), c(v[4]), c(v[5]), c(v[6]), c(v[7]), c(v[8]), c(v[9]), c(v[10]), c(v[11]), c(v[12]), c(v[13]), c(v[14]), c(v[15])
__device__ __forceinline__ void ld_ll4(uint32_t* v, const uint4* p, const uint4* p2) {
  asm volatile(LL_LD4("") : LL_OPS("=r") : "l"(p), "l"(p2) : "memory");
}
__device__ __forceinline__ uint32_t try_ll4(uint32_t* v, const uint4* p, const uint4* p2, uint32_t bar) {
  uint32_t ok;
  asm volatile("{ .reg .pred q; mbarrier.test_wait.parity.shared::cta.b64 q, [%19], 0; selp.u32 %16, 1, 0, q; @!q bra T_D;\n"
               LL_LD("", 17, 0, 0, 1, 2, 3) LL_LD("", 17, 512, 4, 5, 6, 7) LL_LD("", 18, 0, 8, 9, 10, 11) LL_LD("", 18, 512, 12, 13, 14, 15)
               "T_D: }" : LL_OPS("=r"), "=r"(ok) : "l"(p), "l"(p2), "r"(bar) : "memory");
  return ok;
}
__device__ __forceinline__ void wait_ll4(uint32_t* v, const uint4* p, const uint4* p2, uint32_t bar, uint32_t skip) {
  asm volatile("{ .reg .pred q; .reg .u32 n; setp.ne.u32 q, %19, 0; @q bra T_D; mov.u32 n, 0;\n"
               "W_L: mbarrier.try_wait.parity.shared::cta.b64 q, [%18], 0;\n"
               "@q bra W_D; add.u32 n, n, 1; setp.ge.u32 q, n, 4194304; @q trap; bra W_L;\n"
               "W_D: " LL_LD4("") "T_D: }" : LL_OPS("+r") : "l"(p), "l"(p2), "r"(bar), "r"(skip) : "memory");
}
__device__ __forceinline__ void chk_ll(uint32_t* v, const uint4* p, const uint4* p2, uint32_t par) {
  asm volatile(
      "{ .reg .pred p; .reg .b32 t, u, n;\n"
      "mov.u32 n, 0;\n"
      "R_L: lop3.b32 t, %0, %4, %18, 0x7E; lop3.b32 u, %8, %12, %18, 0x7E; lop3.b32 t, t, u, 1, 0xA8;\n"
      "setp.eq.u32 p, t, 0; vote.sync.all.pred p, p, 0xffffffff; setp.ge.or.u32 p, n, 2097152, p; @p bra R_D;\n"
      LL_LD4("")
      "add.u32 n, n, 1; bra R_L;\n"
      "R_D:\n"
      "}"
      : LL_OPS("+r")
      : "l"(p), "l"(p2), "r"(par)
      : "memory");
}

__device__ __forceinline__ void load_x(const __nv_bfloat16* x, uint32_t sb, int r, int warp, int lane) {
  const int l8 = lane >> 3, c = lane & 7;
  const char* src = reinterpret_cast<const char*>(x + (size_t)(r * 128 + warp * 16 + l8) * DM + c * 8);
  const uint32_t dst = sb + (uint32_t)((warp >> 2) * (7 * U) + ((warp & 3) * 16 + l8) * 128 + ((c ^ l8) << 4));
#pragma unroll
  for (int kb = 0; kb < 7; kb++) {
#pragma unroll
    for (int q = 0; q < 4; q++)
      asm volatile("cp.async.cg.shared.global [%0], [%1], 16;" ::"r"((dst ^ ((q & 1) << 6)) + kb * U + q * 512), "l"(src + q * 4 * DM * 2 + kb * 128) : "memory");
    asm volatile("cp.async.commit_group;" ::: "memory");
  }
}
template <int N> __device__ __forceinline__ void cp_wait() { asm volatile("cp.async.wait_group %0;" ::"n"(N) : "memory"); }

#define LANE() const int ln = laneid(), g8 = ln >> 2, t4 = ln & 3; (void)g8; (void)t4
__device__ __forceinline__ void tail(const Maps& M, uint32_t* hf, float* acc, const uint32_t* sg, float* rs_, uint32_t sb, uint32_t pb, int warp, bool lane0) {
  const int wg = warp >> 2, w4 = warp & 3;
  constexpr int BB = 300;
  float a1[64];
  const float hr[2] = {0.5f * rs_[0], 0.5f * rs_[1]}, hc[2] = {hr[0] * hr[0], hr[1] * hr[1]};
  auto e1 = [&](int lo) {
#pragma unroll
    for (int i = lo; i < lo + 16; i++) { acc[32 + i] *= acc[i]; acc[i] = tanh_(acc[i] * hr[(i >> 1) & 1]); }
    pin<16>(acc + lo); pin<16>(acc + 32 + lo);
  };
  auto e2 = [&](int lo) {
#pragma unroll
    for (int m = lo; m < lo + 8; m++) hf[32 + m] = pack2(acc[32 + 2 * m] * fmaf(acc[2 * m], hc[m & 1], hc[m & 1]), acc[33 + 2 * m] * fmaf(acc[2 * m + 1], hc[m & 1], hc[m & 1]));
    pinr<8>(hf + 32 + lo);
  };
  const uint32_t doff = (uint32_t)(wg * 12288 + w4 * 3072 + laneid() * 16);
  auto send = [&](int s) {
    sta4(pb + 11 * U + doff + s * 512, hf + 32 + 4 * s, pb + MISC + 8u * (HF + 4) + wg * 8);
    sta4(pb + 11 * U + doff + s * 512 + 512, hf + 36 + 4 * s, pb + MISC + 8u * (HF + 4) + wg * 8);
  };
  mbar_wait(BAR(PF + 2));
  mbar_wait(BAR(FT + 0));
  wg_fence();
#pragma unroll
  for (int s = 0; s < 4; s++) rs<128>(a1, hf + 4 * s, desc(s * 2048, 16384), s == 0);
  wg_commit();
  BBARI(BB + 1);
  TS7(21);
#define SGP 3
  auto e3 = [&]() {
#pragma unroll
    for (int m = 0; m < 8; m++) {
      const int w = m & 1;
      hf[48 + m] = pack2(blo(sg[m]) * (acc[64 + 2 * m] * hr[w]), bhi(sg[m]) * (acc[65 + 2 * m] * hr[w]));
    }
    pinr<8>(hf + 48);
    send(4);
  };
  if (SGP == 0) e3();
  e1(0);
  if (SGP == 3) { e2(0); send(0); }
  BBARI(BB + 3);
  wg_fence();
#pragma unroll
  for (int s = 4; s < 8; s++) rs<128>(a1, hf + 4 * s, desc(s * 2048, 16384), false);
  wg_commit();
  BBARI(BB + 5);
  TS7(22);
  if (SGP != 3) { e2(0); send(0); }
  if (SGP == 1) e3();
  e1(16);
  if (SGP == 3) { e2(8); send(2); }
  mbar_wait(BAR(FT + 1));
  wg_fence();
#pragma unroll
  for (int s = 0; s < 4; s++) rs<128>(a1, hf + 56 + 4 * s, desc(4 * U + s * 2048, 16384), false);
  wg_commit();
  BBARI(BB + 7);
  TS7(23);
  if (SGP != 3) { e2(8); send(2); }
  if (SGP >= 2) e3();
  BBARI(BB + 9);
  wg_fence();
#pragma unroll
  for (int s = 4; s < 8; s++) rs<128>(a1, hf + 56 + 4 * s, desc(4 * U + s * 2048, 16384), false);
  wg_commit();
  wg_wait<2>();
  if (lane0) mbar_arrive(BAR(ET + 0));
  TS7(24);
  mbar_wait(BAR(FT + 2));
  wg_fence();
#pragma unroll
  for (int s = 0; s < 3; s++) rs<128>(a1, hf + 32 + 4 * s, desc(21 * U + s * 2048, 12288), false);
  wg_commit();
  CTS(9);
  wg_fence();
#pragma unroll
  for (int s = 3; s < 6; s++) rs<128>(a1, hf + 32 + 4 * s, desc(21 * U + s * 2048, 12288), false);
  wg_commit();
  wg_wait<2>();
  if (lane0) mbar_arrive(BAR(ET + 1));
  const uint64_t adw = (uint64_t)(wg * 512);
  float aw[32];
  auto wtile = [&](int t) {
    constexpr int wu[7] = {8, 11, 21, 14, 24, 17, 0};
    mbar_wait(BAR(FW + t));
    wg_fence();
#pragma unroll
    for (int kk = 0; kk < 4; kk++) {
      const uint64_t da = desc(wu[t] * U + kk * 32, 16) + adw, db = desc((wu[t] + 2) * U + kk * 2048, U);
      ssk<64>(aw, da, db, t == 0 && kk == 0);
    }
    wg_commit();
  };
  float a2[16];
  float* a3 = a1;
  auto g2 = [&](int p, int lo, int hi) {
    wg_fence();
#pragma unroll
    for (int s = lo; s < hi; s++) rs<32>(a2, hf + 56 * p + 4 * s, desc((p ? 0 : 17) * U + s * 2048, U), p == 0 && s == 0);
    wg_commit();
  };
  auto g3 = [&](int p, int lo, int hi) {
    wg_fence();
#pragma unroll
    for (int s = lo; s < hi; s++) {
      const uint64_t d = desc((p ? 4 : 24) * U + s * 2048, U);
      if (p == 0 && s == 0) rsz<64>(a3, hf, d); else rs<64>(a3, hf + 56 * p + 4 * s, d, false);
    }
    wg_commit();
  };
  uint32_t par;
  asm volatile("ld.shared.u32 %0, [%1];" : "=r"(par) : "r"(BAR(NBAR)) : "memory");
  TS7(25);
  mbar_wait(BAR(HF + 4) + wg * 8);
#pragma unroll
  for (int s = 0; s < 6; s++) lds4(hf + 88 + 4 * s, sb + 11 * U + doff + s * 512);
  CTS(10);
  const int bid = par >> 8, r = bid >> 3, kq = (bid >> 1) & 3, n = bid & 1;
  const bool Y = kq == 3 - 3 * n;
  const int io = Y ? 2 : kq - n;
  uint4* const pbase = g_p + (size_t)((r * 2 + n) * 4) * 3072 + laneid();
  uint4* const pa = pbase + (n + (io == 2 ? 0 : io + 1)) * 3072 + (Y ? 2048 : 0) + warp * 128;
  uint4* const pb2 = pbase + (n + (io == 0 ? 2 : io - 1)) * 3072 + (Y ? 2048 : 1024) + warp * 128;
  uint4* const pc = pbase + (Y ? n + 2 : 3 - 3 * n) * 3072 + io * 1024 + warp * (Y ? 128 : 64);
  auto hint = [&](int c) {
    const int kd = c == 0 ? n + (io == 2 ? 0 : io + 1) : c == 1 ? n + (io == 0 ? 2 : io - 1) : (Y ? n + 2 : 3 - 3 * n);
    const int slot = Y ? 2 : c == 2 ? io : c;
    if (lane0) SIGNAL(&g_f3[(r * 8 + kd * 2 + n) * 32 + slot * 2 + wg]);
  };
  mbar_wait(BAR(FT + 3));
  wg_fence();
#pragma unroll
  for (int s = 0; s < 6; s++) rs<128>(a1, hf + 88 + 4 * s, desc(14 * U + s * 2048, 12288), false);
  wg_commit();
  if (lane0) mbar_arrive(BAR(LD2));
  TS7(26);
  wg_wait<1>();
  if (lane0) mbar_arrive(BAR(ET + 2));
  mbar_wait(BAR(FT + 5));
  g2(0, 0, 7);
  mbar_wait(BAR(FT + 4));
  wg_wait<1>();
  if (lane0) mbar_arrive(BAR(ET + 3));
  pin<64>(a1);
  TS7(27);
  {
    uint32_t w[16];
#pragma unroll
    for (int i = 0; i < 16; i++) w[i] = pack2(a1[2 * i], a1[2 * i + 1]);
#pragma unroll
    for (int q = 0; q < 4; q++) w[4 * q] = (w[4 * q] & 0xFFFFFFFEu) | (par & 1);
    pinr<16>(w);
    g3(0, 0, 7);
    stg4(pa, w); stg4(pa + 32, w + 4);
    BBARI(BB + 11);
    g3(0, 7, 14);
    stg4(pa + 64, w + 8); stg4(pa + 96, w + 12);
  }
  hint(0);
  BBARI(BB + 13);
  TS7(28);
  mbar_wait(BAR(FT + 6));
  g2(0, 7, 14);
  wg_wait<1>();
  if (lane0) mbar_arrive(BAR(ET + 4));
  g2(1, 0, 7);
  send_ll<2>(pb2, a1 + 32, par & 1);
  BBARI(BB + 15);
  wg_wait<1>();
  if (lane0) mbar_arrive(BAR(ET + 5));
  mbar_wait(BAR(FT + 7));
  g2(1, 7, 14);
  g3(1, 0, 7);
  send_ll<2>(pb2 + 64, a1 + 48, par & 1);
  hint(1);
  BBARI(BB + 17);
  wg_wait<1>();
  if (lane0) mbar_arrive(BAR(ET + 6));
  pin<16>(a2);
  g3(1, 7, 14);
  if (!Y) { send_ll<2>(pc, a2, par & 1); hint(2); }
  BBARI(BB + 19);
  CTS(16);
  wtile(0);
  wg_wait<1>();
  pin<32>(a3);
  CTS(11);
  wtile(1);
  if (Y) {
    send_ll<4>(pc, a3, par & 1);
    hint(2);
#pragma unroll
    for (int i = 0; i < 16; i++) a3[i] = a2[i];
  }
  pin<32>(a3);
  BBARI(BB + 21);
  const uint32_t lb = sb + (uint32_t)((8 + wg) * U + w4 * 2048);
  const int row = r * 128 + warp * 16, col = Y ? 192 + 32 * n : 192 * n + 64 * kq;
  const uint4* pin_ = pbase + kq * 3072 + warp * (Y ? 64 : 128);
  const uint4* pin2 = pin_ + (Y ? 0 : 64);
  const uint32_t lf = BAR(LF) + wg * 8;
  uint32_t v[3][16];
#define LDP 1
  wg_wait<1>();
  if (lane0) mbar_arrive(BAR(EW0));
  uint32_t ok0, ok1;
  wtile(2);
  if (LDP == 1) ok0 = try_ll4(v[0], pin_, pin2, lf);
  wtile(3);
  CTS(17);
  if (LDP == 0) ok0 = try_ll4(v[0], pin_, pin2, lf);
  wtile(4);
  if (LDP == 1) ok1 = try_ll4(v[1], pin_ + 1024, pin2 + 1024, lf + 16);
  wtile(5);
  if (LDP == 0) ok1 = try_ll4(v[1], pin_ + 1024, pin2 + 1024, lf + 16);
  wtile(6);
  CTS(18);
  LANE();
  const uint32_t sa = lb + (uint32_t)((ln & 15) * 128 + (((ln >> 4) ^ (ln & 7)) << 4));
  uint32_t xr[16];
  mbar_wait(BAR(wg ? XR1 : XR0));
#pragma unroll
  for (int kk = 0; kk < 4; kk++) ldsm4(xr + 4 * kk, sa ^ (kk << 5));
#pragma unroll
  for (int i = 0; i < 16; i++) v[2][i] = 0;
  if (!(ok0 & ok1)) {
#pragma unroll
    for (int i = 0; i < 3; i++) { mbar_wait(lf + 16 * i); ld_ll4(v[i], pin_ + i * 1024, pin2 + i * 1024); }
  }
  chk_ll(v[0], pin_, pin2, par);
  chk_ll(v[1], pin_ + 1024, pin2 + 1024, par);
  wait_ll4(v[2], pin_ + 2048, pin2 + 2048, lf + 32, (ok0 & ok1) ^ 1);
  CTS(20);
#pragma unroll
  for (int i = 0; i < 2; i++) {
#pragma unroll
    for (int m = 0; m < 16; m++) { a3[2 * m] += blo(v[i][m]); a3[2 * m + 1] += bhi(v[i][m]); }
  }
  float xf_[32];
#pragma unroll
  for (int m = 0; m < 16; m++) { xf_[2 * m] = blo(xr[m]); xf_[2 * m + 1] = bhi(xr[m]); }
  pin<32>(a3); pin<32>(xf_);
  BBARI(BB + 23);
  wg_wait<0>();
  pin<32>(aw);
  CTS(19);
  chk_ll(v[2], pin_ + 2048, pin2 + 2048, par);
  CTS(12);
#pragma unroll
  for (int kk = 0; kk < 4; kk++) {
    uint32_t o[4];
#pragma unroll
    for (int m = 4 * kk; m < 4 * kk + 4; m++) {
      const float u0 = a3[2 * m] + blo(v[2][m]), u1 = a3[2 * m + 1] + bhi(v[2][m]);
      o[m & 3] = pack2(fmaf(aw[2 * m], fmaf(u0, tanh_(u0), u0), xf_[2 * m]), fmaf(aw[2 * m + 1], fmaf(u1, tanh_(u1), u1), xf_[2 * m + 1]));
    }
    stsm4(sa ^ (kk << 5), o[0], o[1], o[2], o[3]);
  }
  fence_async();
  __syncwarp();
  if (lane0) {
    tma2d_store(Y ? &M.outb : &M.outa, col, row, lb);
    bulk_commit();
    bulk_wait_read();
  }
}

__global__ void __cluster_dims__(2, 1, 1) __launch_bounds__(384, 1)
fused_kernel(const __grid_constant__ Maps M, const __grid_constant__ Ptrs P) {
  const __nv_bfloat16* xg = P.x;
  extern __shared__ __align__(1024) uint8_t smem_raw[];
  uint32_t sb = smem_u32(smem_raw);
  asm volatile("" : "+r"(sb));
  const int tid = threadIdx.x;
  const int warp = __shfl_sync(0xffffffffu, tid >> 5, 0);
  const int lane = tid & 31;
  const int wg = warp >> 2;
  const int bid = P.role[blockIdx.x], r = bid >> 3, j = bid & 7, kq = j >> 1, n = j & 1;

  if (warp < 8) CTS(27);
  if (warp < 4) load_x(xg, sb, r, warp, lane);
  if (warp < 8) CTS(28);
  if (elect_one()) {
    if ((warp >> 1) == 4) {
      const uint32_t ba = BAR(FA) + (warp - 8) * 8;
      mbar_init(ba, 1);
      mbar_expect_tx(ba, 2 * U);
      tma3d(sb + (14 + 2 * (warp - 8)) * U, &M.kv, j * 56 - 8 * n, (warp - 8) * 64, 1, ba);
    }
    const uint32_t b0 = BAR(2 + 8 * warp), cnt = warp < 6 ? 1u : 8u;
#pragma unroll
    for (int i = 0; i < 8; i++) mbar_init(b0 + 8 * i, cnt);
    if (warp >= 2) { mbar_init(BAR(94 + 2 * warp), 8); mbar_init(BAR(95 + 2 * warp), 8); }
  }
  asm volatile("fence.mbarrier_init.release.cluster;" ::: "memory");
  __syncwarp();
  if (warp < 8) CTS(29);
  asm volatile("barrier.cluster.arrive.relaxed.aligned;" ::: "memory");

  if (wg == 2) {
    asm volatile("setmaxnreg.dec.sync.aligned.u32 24;");
    if (warp == 8) {
      asm volatile("barrier.cluster.wait.acquire.aligned;" ::: "memory");
      if (elect_one()) {
        TS(2, 9);
        const int f0 = j * 224, ca = j * 56 - 8 * n;
#pragma unroll 1
        for (int g = 2; g < 7; g++) {
          mbar_expect_tx(BAR(FA + g), 2 * U);
          tma3d(sb + (14 + 2 * g) * U, &M.kv, ca, g * 64, 1, BAR(FA + g));
        }
        TS(2, 1);
        const int ro = f0 + 32 * n, rg = f0 + 192 * (1 - n);
#pragma unroll 1
        for (int p = 0; p < 3; p++) {
          const uint64_t ut = p == 0 ? packtab(unitB) : p == 1 ? packtab(unitC) : packtab(unitD);
          const uint64_t dt = p == 0 ? packtab(depB) : p == 1 ? packtab(depC) : packtab(depD);
          const CUtensorMap* m3 = p == 0 ? &M.wq : p == 1 ? &M.w1b : &M.w3b;
          const int c3 = p == 0 ? ca : rg;
#pragma unroll 1
          for (int g = 0; g < 7; g++) {
            const uint32_t dst = sb + (uint32_t)((ut >> (8 * g)) & 255) * U;
            const uint32_t fb = BAR(FB + 7 * p + g);
            mbar_expect_tx(fb, p == 0 ? 3 * U : 20480u);
            mbar_wait(BAR((uint32_t)((dt >> (8 * g)) & 255)));
            tma2d(dst, &M.w1a, ro + 64 * p, g * 64, fb);
            tma2d(dst + U, &M.w3a, ro + 64 * p, g * 64, fb);
            tma2d(dst + 2 * U, m3, c3, g * 64, fb);
          }
          TS(2, 2 + p);
        }
        const bool isy = kq == 3 - 3 * n;
        const int io = isy ? 2 : kq - n;
        mbar_wait(BAR(OFREE));
        const int cA = 256 * n + 64 * (io == 2 ? 0 : io + 1), cB = 256 * n + 64 * (io == 0 ? 2 : io - 1), cW = 256 * n + 64 * io, cN = 192 + 32 * n;
#pragma unroll 1
        for (int i = 0; i < 8; i++) {
          const int u = (i >> 1) == 2 ? i ^ 1 : i;
          const int t = u < 4 || u == 7 ? u : u == 4 ? 6 : u - 1;
          const uint32_t dst = sb + (uint32_t)((0x040011180E150400ull >> (8 * u)) & 255) * U;
          const uint64_t dt = (uint64_t)LH0 | ((uint64_t)LH1 << 8) | ((uint64_t)ED4 << 16) | ((uint64_t)ED5 << 24) | ((uint64_t)ED4 << 32) | ((uint64_t)ED6 << 40) |
                              ((uint64_t)(ET + 0) << 48) | ((uint64_t)(ET + 1) << 56);
          const uint32_t fb = BAR(FT + u);
          const int pe = t & 1, nn = n ^ pe, fb0 = (j ^ pe) * 224;
          const int r0 = fb0 + 32 * nn, r1 = fb0 + 192 * (1 - nn);
          const bool wide = t >= 6;
          mbar_expect_tx(fb, t < 2 ? 32768u : t < 4 ? 24576u : wide ? 28672u : 14336u);
          mbar_wait(BAR((uint32_t)((dt >> (8 * u)) & 255)));
          if (t < 2) {
            tma2d(dst, &M.w2a, cA, r0, fb); tma2d(dst + U, &M.w2a, cA, r0 + 64, fb);
            tma2d(dst + 2 * U, &M.w2a, cB, r0, fb); tma2d(dst + 3 * U, &M.w2a, cB, r0 + 64, fb);
          } else if (t < 4) {
            tma2d(dst, &M.w2a, cA, r0 + 128, fb); tma2d(dst + U, &M.w2b, cA, r1, fb);
            tma2d(dst + 12288, &M.w2a, cB, r0 + 128, fb); tma2d(dst + 12288 + U, &M.w2b, cB, r1, fb);
          } else {
            const CUtensorMap* m = wide ? &M.w2a : &M.w2c;
            const int c = wide ? cW : cN;
            tma2d(dst, m, c, r0, fb); tma2d(dst + U, m, c, r0 + 64, fb); tma2d(dst + 2 * U, m, c, r0 + 128, fb);
            tma2d(dst + 3 * U, m + 1, c, r1, fb);
          }
          TS(2, 10 + i);
        }
        TS(2, 7);
      }
      __syncwarp();
      {
        const uint32_t* pp = &g_f3[bid * 32 + lane];
        uint32_t ep, todo = 63;
        asm volatile("ld.shared.u32 %0, [%1];" : "=r"(ep) : "r"(BAR(NBAR) + 4) : "memory");
        if (lane == 0) { TS(2, 18); }
        while (todo & 63) {
          uint32_t w;
          asm volatile("ld.relaxed.gpu.global.u32 %0, [%1];" : "=r"(w) : "l"(pp) : "memory");
          const bool go = lane < 6 && (todo >> lane & 1) && (int)(w - 4u * ep) >= 0;
          if (go) { mbar_arrive_n(BAR(LF + lane), 8); TS(2, 19 + lane); }
          todo ^= __ballot_sync(0xffffffffu, go);
          todo += 64;
          if (todo > (1u << 27)) asm volatile("trap;");
        }
        if (lane == 0) { TSDUMP(2); }
      }
    } else {
      if (elect_one()) {
        const CUtensorMap* mp = &M.kv + (warp - 9) * 6;
        if ((sb & 0x3FFFFu) != SM_BASE) asm volatile("trap;");
#pragma unroll
        for (int i = 0; i < 6; i++) map_prefetch(mp + i);
      }
      const uint32_t ep = g_epoch[blockIdx.x] + 1;
      const int at = tid - 288;
      if (at < 32) reinterpret_cast<float4*>(g_kv + ((ep & 1) ^ 1) * (8 * 2048) + j * 2048 + r * 128)[at] = make_float4(0.f, 0.f, 0.f, 0.f);
      asm volatile("barrier.cluster.wait.acquire.aligned;" ::: "memory");
      float* kv = g_kv + (ep & 1) * (8 * 2048) + j * 2048;
      if (warp == 10 && elect_one()) {
#pragma unroll
        for (int i = 0; i < 6; i++) mbar_expect_tx(BAR(HF + i), i < 4 ? 8192u : 12288u);
        mbar_expect_tx(BAR(KVL), KV_BYTES);
      }
      mbar_wait(BAR(EA6));
      const uint32_t kvm = sb + KVM_U * U;
#pragma unroll 1
      for (int c = at; c < 512; c += 96) {
        const int d = c >> 3, cc = c & 7;
        const bool used = d < 56 && (cc == 7 || (d < 28 ? cc < 4 : (cc >= 3)));
        if (!used) { const uint32_t z[4] = {0, 0, 0, 0}; sts4(kvm + d * 128 + ((cc ^ (d & 7)) << 4), z); }
      }
      if (warp == 9) {
        mbar_wait(BAR(KVST));
        if (elect_one()) {
          asm volatile("cp.reduce.async.bulk.global.shared::cta.bulk_group.add.f32 [%0], [%1], %2;" ::"l"(kv), "r"(sb + 12 * U), "r"(KV_BYTES) : "memory");
          bulk_commit();
          bulk_wait_read();
          mbar_arrive_n(BAR(KVFREE), 8);
          bulk_wait_all();
          TS(3, 4);
          SIGNAL(&g_f1[j * 32]);
          TS(3, 0);
          poll_flag(&g_f1[j * 32], 16u * ep);
          asm volatile("fence.proxy.async.global;" ::: "memory");
          TS(3, 1);
          asm volatile("cp.async.bulk.shared::cluster.global.mbarrier::complete_tx::bytes [%0], [%1], %2, [%3];" ::"r"(sb + 27 * U), "l"(kv), "r"(KV_BYTES), "r"(BAR(KVL)) : "memory");
        }
        __syncwarp();
      }
      mbar_wait(BAR(KVL));
#pragma unroll 1
      for (int idx = at; idx < 280; idx += 96) {
        const int d = idx / 5, m = idx - d * 5;
        const bool hi = d >= 28;
        const uint32_t src = sb + 27 * U + d * (KVP * 4);
        uint32_t w[4] = {0, 0, 0, 0}, v[4];
        int cc;
        if (m == 4) {
          cc = 7;
          lds4(v, src + 128);
          w[0] = pack2(__uint_as_float(v[0]), 0.f) << (hi ? 16 : 0);
        } else {
          cc = m + (hi ? 3 : 0);
          const int o = 8 * m - (hi ? 4 : 0);
          if (o >= 0) { lds4(v, src + o * 4); w[0] = pack2(__uint_as_float(v[0]), __uint_as_float(v[1])); w[1] = pack2(__uint_as_float(v[2]), __uint_as_float(v[3])); }
          if (o + 4 < 28) { lds4(v, src + o * 4 + 16); w[2] = pack2(__uint_as_float(v[0]), __uint_as_float(v[1])); w[3] = pack2(__uint_as_float(v[2]), __uint_as_float(v[3])); }
        }
        sts4(kvm + d * 128 + ((cc ^ (d & 7)) << 4), w);
      }
      if (at == 0) asm volatile("st.shared.v2.u32 [%0], {%1, %2};" ::"r"(BAR(NBAR)), "r"((ep & 1) | (uint32_t)(bid << 8)), "r"(ep) : "memory");
      fence_async();
      __syncwarp();
      if (lane == 0) mbar_arrive_n(BAR(KVM), warp < 11 ? 3 : 2);
      if (at == 0) TS(3, 2);
      if (warp < 11) {
        const int h = warp - 9;
        const uint32_t pb = mapa(sb, n ^ 1);
#pragma unroll 1
        for (int b = 0; b < 2; b++) {
          const uint32_t off = (uint32_t)(4 * b * U + h * 8192 + lane * 16), rb = pb + MISC + 8u * (HF + 2 * b + h);
          mbar_wait(BAR(HS + 2 * b + h));
          mbar_wait(BAR(PF + b));
#pragma unroll 1
          for (int i = 0; i < 8192; i += 1024) {
            uint32_t v[8];
            lds4(v, sb + off + i); lds4(v + 4, sb + off + i + 512);
            sta4(pb + 2 * U + off + i, v, rb); sta4(pb + 2 * U + off + i + 512, v + 4, rb);
          }
          if (h == 1 && lane == 0) { TS(3, 22 + b); }
        }
        mbar_wait(BAR(OST + h));
        if (elect_one()) {
          tma2d_store(&M.ost, j * 56, r * 128 + h * 64, sb + (h ? 8 : 27) * U);
          bulk_commit();
          bulk_wait_read();
          mbar_arrive_n(BAR(OFREE), 4);
          bulk_wait_all();
          SIGNAL(&g_f2[r * 32]);
          if (h == 1) { TS(3, 3); }
          const bool isy = kq == 3 - 3 * n;
          const uint32_t xb = BAR(h ? XR1 : XR0);
          mbar_expect_tx(xb, isy ? 4096u : 8192u);
          mbar_arrive_n(xb, 7);
          mbar_wait(BAR(EW0));
#pragma unroll
          for (int i = 0; i < 4; i++) tma2d(sb + (8 + h) * U + i * 2048, isy ? &M.xrb : &M.xra, isy ? 192 + 32 * n : 192 * n + 64 * kq, r * 128 + h * 64 + i * 16, xb);
          if (h == 1) { TS(3, 17); }
        }
      } else if (elect_one()) {
        poll_flag(&g_f2[r * 32], 16u * ep);
        asm volatile("fence.proxy.async.global;" ::: "memory");
        TS(3, 5);
        const bool isy = kq == 3 - 3 * n;
        const int co = isy ? 192 + 32 * n : 192 * n + 64 * kq;
#pragma unroll 1
        for (int t = 0; t < 7; t++) {
          const uint64_t dt = (uint64_t)ED4 | ((uint64_t)LD2 << 8) | ((uint64_t)(ET + 2) << 16) | ((uint64_t)(ET + 3) << 24) | ((uint64_t)(ET + 4) << 32) |
                              ((uint64_t)(ET + 5) << 40) | ((uint64_t)(ET + 6) << 48);
          const uint32_t dst = sb + (uint32_t)((0x0011180E150B08ull >> (8 * t)) & 255) * U;
          mbar_expect_tx(BAR(FW + t), isy ? 20480u : 24576u);
          mbar_wait(BAR((uint32_t)((dt >> (8 * t)) & 255)));
          tma2d(dst, &M.o, t * 64, r * 128, BAR(FW + t));
          tma2d(dst + 2 * U, isy ? &M.wob : &M.woa, co, t * 64, BAR(FW + t));
          TS(3, 10 + t);
        }
        g_epoch[blockIdx.x] = ep;
        TS(3, 6);
      }
    }
  } else {
    asm volatile("setmaxnreg.inc.sync.aligned.u32 240;");
    asm volatile("barrier.cluster.wait.acquire.aligned;" ::: "memory");
    CTS(0);
    if (wg == 1) load_x(xg, sb, r, warp, lane);
    const int w4 = warp & 3;
    const bool lane0 = lane == 0;
    const uint32_t pb = mapa(sb, n ^ 1);
    const uint32_t so = sb + (uint32_t)((wg * 64 + w4 * 16 + (lane & 7) + ((lane >> 3) & 1) * 8) * 128 + (((lane >> 4) ^ (lane & 7)) << 4));
    uint32_t xf[112];
    float rs_[2];
    uint32_t pm0, pm1;
    float q0, q1;
    {
      float cm[2][4], ga[2][4], gb[2][4];
#pragma unroll
      for (int i = 0; i < 8; i++) cm[i >> 2][i & 3] = ga[i >> 2][i & 3] = gb[i >> 2][i & 3] = 0.f;
      const uint32_t sx = so + wg * (6 * U);
      uint32_t s0 = 0, s1 = 0;
#pragma unroll
      for (int kb = 0; kb < 7; kb++) {
        if (kb == 0) cp_wait<6>(); else if (kb == 1) cp_wait<5>(); else if (kb == 2) cp_wait<4>(); else if (kb == 3) cp_wait<3>();
        else if (kb == 4) cp_wait<2>(); else if (kb == 5) cp_wait<1>(); else cp_wait<0>();
        __syncwarp();
        if (kb == 0) CTS(14);
        EPI_TS(if (kb == 3) CTS(26));
        if (kb == 6) CTS(15);
#pragma unroll
        for (int kk = 0; kk < 4; kk++) ldsm4(xf + 16 * kb + 4 * kk, (sx ^ (kk << 5)) + kb * U);
#pragma unroll
        for (int kk = 0; kk < 4; kk++) mma16816(cm[kk & 1], xf + 16 * kb + 4 * kk, 0x3F803F80u, 0x3F803F80u);
        if (kb == 0) {
          s0 = __byte_perm(__shfl_sync(0xffffffffu, xf[0], lane & 28), 0, 0x1010);
          s1 = __byte_perm(__shfl_sync(0xffffffffu, xf[1], lane & 28), 0, 0x1010);
        }
        if (kb == 6) {
          const float m0 = (cm[0][0] + cm[1][0]) * (1.0f / 448.0f), m1 = (cm[0][2] + cm[1][2]) * (1.0f / 448.0f);
          pm0 = pack2(m0, m0); pm1 = pack2(m1, m1);
          q0 = m0 - blo(s0); q1 = m1 - blo(s1);
          __syncwarp();
          if (lane0) mbar_arrive_n(BAR(XC0) + wg * 8, 2);
        }
#pragma unroll
        for (int kk = 0; kk < 4; kk++) {
          const uint32_t* a = xf + 16 * kb + 4 * kk;
          uint32_t t[4];
#pragma unroll
          for (int i = 0; i < 4; i++) asm volatile("sub.rn.bf16x2 %0, %1, %2;" : "=r"(t[i]) : "r"(a[i]), "r"((i & 1) ? s1 : s0));
          mma16816(ga[kk & 1], t, t[0], t[2]);
          mma16816(gb[kk & 1], t, t[1], t[3]);
        }
      }
#pragma unroll
      for (int i = 0; i < 16; i++) asm volatile("sub.rn.bf16x2 %0, %0, %1;" : "+r"(xf[i]) : "r"((i & 1) ? pm1 : pm0));
      const bool odd = (lane >> 2) & 1;
      rs_[0] = odd ? ga[0][1] + ga[1][1] : ga[0][0] + ga[1][0];
      rs_[1] = odd ? gb[0][3] + gb[1][3] : gb[0][2] + gb[1][2];
    }
    CTS(1);
    uint32_t pq[14];
    {
      float acc[60];
      pass1<0, 120>(acc, xf, sb, pb, lane0, (uint64_t)n, [&](int g) {
        if (g < 6) {
#pragma unroll
          for (int i = 0; i < 16; i++) asm volatile("sub.rn.bf16x2 %0, %0, %1;" : "+r"(xf[16 * g + 16 + i]) : "r"((i & 1) ? pm1 : pm0));
        }
        if (g == 1) {
          const int src = (lane & 28) | (lane >> 3);
          const float v0 = fmaxf(fmaf(__shfl_sync(0xffffffffu, rs_[0], src), 1.0f / 448.0f, -q0 * q0), 0.f);
          const float v1 = fmaxf(fmaf(__shfl_sync(0xffffffffu, rs_[1], src), 1.0f / 448.0f, -q1 * q1), 0.f);
          rs_[0] = rcp(bfr(sqrt_(bfr(bfr(v0) + 1e-5f))));
          rs_[1] = rcp(bfr(sqrt_(bfr(bfr(v1) + 1e-5f))));
          pin<2>(rs_);
        }
      }, [&](int) {});
      CTS(2);
      LANE();
      uint32_t pk[16], pv[16];
      float e[28];
      phi1(e, acc, rs_);
#pragma unroll
      for (int m = 0; m < 14; m++) pv[m] = pack2(acc[32 + 2 * m] * rs_[m & 1], acc[33 + 2 * m] * rs_[m & 1]);
      pv[14] = pv[15] = t4 == 0 ? 0x3F803F80u : 0u;
      pinr<16>(pv);
      mbar_wait(BAR(XC1));
#pragma unroll
      for (int kk = 0; kk < 4; kk++) stsm4((so ^ (kk << 5)) + 10 * U, pv[4 * kk], pv[4 * kk + 1], pv[4 * kk + 2], pv[4 * kk + 3]);
#pragma unroll
      for (int m = 0; m < 14; m++) pk[m] = pack2(e[2 * m] + acc[2 * m], e[2 * m + 1] + acc[2 * m + 1]);
      pk[14] = pk[15] = 0u;
#pragma unroll
      for (int kk = 0; kk < 4; kk++) stsm4((so ^ (kk << 5)) + 8 * U, pk[4 * kk], pk[4 * kk + 1], pk[4 * kk + 2], pk[4 * kk + 3]);
      fence_async();
      __syncwarp();
      if (lane0) mbar_arrive(BAR(PKST));
      if (wg == 1) {
        float kv[32];
        mbar_wait(BAR(PKST));
        wg_fence();
#pragma unroll
        for (int ks = 0; ks < 8; ks++) {
          if (ks == 0) ss64_0(kv, desc(8 * U, U), desc(10 * U, U));
          else ss64_1(kv, desc(8 * U + ks * 2048, U), desc(10 * U + ks * 2048, U));
        }
        wg_commit();
        wg_wait<0>();
        pin<32>(kv);
#pragma unroll
        for (int h = 0; h < 2; h++) {
          const int d = w4 * 16 + g8 + 8 * h;
          const uint32_t lim = d < 28 ? 0u : d < 56 ? 28u : 1000u;
          const uint32_t ka = sb + 12 * U + (uint32_t)d * (KVP * 4) + (uint32_t)(2 * t4) * 4 - lim * 4;
#pragma unroll
          for (int i = 0; i < 7; i++)
            asm volatile("{ .reg .pred p; setp.lt.u32 p, %0, 28; @p st.shared.v2.f32 [%1], {%2,%3}; }" ::"r"((uint32_t)(8 * i + 2 * t4) - lim), "r"(ka + 32 * i), "f"(kv[4 * i + 2 * h]), "f"(kv[4 * i + 2 * h + 1]) : "memory");
          asm volatile("{ .reg .pred p; setp.lt.u32 p, %0, 56; @p st.shared.f32 [%1], %2; }" ::"r"((uint32_t)(d + 64 * t4)), "r"(sb + 12 * U + (uint32_t)d * (KVP * 4) + 128), "f"(kv[28 + 2 * h]) : "memory");
        }
        fence_async();
        __syncwarp();
        if (lane0) mbar_arrive_n(BAR(KVST), 2);
      }
      CTS(3);
    }
    const uint32_t hoff = (uint32_t)(wg * 8192 + w4 * 2048 + laneid() * 16);
    {
      float acc[92];
      pass1<1, 184>(acc, xf, sb, pb, lane0, (uint64_t)n, [&](int) {}, [&](int) {});
      CTS(4);
      pin<2>(rs_);
      uint32_t h[16];
      hfrag64<1>(h, acc, rs_, sb, wg);
      pinr<16>(h);
      mbar_wait(BAR(EB1));
      EPI_TS(CTS(23));
#pragma unroll
      for (int s = 0; s < 4; s++) sts4(sb + hoff + s * 512, h + 4 * s);
      __syncwarp();
      if (lane0) mbar_arrive_n(BAR(HS) + wg * 8, 2);
      EPI_TS(CTS(24));
      float e[28];
      phi1(e, acc + 64, rs_);
      EPI_TS(CTS(25));
#pragma unroll
      for (int m = 0; m < 14; m++) pq[m] = pack2(e[2 * m] + acc[64 + 2 * m], e[2 * m + 1] + acc[65 + 2 * m]);
      pq[12] ^= sb; pq[13] ^= sb;
      pinr<14>(pq);
      CTS(5);
    }
    uint32_t sg[8];
    {
      float acc[80];
      pass1<2, 160>(acc, xf, sb, pb, lane0, 0, [&](int) {}, [&](int) {});
      CTS(6);
      pin<2>(rs_);
      uint32_t h[16];
      hfrag64<2>(h, acc, rs_, sb, wg);
      pinr<16>(h);
      mbar_wait(BAR(EC0 + 1));
#pragma unroll
      for (int s = 0; s < 4; s++) sts4(sb + 4 * U + hoff + s * 512, h + 4 * s);
      __syncwarp();
      if (lane0) mbar_arrive_n(BAR(HS + 2) + wg * 8, 2);
      float nm[32];
      mbar_wait(BAR(KVM));
      {
        uint32_t q3[4];
        asm volatile("xor.b32 %0, %4, %6; xor.b32 %1, %5, %6; mov.b32 %2, 0; mov.b32 %3, 0;" : "=r"(q3[0]), "=r"(q3[1]), "=r"(q3[2]), "=r"(q3[3]) : "r"(pq[12]), "r"(pq[13]), "r"(sb));
        wg_fence();
        rs64_0(nm, pq, desc(KVM_U * U, U));
        rs64_1(nm, pq + 4, desc(KVM_U * U + 2048, U));
        rs64_1(nm, pq + 8, desc(KVM_U * U + 4096, U));
        rs64_1(nm, q3, desc(KVM_U * U + 6144, U));
      }
      wg_commit();
      float th[16];
      {
        const float hr[2] = {0.5f * rs_[0], 0.5f * rs_[1]};
#pragma unroll
        for (int i = 0; i < 16; i++) { acc[64 + i] *= hr[(i >> 1) & 1]; th[i] = tanh_(acc[64 + i]); }
        pin<16>(th); pin<16>(acc + 64);
      }
#pragma unroll
      for (int m = 0; m < 8; m++) sg[m] = pack2(fmaf(acc[64 + 2 * m], th[2 * m], acc[64 + 2 * m]), fmaf(acc[65 + 2 * m], th[2 * m + 1], acc[65 + 2 * m]));
      pinr<8>(sg);
      wg_wait<0>();
      pin<32>(nm);
      LANE();
      float rd[4];
#pragma unroll
      for (int i = 0; i < 4; i++) rd[i] = rcp(__shfl_sync(0xffffffffu, nm[28 + i], ln & 28) + 1e-6f);
      uint32_t ob[14];
#pragma unroll
      for (int i = 0; i < 7; i++) {
        const bool h0 = i < 3 || (i == 3 && t4 < 2);
        const float ra = h0 ? rd[0] : rd[1], rb = h0 ? rd[2] : rd[3];
        ob[2 * i] = pack2(nm[4 * i] * ra, nm[4 * i + 1] * ra);
        ob[2 * i + 1] = pack2(nm[4 * i + 2] * rb, nm[4 * i + 3] * rb);
      }
      mbar_wait(BAR(wg ? EC0 + 6 : EC0 + 1));
      const uint32_t sa = sb + (wg ? 8 : 27) * U + (uint32_t)(w4 * 16 + (ln & 15)) * 112;
#pragma unroll
      for (int kk = 0; kk < 3; kk++) stsm4(sa + (ln >> 4) * 16 + kk * 32, ob[4 * kk], ob[4 * kk + 1], ob[4 * kk + 2], ob[4 * kk + 3]);
      stsm2(sa + 96, ob[12], ob[13]);
      fence_async();
      __syncwarp();
      if (lane0) mbar_arrive_n(BAR(OST) + wg * 8, 2);
      CTS(7);
    }
    uint32_t hf[112];
    float acc[80];
    pass1<3, 160>(acc, xf, sb, pb, lane0, 0, [&](int) {}, [&](int g) {
      if (g == 2 || g == 4) {
        const int b = (g >> 1) - 1;
        mbar_wait(BAR(HF + 2 * b) + wg * 8);
#pragma unroll
        for (int s = 0; s < 4; s++) { lds4t(hf + 16 * b + 4 * s, xf + 32 * b + 4 * s, sb + 4 * b * U + hoff + s * 512); lds4t(hf + 56 + 16 * b + 4 * s, xf + 32 * b + 16 + 4 * s, sb + (4 * b + 2) * U + hoff + s * 512); }
        pinr<16>(hf + 16 * b); pinr<16>(hf + 56 + 16 * b);
      }
      if (g == 3 || g == 5) {
        const int b = (g >> 1) - 1;
        const uint32_t* u = hf + 16 * b;
        uint32_t one;
        if (g == 3) BBARI(101); else BBARI(103);
        asm volatile("{ .reg .b32 t; lop3.b32 t, %1, %2, %3, 0xFE; lop3.b32 t, t, %4, %5, 0xFE; lop3.b32 t, t, %6, %7, 0xFE; lop3.b32 t, t, %8, 1, 0xFE;\n"
                     "redux.sync.min.u32 t, t, 0xffffffff; min.u32 %0, t, 1; }"
                     : "=r"(one) : "r"(u[0]), "r"(u[4]), "r"(u[8]), "r"(u[12]), "r"(u[56]), "r"(u[60]), "r"(u[64]), "r"(u[68]));
        if (lane0) mbar_arrive_n(BAR(LH0 + b), one);
      }
    });
    CTS(8);
    tail(M, hf, acc, sg, rs_, sb, pb, warp, lane0);
    CTS(13);
    if ((tid & 127) == 0) { GTS(wg, 30); TSDUMP(wg); if (wg == 1) { TSDUMP(3); } }
  }
}

typedef CUresult (*EncodeFn)(CUtensorMap*, CUtensorMapDataType, cuuint32_t, void*, const cuuint64_t*, const cuuint64_t*, const cuuint32_t*,
                             const cuuint32_t*, CUtensorMapInterleave, CUtensorMapSwizzle, CUtensorMapL2promotion, CUtensorMapFloatOOBfill);

void make_map(EncodeFn enc, CUtensorMap* m, const void* base, uint64_t cols, uint64_t rows, uint32_t bc, uint32_t br, bool sw) {
  cuuint64_t dims[2] = {cols, rows}, str[1] = {cols * 2};
  cuuint32_t box[2] = {bc, br}, es[2] = {1, 1};
  enc(m, CU_TENSOR_MAP_DATA_TYPE_BFLOAT16, 2, const_cast<void*>(base), dims, str, box, es, CU_TENSOR_MAP_INTERLEAVE_NONE,
      sw ? CU_TENSOR_MAP_SWIZZLE_128B : CU_TENSOR_MAP_SWIZZLE_NONE, CU_TENSOR_MAP_L2_PROMOTION_L2_128B, CU_TENSOR_MAP_FLOAT_OOB_FILL_NONE);
}
void make_map3(EncodeFn enc, CUtensorMap* m, const void* base, uint64_t sec, uint64_t nsec, uint64_t rows, uint32_t bc, uint32_t br, uint32_t bs) {
  cuuint64_t dims[3] = {sec, rows, nsec}, str[2] = {sec * nsec * 2, sec * 2};
  cuuint32_t box[3] = {bc, br, bs}, es[3] = {1, 1, 1};
  enc(m, CU_TENSOR_MAP_DATA_TYPE_BFLOAT16, 3, const_cast<void*>(base), dims, str, box, es, CU_TENSOR_MAP_INTERLEAVE_NONE,
      CU_TENSOR_MAP_SWIZZLE_128B, CU_TENSOR_MAP_L2_PROMOTION_L2_128B, CU_TENSOR_MAP_FLOAT_OOB_FILL_NONE);
}

}

extern "C" void kernel_launch(void* const* d_in, const int* in_sizes, int n_in, void* d_out, int out_size) {
  (void)in_sizes; (void)n_in; (void)out_size;
  void* fn = nullptr;
  cudaDriverEntryPointQueryResult q;
  cudaGetDriverEntryPoint("cuTensorMapEncodeTiled", &fn, cudaEnableDefault, &q);
  EncodeFn enc = (EncodeFn)fn;
  void* op = nullptr;
  cudaGetSymbolAddress(&op, g_o);
  Maps M;
  make_map3(enc, &M.kv, d_in[1], DM, 3, DM, 64, 64, 2);
  make_map(enc, &M.wq, d_in[1], 3 * DM, DM, 64, 64, true);
  make_map(enc, &M.w1a, d_in[4], FF, DM, 64, 64, true);
  make_map(enc, &M.w3a, d_in[5], FF, DM, 64, 64, true);
  make_map(enc, &M.w1b, d_in[4], FF, DM, 32, 64, true);
  make_map(enc, &M.w3b, d_in[5], FF, DM, 32, 64, true);
  make_map(enc, &M.w2a, d_in[6], DM, FF, 64, 64, true);
  make_map(enc, &M.w2b, d_in[6], DM, FF, 64, 32, true);
  make_map(enc, &M.w2c, d_in[6], DM, FF, 32, 64, true);
  make_map(enc, &M.w2d, d_in[6], DM, FF, 32, 32, true);
  make_map(enc, &M.woa, d_in[2], DM, DM, 64, 64, true);
  make_map(enc, &M.wob, d_in[2], DM, DM, 32, 64, true);
  make_map(enc, &M.o, op, DM, SEQ, 64, 128, true);
  make_map(enc, &M.ost, op, DM, SEQ, 56, 64, false);
  make_map(enc, &M.outa, d_out, DM, SEQ, 64, 16, true);
  make_map(enc, &M.outb, d_out, DM, SEQ, 32, 16, true);
  make_map(enc, &M.xra, d_in[0], DM, SEQ, 64, 16, true);
  make_map(enc, &M.xrb, d_in[0], DM, SEQ, 32, 16, true);
  cudaFuncSetAttribute(fused_kernel, cudaFuncAttributeMaxDynamicSharedMemorySize, (int)SMEM_BYTES);
  Ptrs P;
  P.x = (const __nv_bfloat16*)d_in[0]; P.wqkv = (const __nv_bfloat16*)d_in[1]; P.wo = (const __nv_bfloat16*)d_in[2];
  P.w1 = (const __nv_bfloat16*)d_in[4]; P.w3 = (const __nv_bfloat16*)d_in[5]; P.w2 = (const __nv_bfloat16*)d_in[6];
  {
    int cnt[4] = {0, 0, 0, 0};
    for (int c = 0; c < 64; c++) {
      const int kq = c < 4 ? 0 : c < 36 ? ((c - 4) & 7) >> 1 : ((c - 36) % 7 + 1) >> 1;
      const int r = cnt[kq]++;
      P.role[2 * c] = (uint32_t)(r * 8 + kq * 2);
      P.role[2 * c + 1] = (uint32_t)(r * 8 + kq * 2 + 1);
    }
  }
  fused_kernel<<<128, 384, SMEM_BYTES>>>(M, P);
}
```

```cpp
#include <cuda_runtime.h>
#include <cuda.h>
#include <cuda_bf16.h>
#include <stdint.h>

namespace {

constexpr int SEQ = 2048, DM = 448, FF = 1792;
constexpr uint32_t U = 8192;
constexpr uint32_t SM_BASE = 1024;
constexpr uint32_t MISC = 28 * U;
constexpr uint32_t SMEM_BYTES = 28 * U + 3072;
constexpr uint32_t KVM_U = 26;

enum : int { FA = 0, FB = 7, FC = 14, FD = 21, FT = 28, FW = 36, HF = 43, KVL = 49,
             LH0 = 50, LH1, EA1 = 52, EA2, EA4, EA5, EA6, EB1 = 57, EC0 = 63, ED1 = 70, OF0, ED4, ED5, ED6, ET = 75,
             PKST = 83, LD2, PF = 85, EW0 = 88, XC0, XC1, KVST, OST = 92, KVM = 94, OFREE, XR0, KVFREE, ED2 = 98, ED3, LHA, XH, XG = 104, XR1 = 105, CLR = 106, HS = 112, NBAR = 118 };
constexpr int KVP = 36;
constexpr uint32_t KV_BYTES = 56 * KVP * 4;

struct Maps { CUtensorMap kv, wq, w1a, w3a, w1b, w3b, w2a, w2b, w2c, w2d, woa, wob, o, ost, outa, outb, xra, xrb; };

struct Ptrs { const __nv_bfloat16 *x, *wqkv, *wo, *w1, *w3, *w2; __nv_bfloat16* out; uint32_t role[128]; };

__device__ uint32_t g_epoch[128];
__device__ uint32_t g_f1[8 * 32];
__device__ uint32_t g_f2[16 * 32];
__device__ __align__(128) float g_kv[2 * 8 * 2048];
__device__ __nv_bfloat16 g_o[SEQ * DM];
__device__ uint4 g_p[16 * 2 * 4 * 3 * 1024];
#define TS(role, i)
#define GTS(role, i)
#define CTS(i)
#define TSDUMP(role)

__device__ __forceinline__ uint32_t smem_u32(const void* p) { return (uint32_t)__cvta_generic_to_shared(p); }
__device__ __forceinline__ void mbar_init(uint32_t bar, uint32_t cnt) { asm volatile("mbarrier.init.shared::cta.b64 [%0], %1;" ::"r"(bar), "r"(cnt) : "memory"); }
__device__ __forceinline__ void mbar_expect_tx(uint32_t bar, uint32_t bytes) { asm volatile("mbarrier.arrive.expect_tx.shared::cta.b64 _, [%0], %1;" ::"r"(bar), "r"(bytes) : "memory"); }
__device__ __forceinline__ void mbar_arrive_n(uint32_t bar, uint32_t n) { asm volatile("mbarrier.arrive.shared::cta.b64 _, [%0], %1;" ::"r"(bar), "r"(n) : "memory"); }
__device__ __forceinline__ void mbar_arrive(uint32_t bar) { asm volatile("mbarrier.arrive.shared::cta.b64 _, [%0];" ::"r"(bar) : "memory"); }
__device__ __forceinline__ void mbar_arrive_remote(uint32_t rbar) { asm volatile("mbarrier.arrive.shared::cluster.b64 _, [%0];" ::"r"(rbar) : "memory"); }
__device__ __forceinline__ void mbar_wait(uint32_t bar) {
  asm volatile("{ .reg .pred p; .reg .u32 n; mov.u32 n, 0;\n"
               "W_L: mbarrier.try_wait.parity.shared::cta.b64 p, [%0], 0;\n"
               "@p bra W_D;\n add.u32 n, n, 1;\n setp.lt.u32 p, n, 4194304;\n @p bra W_L;\n trap;\n W_D: }" ::"r"(bar) : "memory");
}
__device__ __forceinline__ void tma2d(uint32_t dst, const CUtensorMap* m, int c0, int c1, uint32_t bar) {
  asm volatile("cp.async.bulk.tensor.2d.shared::cluster.global.mbarrier::complete_tx::bytes [%0], [%1, {%3, %4}], [%2];" ::"r"(dst), "l"(m), "r"(bar), "r"(c0), "r"(c1) : "memory");
}
__device__ __forceinline__ void tma3d(uint32_t dst, const CUtensorMap* m, int c0, int c1, int c2, uint32_t bar) {
  asm volatile("cp.async.bulk.tensor.3d.shared::cluster.global.mbarrier::complete_tx::bytes [%0], [%1, {%3, %4, %5}], [%2];" ::"r"(dst), "l"(m), "r"(bar), "r"(c0), "r"(c1), "r"(c2) : "memory");
}
__device__ __forceinline__ void bulk_s2g(void* g, uint32_t src, uint32_t bytes) {
  asm volatile("cp.async.bulk.global.shared::cta.bulk_group [%0], [%1], %2;" ::"l"(g), "r"(src), "r"(bytes) : "memory");
}
__device__ __forceinline__ void bulk_commit() { asm volatile("cp.async.bulk.commit_group;" ::: "memory"); }
__device__ __forceinline__ void bulk_wait_read() { asm volatile("cp.async.bulk.wait_group.read 0;" ::: "memory"); }
__device__ __forceinline__ void bulk_wait_all() { asm volatile("cp.async.bulk.wait_group 0;" ::: "memory"); }
__device__ __forceinline__ void l2_prefetch(const void* g, uint32_t bytes) { asm volatile("cp.async.bulk.prefetch.L2.global [%0], %1;" ::"l"(g), "r"(bytes) : "memory"); }
__device__ __forceinline__ void map_prefetch(const CUtensorMap* m) { asm volatile("prefetch.tensormap [%0];" ::"l"(m) : "memory"); }
__device__ __forceinline__ void tma2d_store(const CUtensorMap* m, int c0, int c1, uint32_t src) {
  asm volatile("cp.async.bulk.tensor.2d.global.shared::cta.bulk_group [%0, {%2, %3}], [%1];" ::"l"(m), "r"(src), "r"(c0), "r"(c1) : "memory");
}
__device__ __forceinline__ void bulk_s2c(uint32_t rdst, uint32_t src, uint32_t bytes, uint32_t rbar) {
  asm volatile("cp.async.bulk.shared::cluster.shared::cta.mbarrier::complete_tx::bytes [%0], [%1], %2, [%3];" ::"r"(rdst), "r"(src), "r"(bytes), "r"(rbar) : "memory");
}
__device__ __forceinline__ uint32_t mapa(uint32_t a, uint32_t cta) { uint32_t r; asm volatile("mapa.shared::cluster.u32 %0, %1, %2;" : "=r"(r) : "r"(a), "r"(cta)); return r; }
__device__ __forceinline__ bool elect_one() { uint32_t p; asm volatile("{ .reg .pred P; elect.sync _|P, 0xffffffff; selp.u32 %0, 1, 0, P; }" : "=r"(p)); return p; }
__device__ __forceinline__ int laneid() { int l; asm volatile("mov.u32 %0, %%laneid;" : "=r"(l)); return l; }
__device__ __forceinline__ void fence_async() { asm volatile("fence.proxy.async.shared::cta;" ::: "memory"); }
__device__ __forceinline__ void wg_fence() { asm volatile("wgmma.fence.sync.aligned;" ::: "memory"); }
__device__ __forceinline__ void wg_commit() { asm volatile("wgmma.commit_group.sync.aligned;" ::: "memory"); }
template <int N> __device__ __forceinline__ void wg_wait() { asm volatile("wgmma.wait_group.sync.aligned %0;" ::"n"(N) : "memory"); }
template <int N> __device__ __forceinline__ void pin(float* a) {
#pragma unroll
  for (int i = 0; i < N; i++) asm volatile("" : "+f"(a[i])::"memory");
}
template <int N> __device__ __forceinline__ void pinr(uint32_t* a) {
#pragma unroll
  for (int i = 0; i < N; i++) asm volatile("" : "+r"(a[i])::"memory");
}
__device__ __forceinline__ void ldsm4(uint32_t* r, uint32_t a) { asm volatile("ldmatrix.sync.aligned.m8n8.x4.shared.b16 {%0,%1,%2,%3}, [%4];" : "=r"(r[0]), "=r"(r[1]), "=r"(r[2]), "=r"(r[3]) : "r"(a) : "memory"); }
__device__ __forceinline__ void stsm4(uint32_t a, uint32_t r0, uint32_t r1, uint32_t r2, uint32_t r3) { asm volatile("stmatrix.sync.aligned.m8n8.x4.shared.b16 [%0], {%1,%2,%3,%4};" ::"r"(a), "r"(r0), "r"(r1), "r"(r2), "r"(r3) : "memory"); }
__device__ __forceinline__ void stsm2(uint32_t a, uint32_t r0, uint32_t r1) { asm volatile("stmatrix.sync.aligned.m8n8.x2.shared.b16 [%0], {%1,%2};" ::"r"(a), "r"(r0), "r"(r1) : "memory"); }
__device__ __forceinline__ void sts4(uint32_t a, const uint32_t* r) { asm volatile("st.shared.v4.b32 [%0], {%1,%2,%3,%4};" ::"r"(a), "r"(r[0]), "r"(r[1]), "r"(r[2]), "r"(r[3]) : "memory"); }
__device__ __forceinline__ void sta4(uint32_t ra, const uint32_t* r, uint32_t rbar) {
  asm volatile("st.async.weak.shared::cluster.mbarrier::complete_tx::bytes.v4.b32 [%0], {%1,%2,%3,%4}, [%5];" ::"r"(ra), "r"(r[0]), "r"(r[1]), "r"(r[2]), "r"(r[3]), "r"(rbar) : "memory");
}
__device__ __forceinline__ void lds4(uint32_t* r, uint32_t a) { asm volatile("ld.shared.v4.b32 {%0,%1,%2,%3}, [%4];" : "=r"(r[0]), "=r"(r[1]), "=r"(r[2]), "=r"(r[3]) : "r"(a) : "memory"); }
__device__ __forceinline__ void lds4t(uint32_t* r, const uint32_t* o, uint32_t a) {
  r[0] = o[0]; r[1] = o[1]; r[2] = o[2]; r[3] = o[3];
  asm volatile("{ .reg .pred p; setp.ne.u32 p, %4, 1; @p ld.shared.v4.b32 {%0,%1,%2,%3}, [%4]; }" : "+r"(r[0]), "+r"(r[1]), "+r"(r[2]), "+r"(r[3]) : "r"(a) : "memory");
}
__device__ __forceinline__ uint32_t pack2(float lo, float hi) { uint32_t r; asm("cvt.rn.bf16x2.f32 %0, %1, %2;" : "=r"(r) : "f"(hi), "f"(lo)); return r; }
__device__ __forceinline__ float blo(uint32_t v) { return __uint_as_float(v << 16); }
__device__ __forceinline__ float bhi(uint32_t v) { return __uint_as_float(v & 0xFFFF0000u); }
__device__ __forceinline__ float ex2(float x) { float y; asm("ex2.approx.ftz.f32 %0, %1;" : "=f"(y) : "f"(x)); return y; }
__device__ __forceinline__ float rcp(float x) { float y; asm("rcp.approx.ftz.f32 %0, %1;" : "=f"(y) : "f"(x)); return y; }
__device__ __forceinline__ float sqrt_(float x) { float y; asm("sqrt.approx.ftz.f32 %0, %1;" : "=f"(y) : "f"(x)); return y; }
__device__ __forceinline__ void mma16816(float* c, const uint32_t* a, uint32_t b0, uint32_t b1) {
  asm volatile("mma.sync.aligned.m16n8k16.row.col.f32.bf16.bf16.f32 {%0,%1,%2,%3}, {%4,%5,%6,%7}, {%8,%9}, {%0,%1,%2,%3};"
               : "+f"(c[0]), "+f"(c[1]), "+f"(c[2]), "+f"(c[3]) : "r"(a[0]), "r"(a[1]), "r"(a[2]), "r"(a[3]), "r"(b0), "r"(b1));
}
__device__ __forceinline__ float tanh_(float x) { float y; asm("tanh.approx.f32 %0, %1;" : "=f"(y) : "f"(x)); return y; }
__device__ __forceinline__ float bfr(float x) { return __bfloat162float(__float2bfloat16_rn(x)); }
__device__ __forceinline__ uint32_t ld_acq(const uint32_t* p) { uint32_t v; asm volatile("ld.acquire.gpu.global.u32 %0, [%1];" : "=r"(v) : "l"(p) : "memory"); return v; }
__device__ __forceinline__ void poll_flag(const uint32_t* p, uint32_t target) {
  uint32_t n = 0;
  while ((int)(ld_acq(p) - target) < 0) { if (++n > (1u << 21)) asm volatile("trap;"); }
}
#define SIGNAL(p) asm volatile("red.relaxed.gpu.global.add.u32 [%0], 1;" ::"l"(p) : "memory")
__device__ __forceinline__ void ld_ll(uint32_t* r, const uint4* p) {
  asm volatile("{ .reg .b128 t; .reg .b64 lo, hi; ld.relaxed.gpu.global.b128 t, [%4]; mov.b128 {lo,hi}, t; mov.b64 {%0,%1}, lo; mov.b64 {%2,%3}, hi; }" : "=r"(r[0]), "=r"(r[1]), "=r"(r[2]), "=r"(r[3]) : "l"(p) : "memory");
}
__device__ __forceinline__ constexpr uint64_t desc(uint32_t off, uint32_t lbo) {
  return (uint64_t)((SM_BASE + off) >> 4) | ((uint64_t)(lbo >> 4) << 16) | ((uint64_t)64 << 32) | ((uint64_t)1 << 62);
}

__device__ __forceinline__ void rs120_0(float* d, const uint32_t* a, uint64_t db){
  asm volatile("{ .reg .pred p; setp.ne.b32 p, 0, 0; wgmma.mma_async.sync.aligned.m64n120k16.f32.bf16.bf16 {%0, %1, %2, %3, %4, %5, %6, %7, %8, %9, %10, %11, %12, %13, %14, %15, %16, %17, %18, %19, %20, %21, %22, %23, %24, %25, %26, %27, %28, %29, %30, %31, %32, %33, %34, %35, %36, %37, %38, %39, %40, %41, %42, %43, %44, %45, %46, %47, %48, %49, %50, %51, %52, %53, %54, %55, %56, %57, %58, %59}, {%60,%61,%62,%63}, %64, p, 1, 1, 1; }"
   : "=f"(d[0]), "=f"(d[1]), "=f"(d[2]), "=f"(d[3]), "=f"(d[4]), "=f"(d[5]), "=f"(d[6]), "=f"(d[7]), "=f"(d[8]), "=f"(d[9]), "=f"(d[10]), "=f"(d[11]), "=f"(d[12]), "=f"(d[13]), "=f"(d[14]), "=f"(d[15]), "=f"(d[16]), "=f"(d[17]), "=f"(d[18]), "=f"(d[19]), "=f"(d[20]), "=f"(d[21]), "=f"(d[22]), "=f"(d[23]), "=f"(d[24]), "=f"(d[25]), "=f"(d[26]), "=f"(d[27]), "=f"(d[28]), "=f"(d[29]), "=f"(d[30]), "=f"(d[31]), "=f"(d[32]), "=f"(d[33]), "=f"(d[34]), "=f"(d[35]), "=f"(d[36]), "=f"(d[37]), "=f"(d[38]), "=f"(d[39]), "=f"(d[40]), "=f"(d[41]), "=f"(d[42]), "=f"(d[43]), "=f"(d[44]), "=f"(d[45]), "=f"(d[46]), "=f"(d[47]), "=f"(d[48]), "=f"(d[49]), "=f"(d[50]), "=f"(d[51]), "=f"(d[52]), "=f"(d[53]), "=f"(d[54]), "=f"(d[55]), "=f"(d[56]), "=f"(d[57]), "=f"(d[58]), "=f"(d[59]) : "r"(a[0]),"r"(a[1]),"r"(a[2]),"r"(a[3]), "l"(db));
}
__device__ __forceinline__ void rs120_1(float* d, const uint32_t* a, uint64_t db){
  asm volatile("{ .reg .pred p; setp.ne.b32 p, 1, 0; wgmma.mma_async.sync.aligned.m64n120k16.f32.bf16.bf16 {%0, %1, %2, %3, %4, %5, %6, %7, %8, %9, %10, %11, %12, %13, %14, %15, %16, %17, %18, %19, %20, %21, %22, %23, %24, %25, %26, %27, %28, %29, %30, %31, %32, %33, %34, %35, %36, %37, %38, %39, %40, %41, %42, %43, %44, %45, %46, %47, %48, %49, %50, %51, %52, %53, %54, %55, %56, %57, %58, %59}, {%60,%61,%62,%63}, %64, p, 1, 1, 1; }"
   : "+f"(d[0]), "+f"(d[1]), "+f"(d[2]), "+f"(d[3]), "+f"(d[4]), "+f"(d[5]), "+f"(d[6]), "+f"(d[7]), "+f"(d[8]), "+f"(d[9]), "+f"(d[10]), "+f"(d[11]), "+f"(d[12]), "+f"(d[13]), "+f"(d[14]), "+f"(d[15]), "+f"(d[16]), "+f"(d[17]), "+f"(d[18]), "+f"(d[19]), "+f"(d[20]), "+f"(d[21]), "+f"(d[22]), "+f"(d[23]), "+f"(d[24]), "+f"(d[25]), "+f"(d[26]), "+f"(d[27]), "+f"(d[28]), "+f"(d[29]), "+f"(d[30]), "+f"(d[31]), "+f"(d[32]), "+f"(d[33]), "+f"(d[34]), "+f"(d[35]), "+f"(d[36]), "+f"(d[37]), "+f"(d[38]), "+f"(d[39]), "+f"(d[40]), "+f"(d[41]), "+f"(d[42]), "+f"(d[43]), "+f"(d[44]), "+f"(d[45]), "+f"(d[46]), "+f"(d[47]), "+f"(d[48]), "+f"(d[49]), "+f"(d[50]), "+f"(d[51]), "+f"(d[52]), "+f"(d[53]), "+f"(d[54]), "+f"(d[55]), "+f"(d[56]), "+f"(d[57]), "+f"(d[58]), "+f"(d[59]) : "r"(a[0]),"r"(a[1]),"r"(a[2]),"r"(a[3]), "l"(db));
}
__device__ __forceinline__ void rs128_0(float* d, const uint32_t* a, uint64_t db){
  asm volatile("{ .reg .pred p; setp.ne.b32 p, 0, 0; wgmma.mma_async.sync.aligned.m64n128k16.f32.bf16.bf16 {%0, %1, %2, %3, %4, %5, %6, %7, %8, %9, %10, %11, %12, %13, %14, %15, %16, %17, %18, %19, %20, %21, %22, %23, %24, %25, %26, %27, %28, %29, %30, %31, %32, %33, %34, %35, %36, %37, %38, %39, %40, %41, %42, %43, %44, %45, %46, %47, %48, %49, %50, %51, %52, %53, %54, %55, %56, %57, %58, %59, %60, %61, %62, %63}, {%64,%65,%66,%67}, %68, p, 1, 1, 1; }"
   : "=f"(d[0]), "=f"(d[1]), "=f"(d[2]), "=f"(d[3]), "=f"(d[4]), "=f"(d[5]), "=f"(d[6]), "=f"(d[7]), "=f"(d[8]), "=f"(d[9]), "=f"(d[10]), "=f"(d[11]), "=f"(d[12]), "=f"(d[13]), "=f"(d[14]), "=f"(d[15]), "=f"(d[16]), "=f"(d[17]), "=f"(d[18]), "=f"(d[19]), "=f"(d[20]), "=f"(d[21]), "=f"(d[22]), "=f"(d[23]), "=f"(d[24]), "=f"(d[25]), "=f"(d[26]), "=f"(d[27]), "=f"(d[28]), "=f"(d[29]), "=f"(d[30]), "=f"(d[31]), "=f"(d[32]), "=f"(d[33]), "=f"(d[34]), "=f"(d[35]), "=f"(d[36]), "=f"(d[37]), "=f"(d[38]), "=f"(d[39]), "=f"(d[40]), "=f"(d[41]), "=f"(d[42]), "=f"(d[43]), "=f"(d[44]), "=f"(d[45]), "=f"(d[46]), "=f"(d[47]), "=f"(d[48]), "=f"(d[49]), "=f"(d[50]), "=f"(d[51]), "=f"(d[52]), "=f"(d[53]), "=f"(d[54]), "=f"(d[55]), "=f"(d[56]), "=f"(d[57]), "=f"(d[58]), "=f"(d[59]), "=f"(d[60]), "=f"(d[61]), "=f"(d[62]), "=f"(d[63]) : "r"(a[0]),"r"(a[1]),"r"(a[2]),"r"(a[3]), "l"(db));
}
__device__ __forceinline__ void rs128_1(float* d, const uint32_t* a, uint64_t db){
  asm volatile("{ .reg .pred p; setp.ne.b32 p, 1, 0; wgmma.mma_async.sync.aligned.m64n128k16.f32.bf16.bf16 {%0, %1, %2, %3, %4, %5, %6, %7, %8, %9, %10, %11, %12, %13, %14, %15, %16, %17, %18, %19, %20, %21, %22, %23, %24, %25, %26, %27, %28, %29, %30, %31, %32, %33, %34, %35, %36, %37, %38, %39, %40, %41, %42, %43, %44, %45, %46, %47, %48, %49, %50, %51, %52, %53, %54, %55, %56, %57, %58, %59, %60, %61, %62, %63}, {%64,%65,%66,%67}, %68, p, 1, 1, 1; }"
   : "+f"(d[0]), "+f"(d[1]), "+f"(d[2]), "+f"(d[3]), "+f"(d[4]), "+f"(d[5]), "+f"(d[6]), "+f"(d[7]), "+f"(d[8]), "+f"(d[9]), "+f"(d[10]), "+f"(d[11]), "+f"(d[12]), "+f"(d[13]), "+f"(d[14]), "+f"(d[15]), "+f"(d[16]), "+f"(d[17]), "+f"(d[18]), "+f"(d[19]), "+f"(d[20]), "+f"(d[21]), "+f"(d[22]), "+f"(d[23]), "+f"(d[24]), "+f"(d[25]), "+f"(d[26]), "+f"(d[27]), "+f"(d[28]), "+f"(d[29]), "+f"(d[30]), "+f"(d[31]), "+f"(d[32]), "+f"(d[33]), "+f"(d[34]), "+f"(d[35]), "+f"(d[36]), "+f"(d[37]), "+f"(d[38]), "+f"(d[39]), "+f"(d[40]), "+f"(d[41]), "+f"(d[42]), "+f"(d[43]), "+f"(d[44]), "+f"(d[45]), "+f"(d[46]), "+f"(d[47]), "+f"(d[48]), "+f"(d[49]), "+f"(d[50]), "+f"(d[51]), "+f"(d[52]), "+f"(d[53]), "+f"(d[54]), "+f"(d[55]), "+f"(d[56]), "+f"(d[57]), "+f"(d[58]), "+f"(d[59]), "+f"(d[60]), "+f"(d[61]), "+f"(d[62]), "+f"(d[63]) : "r"(a[0]),"r"(a[1]),"r"(a[2]),"r"(a[3]), "l"(db));
}
__device__ __forceinline__ void rs160_0(float* d, const uint32_t* a, uint64_t db){
  asm volatile("{ .reg .pred p; setp.ne.b32 p, 0, 0; wgmma.mma_async.sync.aligned.m64n160k16.f32.bf16.bf16 {%0, %1, %2, %3, %4, %5, %6, %7, %8, %9, %10, %11, %12, %13, %14, %15, %16, %17, %18, %19, %20, %21, %22, %23, %24, %25, %26, %27, %28, %29, %30, %31, %32, %33, %34, %35, %36, %37, %38, %39, %40, %41, %42, %43, %44, %45, %46, %47, %48, %49, %50, %51, %52, %53, %54, %55, %56, %57, %58, %59, %60, %61, %62, %63, %64, %65, %66, %67, %68, %69, %70, %71, %72, %73, %74, %75, %76, %77, %78, %79}, {%80,%81,%82,%83}, %84, p, 1, 1, 1; }"
   : "=f"(d[0]), "=f"(d[1]), "=f"(d[2]), "=f"(d[3]), "=f"(d[4]), "=f"(d[5]), "=f"(d[6]), "=f"(d[7]), "=f"(d[8]), "=f"(d[9]), "=f"(d[10]), "=f"(d[11]), "=f"(d[12]), "=f"(d[13]), "=f"(d[14]), "=f"(d[15]), "=f"(d[16]), "=f"(d[17]), "=f"(d[18]), "=f"(d[19]), "=f"(d[20]), "=f"(d[21]), "=f"(d[22]), "=f"(d[23]), "=f"(d[24]), "=f"(d[25]), "=f"(d[26]), "=f"(d[27]), "=f"(d[28]), "=f"(d[29]), "=f"(d[30]), "=f"(d[31]), "=f"(d[32]), "=f"(d[33]), "=f"(d[34]), "=f"(d[35]), "=f"(d[36]), "=f"(d[37]), "=f"(d[38]), "=f"(d[39]), "=f"(d[40]), "=f"(d[41]), "=f"(d[42]), "=f"(d[43]), "=f"(d[44]), "=f"(d[45]), "=f"(d[46]), "=f"(d[47]), "=f"(d[48]), "=f"(d[49]), "=f"(d[50]), "=f"(d[51]), "=f"(d[52]), "=f"(d[53]), "=f"(d[54]), "=f"(d[55]), "=f"(d[56]), "=f"(d[57]), "=f"(d[58]), "=f"(d[59]), "=f"(d[60]), "=f"(d[61]), "=f"(d[62]), "=f"(d[63]), "=f"(d[64]), "=f"(d[65]), "=f"(d[66]), "=f"(d[67]), "=f"(d[68]), "=f"(d[69]), "=f"(d[70]), "=f"(d[71]), "=f"(d[72]), "=f"(d[73]), "=f"(d[74]), "=f"(d[75]), "=f"(d[76]), "=f"(d[77]), "=f"(d[78]), "=f"(d[79]) : "r"(a[0]),"r"(a[1]),"r"(a[2]),"r"(a[3]), "l"(db));
}
__device__ __forceinline__ void rs160_1(float* d, const uint32_t* a, uint64_t db){
  asm volatile("{ .reg .pred p; setp.ne.b32 p, 1, 0; wgmma.mma_async.sync.aligned.m64n160k16.f32.bf16.bf16 {%0, %1, %2, %3, %4, %5, %6, %7, %8, %9, %10, %11, %12, %13, %14, %15, %16, %17, %18, %19, %20, %21, %22, %23, %24, %25, %26, %27, %28, %29, %30, %31, %32, %33, %34, %35, %36, %37, %38, %39, %40, %41, %42, %43, %44, %45, %46, %47, %48, %49, %50, %51, %52, %53, %54, %55, %56, %57, %58, %59, %60, %61, %62, %63, %64, %65, %66, %67, %68, %69, %70, %71, %72, %73, %74, %75, %76, %77, %78, %79}, {%80,%81,%82,%83}, %84, p, 1, 1, 1; }"
   : "+f"(d[0]), "+f"(d[1]), "+f"(d[2]), "+f"(d[3]), "+f"(d[4]), "+f"(d[5]), "+f"(d[6]), "+f"(d[7]), "+f"(d[8]), "+f"(d[9]), "+f"(d[10]), "+f"(d[11]), "+f"(d[12]), "+f"(d[13]), "+f"(d[14]), "+f"(d[15]), "+f"(d[16]), "+f"(d[17]), "+f"(d[18]), "+f"(d[19]), "+f"(d[20]), "+f"(d[21]), "+f"(d[22]), "+f"(d[23]), "+f"(d[24]), "+f"(d[25]), "+f"(d[26]), "+f"(d[27]), "+f"(d[28]), "+f"(d[29]), "+f"(d[30]), "+f"(d[31]), "+f"(d[32]), "+f"(d[33]), "+f"(d[34]), "+f"(d[35]), "+f"(d[36]), "+f"(d[37]), "+f"(d[38]), "+f"(d[39]), "+f"(d[40]), "+f"(d[41]), "+f"(d[42]), "+f"(d[43]), "+f"(d[44]), "+f"(d[45]), "+f"(d[46]), "+f"(d[47]), "+f"(d[48]), "+f"(d[49]), "+f"(d[50]), "+f"(d[51]), "+f"(d[52]), "+f"(d[53]), "+f"(d[54]), "+f"(d[55]), "+f"(d[56]), "+f"(d[57]), "+f"(d[58]), "+f"(d[59]), "+f"(d[60]), "+f"(d[61]), "+f"(d[62]), "+f"(d[63]), "+f"(d[64]), "+f"(d[65]), "+f"(d[66]), "+f"(d[67]), "+f"(d[68]), "+f"(d[69]), "+f"(d[70]), "+f"(d[71]), "+f"(d[72]), "+f"(d[73]), "+f"(d[74]), "+f"(d[75]), "+f"(d[76]), "+f"(d[77]), "+f"(d[78]), "+f"(d[79]) : "r"(a[0]),"r"(a[1]),"r"(a[2]),"r"(a[3]), "l"(db));
}
__device__ __forceinline__ void rs64_0(float* d, const uint32_t* a, uint64_t db){
  asm volatile("{ .reg .pred p; setp.ne.b32 p, 0, 0; wgmma.mma_async.sync.aligned.m64n64k16.f32.bf16.bf16 {%0, %1, %2, %3, %4, %5, %6, %7, %8, %9, %10, %11, %12, %13, %14, %15, %16, %17, %18, %19, %20, %21, %22, %23, %24, %25, %26, %27, %28, %29, %30, %31}, {%32,%33,%34,%35}, %36, p, 1, 1, 1; }"
   : "=f"(d[0]), "=f"(d[1]), "=f"(d[2]), "=f"(d[3]), "=f"(d[4]), "=f"(d[5]), "=f"(d[6]), "=f"(d[7]), "=f"(d[8]), "=f"(d[9]), "=f"(d[10]), "=f"(d[11]), "=f"(d[12]), "=f"(d[13]), "=f"(d[14]), "=f"(d[15]), "=f"(d[16]), "=f"(d[17]), "=f"(d[18]), "=f"(d[19]), "=f"(d[20]), "=f"(d[21]), "=f"(d[22]), "=f"(d[23]), "=f"(d[24]), "=f"(d[25]), "=f"(d[26]), "=f"(d[27]), "=f"(d[28]), "=f"(d[29]), "=f"(d[30]), "=f"(d[31]) : "r"(a[0]),"r"(a[1]),"r"(a[2]),"r"(a[3]), "l"(db));
}
__device__ __forceinline__ void rs64_1(float* d, const uint32_t* a, uint64_t db){
  asm volatile("{ .reg .pred p; setp.ne.b32 p, 1, 0; wgmma.mma_async.sync.aligned.m64n64k16.f32.bf16.bf16 {%0, %1, %2, %3, %4, %5, %6, %7, %8, %9, %10, %11, %12, %13, %14, %15, %16, %17, %18, %19, %20, %21, %22, %23, %24, %25, %26, %27, %28, %29, %30, %31}, {%32,%33,%34,%35}, %36, p, 1, 1, 1; }"
   : "+f"(d[0]), "+f"(d[1]), "+f"(d[2]), "+f"(d[3]), "+f"(d[4]), "+f"(d[5]), "+f"(d[6]), "+f"(d[7]), "+f"(d[8]), "+f"(d[9]), "+f"(d[10]), "+f"(d[11]), "+f"(d[12]), "+f"(d[13]), "+f"(d[14]), "+f"(d[15]), "+f"(d[16]), "+f"(d[17]), "+f"(d[18]), "+f"(d[19]), "+f"(d[20]), "+f"(d[21]), "+f"(d[22]), "+f"(d[23]), "+f"(d[24]), "+f"(d[25]), "+f"(d[26]), "+f"(d[27]), "+f"(d[28]), "+f"(d[29]), "+f"(d[30]), "+f"(d[31]) : "r"(a[0]),"r"(a[1]),"r"(a[2]),"r"(a[3]), "l"(db));
}
__device__ __forceinline__ void rs56_0(float* d, const uint32_t* a, uint64_t db){
  asm volatile("{ .reg .pred p; setp.ne.b32 p, 0, 0; wgmma.mma_async.sync.aligned.m64n56k16.f32.bf16.bf16 {%0, %1, %2, %3, %4, %5, %6, %7, %8, %9, %10, %11, %12, %13, %14, %15, %16, %17, %18, %19, %20, %21, %22, %23, %24, %25, %26, %27}, {%28,%29,%30,%31}, %32, p, 1, 1, 1; }"
   : "=f"(d[0]), "=f"(d[1]), "=f"(d[2]), "=f"(d[3]), "=f"(d[4]), "=f"(d[5]), "=f"(d[6]), "=f"(d[7]), "=f"(d[8]), "=f"(d[9]), "=f"(d[10]), "=f"(d[11]), "=f"(d[12]), "=f"(d[13]), "=f"(d[14]), "=f"(d[15]), "=f"(d[16]), "=f"(d[17]), "=f"(d[18]), "=f"(d[19]), "=f"(d[20]), "=f"(d[21]), "=f"(d[22]), "=f"(d[23]), "=f"(d[24]), "=f"(d[25]), "=f"(d[26]), "=f"(d[27]) : "r"(a[0]),"r"(a[1]),"r"(a[2]),"r"(a[3]), "l"(db));
}
__device__ __forceinline__ void rs56_1(float* d, const uint32_t* a, uint64_t db){
  asm volatile("{ .reg .pred p; setp.ne.b32 p, 1, 0; wgmma.mma_async.sync.aligned.m64n56k16.f32.bf16.bf16 {%0, %1, %2, %3, %4, %5, %6, %7, %8, %9, %10, %11, %12, %13, %14, %15, %16, %17, %18, %19, %20, %21, %22, %23, %24, %25, %26, %27}, {%28,%29,%30,%31}, %32, p, 1, 1, 1; }"
   : "+f"(d[0]), "+f"(d[1]), "+f"(d[2]), "+f"(d[3]), "+f"(d[4]), "+f"(d[5]), "+f"(d[6]), "+f"(d[7]), "+f"(d[8]), "+f"(d[9]), "+f"(d[10]), "+f"(d[11]), "+f"(d[12]), "+f"(d[13]), "+f"(d[14]), "+f"(d[15]), "+f"(d[16]), "+f"(d[17]), "+f"(d[18]), "+f"(d[19]), "+f"(d[20]), "+f"(d[21]), "+f"(d[22]), "+f"(d[23]), "+f"(d[24]), "+f"(d[25]), "+f"(d[26]), "+f"(d[27]) : "r"(a[0]),"r"(a[1]),"r"(a[2]),"r"(a[3]), "l"(db));
}
__device__ __forceinline__ void rs32_0(float* d, const uint32_t* a, uint64_t db){
  asm volatile("{ .reg .pred p; setp.ne.b32 p, 0, 0; wgmma.mma_async.sync.aligned.m64n32k16.f32.bf16.bf16 {%0, %1, %2, %3, %4, %5, %6, %7, %8, %9, %10, %11, %12, %13, %14, %15}, {%16,%17,%18,%19}, %20, p, 1, 1, 1; }"
   : "=f"(d[0]), "=f"(d[1]), "=f"(d[2]), "=f"(d[3]), "=f"(d[4]), "=f"(d[5]), "=f"(d[6]), "=f"(d[7]), "=f"(d[8]), "=f"(d[9]), "=f"(d[10]), "=f"(d[11]), "=f"(d[12]), "=f"(d[13]), "=f"(d[14]), "=f"(d[15]) : "r"(a[0]),"r"(a[1]),"r"(a[2]),"r"(a[3]), "l"(db));
}
__device__ __forceinline__ void rs32_1(float* d, const uint32_t* a, uint64_t db){
  asm volatile("{ .reg .pred p; setp.ne.b32 p, 1, 0; wgmma.mma_async.sync.aligned.m64n32k16.f32.bf16.bf16 {%0, %1, %2, %3, %4, %5, %6, %7, %8, %9, %10, %11, %12, %13, %14, %15}, {%16,%17,%18,%19}, %20, p, 1, 1, 1; }"
   : "+f"(d[0]), "+f"(d[1]), "+f"(d[2]), "+f"(d[3]), "+f"(d[4]), "+f"(d[5]), "+f"(d[6]), "+f"(d[7]), "+f"(d[8]), "+f"(d[9]), "+f"(d[10]), "+f"(d[11]), "+f"(d[12]), "+f"(d[13]), "+f"(d[14]), "+f"(d[15]) : "r"(a[0]),"r"(a[1]),"r"(a[2]),"r"(a[3]), "l"(db));
}
__device__ __forceinline__ void ss64_0(float* d, uint64_t da, uint64_t db){
  asm volatile("{ .reg .pred p; setp.ne.b32 p, 0, 0; wgmma.mma_async.sync.aligned.m64n64k16.f32.bf16.bf16 {%0, %1, %2, %3, %4, %5, %6, %7, %8, %9, %10, %11, %12, %13, %14, %15, %16, %17, %18, %19, %20, %21, %22, %23, %24, %25, %26, %27, %28, %29, %30, %31}, %32, %33, p, 1, 1, 1, 1; }"
   : "=f"(d[0]), "=f"(d[1]), "=f"(d[2]), "=f"(d[3]), "=f"(d[4]), "=f"(d[5]), "=f"(d[6]), "=f"(d[7]), "=f"(d[8]), "=f"(d[9]), "=f"(d[10]), "=f"(d[11]), "=f"(d[12]), "=f"(d[13]), "=f"(d[14]), "=f"(d[15]), "=f"(d[16]), "=f"(d[17]), "=f"(d[18]), "=f"(d[19]), "=f"(d[20]), "=f"(d[21]), "=f"(d[22]), "=f"(d[23]), "=f"(d[24]), "=f"(d[25]), "=f"(d[26]), "=f"(d[27]), "=f"(d[28]), "=f"(d[29]), "=f"(d[30]), "=f"(d[31]) : "l"(da), "l"(db));
}
__device__ __forceinline__ void ss64_1(float* d, uint64_t da, uint64_t db){
  asm volatile("{ .reg .pred p; setp.ne.b32 p, 1, 0; wgmma.mma_async.sync.aligned.m64n64k16.f32.bf16.bf16 {%0, %1, %2, %3, %4, %5, %6, %7, %8, %9, %10, %11, %12, %13, %14, %15, %16, %17, %18, %19, %20, %21, %22, %23, %24, %25, %26, %27, %28, %29, %30, %31}, %32, %33, p, 1, 1, 1, 1; }"
   : "+f"(d[0]), "+f"(d[1]), "+f"(d[2]), "+f"(d[3]), "+f"(d[4]), "+f"(d[5]), "+f"(d[6]), "+f"(d[7]), "+f"(d[8]), "+f"(d[9]), "+f"(d[10]), "+f"(d[11]), "+f"(d[12]), "+f"(d[13]), "+f"(d[14]), "+f"(d[15]), "+f"(d[16]), "+f"(d[17]), "+f"(d[18]), "+f"(d[19]), "+f"(d[20]), "+f"(d[21]), "+f"(d[22]), "+f"(d[23]), "+f"(d[24]), "+f"(d[25]), "+f"(d[26]), "+f"(d[27]), "+f"(d[28]), "+f"(d[29]), "+f"(d[30]), "+f"(d[31]) : "l"(da), "l"(db));
}
__device__ __forceinline__ void rs64_z(float* d, const uint32_t* a, uint64_t db){
  asm volatile("{ .reg .pred p; setp.ne.b32 p, 0, 0; wgmma.mma_async.sync.aligned.m64n64k16.f32.bf16.bf16 {%0, %1, %2, %3, %4, %5, %6, %7, %8, %9, %10, %11, %12, %13, %14, %15, %16, %17, %18, %19, %20, %21, %22, %23, %24, %25, %26, %27, %28, %29, %30, %31}, {%32,%33,%34,%35}, %36, p, 1, 1, 1; }"
   : "+f"(d[0]), "+f"(d[1]), "+f"(d[2]), "+f"(d[3]), "+f"(d[4]), "+f"(d[5]), "+f"(d[6]), "+f"(d[7]), "+f"(d[8]), "+f"(d[9]), "+f"(d[10]), "+f"(d[11]), "+f"(d[12]), "+f"(d[13]), "+f"(d[14]), "+f"(d[15]), "+f"(d[16]), "+f"(d[17]), "+f"(d[18]), "+f"(d[19]), "+f"(d[20]), "+f"(d[21]), "+f"(d[22]), "+f"(d[23]), "+f"(d[24]), "+f"(d[25]), "+f"(d[26]), "+f"(d[27]), "+f"(d[28]), "+f"(d[29]), "+f"(d[30]), "+f"(d[31]) : "r"(a[0]),"r"(a[1]),"r"(a[2]),"r"(a[3]), "l"(db));
}
__device__ __forceinline__ void rs32_z(float* d, const uint32_t* a, uint64_t db){
  asm volatile("{ .reg .pred p; setp.ne.b32 p, 0, 0; wgmma.mma_async.sync.aligned.m64n32k16.f32.bf16.bf16 {%0, %1, %2, %3, %4, %5, %6, %7, %8, %9, %10, %11, %12, %13, %14, %15}, {%16,%17,%18,%19}, %20, p, 1, 1, 1; }"
   : "+f"(d[0]), "+f"(d[1]), "+f"(d[2]), "+f"(d[3]), "+f"(d[4]), "+f"(d[5]), "+f"(d[6]), "+f"(d[7]), "+f"(d[8]), "+f"(d[9]), "+f"(d[10]), "+f"(d[11]), "+f"(d[12]), "+f"(d[13]), "+f"(d[14]), "+f"(d[15]) : "r"(a[0]),"r"(a[1]),"r"(a[2]),"r"(a[3]), "l"(db));
}
__device__ __forceinline__ void sk64_0(float* d, uint64_t da, uint64_t db){
  asm volatile("{ .reg .pred p; setp.ne.b32 p, 0, 0; wgmma.mma_async.sync.aligned.m64n64k16.f32.bf16.bf16 {%0, %1, %2, %3, %4, %5, %6, %7, %8, %9, %10, %11, %12, %13, %14, %15, %16, %17, %18, %19, %20, %21, %22, %23, %24, %25, %26, %27, %28, %29, %30, %31}, %32, %33, p, 1, 1, 0, 1; }"
   : "=f"(d[0]), "=f"(d[1]), "=f"(d[2]), "=f"(d[3]), "=f"(d[4]), "=f"(d[5]), "=f"(d[6]), "=f"(d[7]), "=f"(d[8]), "=f"(d[9]), "=f"(d[10]), "=f"(d[11]), "=f"(d[12]), "=f"(d[13]), "=f"(d[14]), "=f"(d[15]), "=f"(d[16]), "=f"(d[17]), "=f"(d[18]), "=f"(d[19]), "=f"(d[20]), "=f"(d[21]), "=f"(d[22]), "=f"(d[23]), "=f"(d[24]), "=f"(d[25]), "=f"(d[26]), "=f"(d[27]), "=f"(d[28]), "=f"(d[29]), "=f"(d[30]), "=f"(d[31]) : "l"(da), "l"(db));
}
__device__ __forceinline__ void sk64_1(float* d, uint64_t da, uint64_t db){
  asm volatile("{ .reg .pred p; setp.ne.b32 p, 1, 0; wgmma.mma_async.sync.aligned.m64n64k16.f32.bf16.bf16 {%0, %1, %2, %3, %4, %5, %6, %7, %8, %9, %10, %11, %12, %13, %14, %15, %16, %17, %18, %19, %20, %21, %22, %23, %24, %25, %26, %27, %28, %29, %30, %31}, %32, %33, p, 1, 1, 0, 1; }"
   : "+f"(d[0]), "+f"(d[1]), "+f"(d[2]), "+f"(d[3]), "+f"(d[4]), "+f"(d[5]), "+f"(d[6]), "+f"(d[7]), "+f"(d[8]), "+f"(d[9]), "+f"(d[10]), "+f"(d[11]), "+f"(d[12]), "+f"(d[13]), "+f"(d[14]), "+f"(d[15]), "+f"(d[16]), "+f"(d[17]), "+f"(d[18]), "+f"(d[19]), "+f"(d[20]), "+f"(d[21]), "+f"(d[22]), "+f"(d[23]), "+f"(d[24]), "+f"(d[25]), "+f"(d[26]), "+f"(d[27]), "+f"(d[28]), "+f"(d[29]), "+f"(d[30]), "+f"(d[31]) : "l"(da), "l"(db));
}
__device__ __forceinline__ void sk64_z(float* d, uint64_t da, uint64_t db){
  asm volatile("{ .reg .pred p; setp.ne.b32 p, 0, 0; wgmma.mma_async.sync.aligned.m64n64k16.f32.bf16.bf16 {%0, %1, %2, %3, %4, %5, %6, %7, %8, %9, %10, %11, %12, %13, %14, %15, %16, %17, %18, %19, %20, %21, %22, %23, %24, %25, %26, %27, %28, %29, %30, %31}, %32, %33, p, 1, 1, 0, 1; }"
   : "+f"(d[0]), "+f"(d[1]), "+f"(d[2]), "+f"(d[3]), "+f"(d[4]), "+f"(d[5]), "+f"(d[6]), "+f"(d[7]), "+f"(d[8]), "+f"(d[9]), "+f"(d[10]), "+f"(d[11]), "+f"(d[12]), "+f"(d[13]), "+f"(d[14]), "+f"(d[15]), "+f"(d[16]), "+f"(d[17]), "+f"(d[18]), "+f"(d[19]), "+f"(d[20]), "+f"(d[21]), "+f"(d[22]), "+f"(d[23]), "+f"(d[24]), "+f"(d[25]), "+f"(d[26]), "+f"(d[27]), "+f"(d[28]), "+f"(d[29]), "+f"(d[30]), "+f"(d[31]) : "l"(da), "l"(db));
}
__device__ __forceinline__ void sk32_0(float* d, uint64_t da, uint64_t db){
  asm volatile("{ .reg .pred p; setp.ne.b32 p, 0, 0; wgmma.mma_async.sync.aligned.m64n32k16.f32.bf16.bf16 {%0, %1, %2, %3, %4, %5, %6, %7, %8, %9, %10, %11, %12, %13, %14, %15}, %16, %17, p, 1, 1, 0, 1; }"
   : "=f"(d[0]), "=f"(d[1]), "=f"(d[2]), "=f"(d[3]), "=f"(d[4]), "=f"(d[5]), "=f"(d[6]), "=f"(d[7]), "=f"(d[8]), "=f"(d[9]), "=f"(d[10]), "=f"(d[11]), "=f"(d[12]), "=f"(d[13]), "=f"(d[14]), "=f"(d[15]) : "l"(da), "l"(db));
}
__device__ __forceinline__ void sk32_1(float* d, uint64_t da, uint64_t db){
  asm volatile("{ .reg .pred p; setp.ne.b32 p, 1, 0; wgmma.mma_async.sync.aligned.m64n32k16.f32.bf16.bf16 {%0, %1, %2, %3, %4, %5, %6, %7, %8, %9, %10, %11, %12, %13, %14, %15}, %16, %17, p, 1, 1, 0, 1; }"
   : "+f"(d[0]), "+f"(d[1]), "+f"(d[2]), "+f"(d[3]), "+f"(d[4]), "+f"(d[5]), "+f"(d[6]), "+f"(d[7]), "+f"(d[8]), "+f"(d[9]), "+f"(d[10]), "+f"(d[11]), "+f"(d[12]), "+f"(d[13]), "+f"(d[14]), "+f"(d[15]) : "l"(da), "l"(db));
}
__device__ __forceinline__ void sk32_z(float* d, uint64_t da, uint64_t db){
  asm volatile("{ .reg .pred p; setp.ne.b32 p, 0, 0; wgmma.mma_async.sync.aligned.m64n32k16.f32.bf16.bf16 {%0, %1, %2, %3, %4, %5, %6, %7, %8, %9, %10, %11, %12, %13, %14, %15}, %16, %17, p, 1, 1, 0, 1; }"
   : "+f"(d[0]), "+f"(d[1]), "+f"(d[2]), "+f"(d[3]), "+f"(d[4]), "+f"(d[5]), "+f"(d[6]), "+f"(d[7]), "+f"(d[8]), "+f"(d[9]), "+f"(d[10]), "+f"(d[11]), "+f"(d[12]), "+f"(d[13]), "+f"(d[14]), "+f"(d[15]) : "l"(da), "l"(db));
}
template<int N> __device__ __forceinline__ void ssz(float* d, uint64_t da, uint64_t db){
  if constexpr (N==64) sk64_z(d,da,db); else sk32_z(d,da,db);
}
template<int N> __device__ __forceinline__ void rsz(float* d, const uint32_t* a, uint64_t db){
  if constexpr (N==64) rs64_z(d,a,db); else rs32_z(d,a,db);
}
template<int N> __device__ __forceinline__ void ssk(float* d, uint64_t da, uint64_t db, bool first){
  if constexpr (N==64) { if(first) sk64_0(d,da,db); else sk64_1(d,da,db); } else { if(first) sk32_0(d,da,db); else sk32_1(d,da,db); }
}
template<int N> __device__ __forceinline__ void rs(float* d, const uint32_t* a, uint64_t db, bool first){
  if constexpr (N==120) { if(first) rs120_0(d,a,db); else rs120_1(d,a,db); }
  if constexpr (N==128) { if(first) rs128_0(d,a,db); else rs128_1(d,a,db); }
  if constexpr (N==160) { if(first) rs160_0(d,a,db); else rs160_1(d,a,db); }
  if constexpr (N==64) { if(first) rs64_0(d,a,db); else rs64_1(d,a,db); }
  if constexpr (N==56) { if(first) rs56_0(d,a,db); else rs56_1(d,a,db); }
  if constexpr (N==32) { if(first) rs32_0(d,a,db); else rs32_1(d,a,db); }
}

constexpr float LOG2E = 1.4426950408889634f;
#define EPI_TS(x) x
#define TS7(i)
#define TS5(i)
#define TS4(i)
#define BAR(i) (sb + MISC + 8u * (uint32_t)(i))
#define BBARI(k) asm volatile("{ .reg .pred p; setp.ne.u32 p, %0, %1; @p bra B_L; trap; B_L: }" ::"r"(sb), "n"(k) : "memory")
#define BBAR() asm volatile("{ .reg .pred p; setp.ne.u32 p, %0, %1; @p bra B_L; trap; B_L: }" ::"r"(sb), "n"(__LINE__ * 2 + 1) : "memory")

__host__ __device__ constexpr int unitB(int g) { return g == 0 ? 0 : g == 1 ? 3 : g == 2 ? 8 : 14 + 3 * (g - 3); }
__host__ __device__ constexpr int unitC(int g) { return g == 0 ? 11 : g == 1 ? 5 : g == 2 ? 8 : 14 + 3 * (g - 3); }
__host__ __device__ constexpr int unitD(int g) { return g == 0 ? 11 : g == 1 ? 8 : g == 6 ? 3 : 14 + 3 * (g - 2); }
#define AHOLD 4
#define B01DEP XC0
__host__ __device__ constexpr int depB(int g) { return g < 2 ? B01DEP : g == 2 ? XC1 : g == 3 ? EA1 : g == 4 ? EA2 : g == 5 ? EA4 : EA5; }
__host__ __device__ constexpr int depC(int g) { return g == 0 ? KVFREE : EB1 + g - 1; }
__host__ __device__ constexpr int depD(int g) { return g == 0 ? EC0 : g < 6 ? EC0 + g + 1 : LHA; }
__host__ __device__ constexpr int eid(int P, int g) {
  return P == 0 ? (g == 1 ? EA1 : g == 2 ? EA2 : g >= 4 ? EA4 + g - 4 : -1)
       : P == 1 ? (g >= 1 ? EB1 + g - 1 : -1)
       : P == 2 ? EC0 + g
                : (g == 1 ? ED1 : g == 2 ? ED2 : g == 3 ? ED3 : g >= 4 ? ED4 + g - 4 : -1);
}
template <int P> __host__ __device__ constexpr int unitP(int g) { return P == 0 ? 14 + 2 * g : P == 1 ? unitB(g) : P == 2 ? unitC(g) : unitD(g); }
template <typename Fn> __host__ __device__ constexpr uint64_t packtab(Fn f) { uint64_t t = 0; for (int g = 0; g < 7; g++) t |= (uint64_t)f(g) << (8 * g); return t; }

template <int P, int N, typename Fn, typename Fp>
__device__ __forceinline__ void pass1(float* acc, const uint32_t* xf, uint32_t sb, uint32_t pb, bool lane0, uint64_t sh, Fn shadow, Fp post) {
#pragma unroll
  for (int g = 0; g < 7; g++) {
    mbar_wait(BAR(FA + 7 * P + g));
    wg_fence();
#pragma unroll
    for (int kk = 0; kk < 4; kk++) {
      if (P == 1) {
        rs<128>(acc, xf + 16 * g + 4 * kk, desc(unitP<P>(g) * U + kk * 2048, U), g == 0 && kk == 0);
        rs<56>(acc + 64, xf + 16 * g + 4 * kk, desc((unitP<P>(g) + 2) * U + kk * 2048, U) + sh, g == 0 && kk == 0);
      } else {
        rs<N>(acc, xf + 16 * g + 4 * kk, desc(unitP<P>(g) * U + kk * 2048, U) + (P == 0 ? sh : 0), g == 0 && kk == 0);
      }
    }
    wg_commit();
    shadow(g);
    if (g > 0) {
      wg_wait<1>();
      if (lane0) {
        if (eid(P, g - 1) >= 0) mbar_arrive(BAR(eid(P, g - 1)));
        if ((P == 1 || P == 2) && g == 2) mbar_arrive_remote(pb + MISC + 8u * (PF + P - 1));
        if (P == 3 && g == 1) mbar_arrive_remote(pb + MISC + 8u * (PF + 2));
      }
      post(g);
    }
  }
  wg_wait<0>();
  if (lane0) mbar_arrive(BAR(eid(P, 6)));
  pin<N / 2>(acc);
}

template <int ID> __device__ __forceinline__ void hfrag64(uint32_t* h, float* acc, const float* rs_, uint32_t sb, int wg) {
  const float hr[2] = {0.5f * rs_[0], 0.5f * rs_[1]};
#pragma unroll
  for (int i = 0; i < 32; i++) {
    acc[32 + i] *= acc[i];
    acc[i] *= hr[(i >> 1) & 1];
    if (i < 16) acc[i] = tanh_(acc[i]);
  }
  pin<64>(acc);
  BBARI(ID * 4 + 1);
  EPI_TS(if (ID == 1) CTS(21));
  const float c[2] = {hr[0] * hr[0], hr[1] * hr[1]};
#pragma unroll
  for (int i = 16; i < 32; i++) acc[i] = tanh_(acc[i]);
#pragma unroll
  for (int m = 0; m < 8; m++) h[m] = pack2(acc[32 + 2 * m] * fmaf(acc[2 * m], c[m & 1], c[m & 1]), acc[33 + 2 * m] * fmaf(acc[2 * m + 1], c[m & 1], c[m & 1]));
  pin<16>(acc + 16);
  pinr<8>(h);
  BBARI(ID * 4 + 3);
  EPI_TS(if (ID == 1) CTS(22));
#pragma unroll
  for (int m = 8; m < 16; m++) h[m] = pack2(acc[32 + 2 * m] * fmaf(acc[2 * m], c[m & 1], c[m & 1]), acc[33 + 2 * m] * fmaf(acc[2 * m + 1], c[m & 1], c[m & 1]));
}
__device__ __forceinline__ void phi1(float* e, float* a, const float* rs_) {
  const float rl[2] = {rs_[0] * (0.5f * LOG2E), rs_[1] * (0.5f * LOG2E)};
#pragma unroll
  for (int i = 0; i < 28; i++) {
    const float u = a[i] * rl[(i >> 1) & 1];
    e[i] = ex2(u - fabsf(u));
    a[i] = fmaf(u + fabsf(u), 0.6931471805599453f, 1e-6f);
  }
  pin<28>(e);
  pin<28>(a);
}

template <int NP> __device__ __forceinline__ void send_ll(uint4* dst, const float* a) {
#pragma unroll
  for (int q = 0; q < NP; q++)
    asm volatile("{ .reg .b128 t; .reg .b64 lo, hi; mov.b64 lo, {%1,%2}; mov.b64 hi, {%3,%4}; mov.b128 t, {lo,hi}; st.relaxed.gpu.global.b128 [%0], t; }" ::"l"(dst + q * 32),
                 "r"(pack2(a[8 * q], a[8 * q + 1]) | 1u), "r"(pack2(a[8 * q + 2], a[8 * q + 3])), "r"(pack2(a[8 * q + 4], a[8 * q + 5])), "r"(pack2(a[8 * q + 6], a[8 * q + 7])) : "memory");
}
__device__ __forceinline__ void stg4(uint4* dst, const uint32_t* w) {
  asm volatile("{ .reg .b128 t; .reg .b64 lo, hi; mov.b64 lo, {%1,%2}; mov.b64 hi, {%3,%4}; mov.b128 t, {lo,hi}; st.relaxed.gpu.global.b128 [%0], t; }" ::"l"(dst),
               "r"(w[0]), "r"(w[1]), "r"(w[2]), "r"(w[3]) : "memory");
}
#define LL_LD(g, p, o, a, b, c, d) g "ld.relaxed.gpu.global.v4.b32 {%" #a ",%" #b ",%" #c ",%" #d "}, [%" #p "+" #o "];\n"
#define LL_LD4(g) LL_LD(g, 16, 0, 0, 1, 2, 3) LL_LD(g, 16, 512, 4, 5, 6, 7) LL_LD(g, 17, 0, 8, 9, 10, 11) LL_LD(g, 17, 512, 12, 13, 14, 15)
#define LL_OPS(c) c(v[0]), c(v[1]), c(v[2]), c(v[3]), c(v[4]), c(v[5]), c(v[6]), c(v[7]), c(v[8]), c(v[9]), c(v[10]), c(v[11]), c(v[12]), c(v[13]), c(v[14]), c(v[15])
__device__ __forceinline__ void ld_ll4(uint32_t* v, const uint4* p, const uint4* p2) {
  asm volatile(LL_LD4("") : LL_OPS("=r") : "l"(p), "l"(p2) : "memory");
}
__device__ __forceinline__ void ref_ll(uint32_t* v, const uint4* p, const uint4* p2) {
  asm volatile("{ .reg .pred p; .reg .b32 t;\n"
               "lop3.b32 t, %0, %4, %8, 0x80; lop3.b32 t, t, %12, 1, 0x80; setp.ne.u32 p, t, 0; vote.sync.all.pred p, p, 0xffffffff; @p bra R_D;\n"
               LL_LD4("") "R_D: }" : LL_OPS("+r") : "l"(p), "l"(p2) : "memory");
}
#define LL_LDX(o, a) LL_LD("", 48, o, a + 0, a + 1, a + 2, a + 3)
#define LL_CK(q, a, b, c, d) "lop3.b32 t, %" #a ", %" #b ", %" #c ", 0x80; lop3.b32 t, t, %" #d ", 1, 0x80; setp.ne.u32 " #q ", t, 0; vote.sync.all.pred " #q ", " #q ", 0xffffffff;\n"
#define LL_O16(v) "+r"(v[0]), "+r"(v[1]), "+r"(v[2]), "+r"(v[3]), "+r"(v[4]), "+r"(v[5]), "+r"(v[6]), "+r"(v[7]), "+r"(v[8]), "+r"(v[9]), "+r"(v[10]), "+r"(v[11]), "+r"(v[12]), "+r"(v[13]), "+r"(v[14]), "+r"(v[15])
__device__ __forceinline__ void chk_ll(uint32_t (*v)[16], const uint4* p, const uint4* p2) {
  asm volatile(
      "{ .reg .pred p, q; .reg .b32 t, u, n;\n"
      "mov.u32 n, 0;\n"
      "R_L: lop3.b32 t, %0, %4, %8, 0x80; lop3.b32 u, %12, %16, %20, 0x80; lop3.b32 t, t, %24, %28, 0x80; lop3.b32 u, u, %32, %36, 0x80; lop3.b32 t, t, %40, %44, 0x80; lop3.b32 t, t, u, 1, 0x80;\n"
      "setp.ne.u32 p, t, 0; vote.sync.all.pred p, p, 0xffffffff; setp.ge.or.u32 p, n, 2097152, p; @p bra R_D;\n"
      LL_CK(q, 0, 4, 8, 12) "@q bra R_1;\n"
      LL_LD("", 48, 0, 0, 1, 2, 3) LL_LD("", 48, 512, 4, 5, 6, 7) LL_LD("", 49, 0, 8, 9, 10, 11) LL_LD("", 49, 512, 12, 13, 14, 15)
      "R_1: " LL_CK(q, 16, 20, 24, 28) "@q bra R_2;\n"
      LL_LD("", 48, 16384, 16, 17, 18, 19) LL_LD("", 48, 16896, 20, 21, 22, 23) LL_LD("", 49, 16384, 24, 25, 26, 27) LL_LD("", 49, 16896, 28, 29, 30, 31)
      "R_2: " LL_CK(q, 32, 36, 40, 44) "@q bra R_3;\n"
      LL_LD("", 48, 32768, 32, 33, 34, 35) LL_LD("", 48, 33280, 36, 37, 38, 39) LL_LD("", 49, 32768, 40, 41, 42, 43) LL_LD("", 49, 33280, 44, 45, 46, 47)
      "R_3: add.u32 n, n, 1; bra R_L;\n"
      "R_D:\n"
      "}"
      : LL_O16(v[0]), LL_O16(v[1]), LL_O16(v[2])
      : "l"(p), "l"(p2)
      : "memory");
}

__device__ __forceinline__ void load_x(const __nv_bfloat16* x, uint32_t sb, int r, int warp, int lane) {
  const int l8 = lane >> 3, c = lane & 7;
  const char* src = reinterpret_cast<const char*>(x + (size_t)(r * 128 + warp * 16 + l8) * DM + c * 8);
  const uint32_t dst = sb + (uint32_t)((warp >> 2) * (7 * U) + ((warp & 3) * 16 + l8) * 128 + ((c ^ l8) << 4));
#pragma unroll
  for (int kb = 0; kb < 7; kb++) {
#pragma unroll
    for (int q = 0; q < 4; q++)
      asm volatile("cp.async.cg.shared.global [%0], [%1], 16;" ::"r"((dst ^ ((q & 1) << 6)) + kb * U + q * 512), "l"(src + q * 4 * DM * 2 + kb * 128) : "memory");
    asm volatile("cp.async.commit_group;" ::: "memory");
  }
}
template <int N> __device__ __forceinline__ void cp_wait() { asm volatile("cp.async.wait_group %0;" ::"n"(N) : "memory"); }

template <int H> __device__ __forceinline__ void w2_tiles(const Maps& M, uint32_t sb, int j) {
  const int kq = j >> 1, n = j & 1;
  const int io = kq == 3 - 3 * n ? 2 : kq - n;
  const int cA = 256 * n + 64 * (io == 2 ? 0 : io + 1), cB = 256 * n + 64 * (io == 0 ? 2 : io - 1);
#pragma unroll 1
  for (int i = 0; i < 4; i++) {
    const uint32_t ut = H == 0 ? (i == 0 ? 0x12103634u : i == 1 ? 0x27252422u : i == 2 ? 0x0C040200u : 0x12103634u)
                               : (i == 0 ? 0x20141E1Cu : i == 1 ? 0x2D2B2A28u : i == 2 ? 0x0D32302Eu : 0x14201E1Cu);
    const uint32_t fb = BAR(FT + (H == 0 ? (0x6520 >> (4 * i)) & 15 : (0x7431 >> (4 * i)) & 15));
    const uint32_t dt = H == 0 ? ED1 | (ED3 << 8) | (LH1 << 16) | ((ET + 0) << 24) : ED2 | (ED4 << 8) | (ED5 << 16) | ((ET + 1) << 24);
    const uint32_t dep = BAR((dt >> (8 * i)) & 255);
    const int pe = i < 2 ? H : i & 1, nn = n ^ pe, fb0 = (j ^ pe) * 224;
    const int r0 = fb0 + 32 * nn, r1 = fb0 + 192 * (1 - nn);
    const CUtensorMap* m = i >= 2 && H == 0 ? &M.w2c : &M.w2a;
    const int c2 = H == 0 ? 192 + 32 * n : 256 * n + 64 * io;
    if (H == 1 || i) mbar_wait(dep);
    tma2d(sb + (ut & 255) * 4096, m, i < 2 ? cA : c2, i == 1 ? r0 + 128 : r0, fb);
    tma2d(sb + ((ut >> 8) & 255) * 4096, i == 1 ? m + 1 : m, i == 0 ? cB : i == 1 ? cA : c2, i == 0 ? r0 : i == 1 ? r1 : r0 + 64, fb);
    if (H == 0 && !i) mbar_wait(dep);
    tma2d(sb + ((ut >> 16) & 255) * 4096, m, i == 0 ? cA : i == 1 ? cB : c2, i == 0 ? r0 + 64 : r0 + 128, fb);
    tma2d(sb + (ut >> 24) * 4096, i == 0 ? m : m + 1, i < 2 ? cB : c2, i == 0 ? r0 + 64 : r1, fb);
    TS(2, 10 + 2 * i + H);
  }
}

#define LANE() const int ln = laneid(), g8 = ln >> 2, t4 = ln & 3; (void)g8; (void)t4
__device__ __forceinline__ void tail(const Maps& M, __nv_bfloat16* out, uint32_t* hf, float* acc, const uint32_t* sg, float* rs_, uint32_t sb, uint32_t pb, int warp, bool lane0) {
  const int wg = warp >> 2, w4 = warp & 3;
  constexpr int BB = 300;
  float a1[64];
  const float hr[2] = {0.5f * rs_[0], 0.5f * rs_[1]}, hc[2] = {hr[0] * hr[0], hr[1] * hr[1]};
  auto e1 = [&](int lo) {
#pragma unroll
    for (int i = lo; i < lo + 16; i++) { acc[32 + i] *= acc[i]; acc[i] = tanh_(acc[i] * hr[(i >> 1) & 1]); }
    pin<16>(acc + lo); pin<16>(acc + 32 + lo);
  };
  auto e2 = [&](int lo) {
#pragma unroll
    for (int m = lo; m < lo + 8; m++) hf[32 + m] = pack2(acc[32 + 2 * m] * fmaf(acc[2 * m], hc[m & 1], hc[m & 1]), acc[33 + 2 * m] * fmaf(acc[2 * m + 1], hc[m & 1], hc[m & 1]));
    pinr<8>(hf + 32 + lo);
  };
  const uint32_t doff = (uint32_t)(wg * 12288 + w4 * 3072 + laneid() * 16);
  auto send = [&](int s) {
    sta4(pb + 11 * U + doff + s * 512, hf + 32 + 4 * s, pb + MISC + 8u * (HF + 4) + wg * 8);
    sta4(pb + 11 * U + doff + s * 512 + 512, hf + 36 + 4 * s, pb + MISC + 8u * (HF + 4) + wg * 8);
  };
  auto e3 = [&]() {
#pragma unroll
    for (int m = 0; m < 8; m++) {
      const int w = m & 1;
      hf[48 + m] = pack2(blo(sg[m]) * (acc[64 + 2 * m] * hr[w]), bhi(sg[m]) * (acc[65 + 2 * m] * hr[w]));
    }
    pinr<8>(hf + 48);
    send(4);
  };
  mbar_wait(BAR(PF + 2));
  e3();
  e1(0);
  BBARI(BB + 1);
  e1(16);
  e2(0); send(0);
  BBARI(BB + 3);
  e2(8); send(2);
  TS7(21);
  mbar_wait(BAR(FT + 0));
  wg_fence();
#pragma unroll
  for (int s = 0; s < 8; s++) rs<128>(a1, hf + 4 * s, desc((s < 4 ? 26 : 7) * U + s * 2048, U), s == 0);
  wg_commit();
  TS7(22);
  mbar_wait(BAR(FT + 1));
  wg_fence();
#pragma unroll
  for (int s = 0; s < 8; s++) rs<128>(a1, hf + 56 + 4 * s, desc((s < 4 ? 14 : 9) * U + s * 2048, s < 4 ? U : 6 * U), false);
  wg_commit();
  TS7(23);
  wg_wait<1>();
  if (lane0) mbar_arrive(BAR(ET + 0));
  mbar_wait(BAR(FT + 2));
  wg_fence();
#pragma unroll
  for (int s = 0; s < 6; s++) rs<128>(a1, hf + 32 + 4 * s, desc(17 * U + s * 2048, 12288), false);
  wg_commit();
  CTS(9);
  uint32_t par;
  asm volatile("ld.shared.u32 %0, [%1];" : "=r"(par) : "r"(BAR(NBAR)) : "memory");
  mbar_wait(BAR(HF + 4) + wg * 8);
#pragma unroll
  for (int s = 0; s < 6; s++) lds4(hf + 88 + 4 * s, sb + 11 * U + doff + s * 512);
  CTS(10);
  wg_wait<1>();
  if (lane0) mbar_arrive(BAR(ET + 1));
  const uint64_t adw = (uint64_t)(wg * 512);
  float aw[32];
  auto wtile = [&](int t) {
    constexpr int wu[7] = {3, 11, 17, 20, 23, 0, 26};
    mbar_wait(BAR(FW + t));
    wg_fence();
#pragma unroll
    for (int kk = 0; kk < 4; kk++) {
      const uint64_t da = desc(wu[t] * U + kk * 32, 16) + adw, db = desc((t == 6 ? 7 : wu[t] + 2) * U + kk * 2048, U);
      ssk<64>(aw, da, db, t == 0 && kk == 0);
    }
    wg_commit();
  };
  float a2[16];
  float* a3 = a1;
  auto g2 = [&](int p, int lo, int hi) {
    wg_fence();
#pragma unroll
    for (int s = lo; s < hi; s++) rs<32>(a2, hf + 56 * p + 4 * s, desc((p ? (s < 8 ? 26 : 6) : (s < 12 ? 0 : 3)) * U + s * 2048, U), p == 0 && s == 0);
    wg_commit();
  };
  auto g3 = [&](int p, int lo, int hi) {
    wg_fence();
#pragma unroll
    for (int s = lo; s < hi; s++) {
      const uint64_t d = desc((p ? (s < 12 ? 14 * U : 7 * U) : (s < 12 ? 23 * U : 3 * U + 4096)) + s * 2048, U);
      if (p == 0 && s == 0) rsz<64>(a3, hf, d); else rs<64>(a3, hf + 56 * p + 4 * s, d, false);
    }
    wg_commit();
  };
  const int bid = par, r = bid >> 3, kq = (bid >> 1) & 3, n = bid & 1;
  const bool Y = kq == 3 - 3 * n;
  const int io = Y ? 2 : kq - n;
  uint4* const pbase = g_p + (size_t)((r * 2 + n) * 4) * 3072 + laneid();
  uint4* const pa = pbase + (n + (io == 2 ? 0 : io + 1)) * 3072 + (Y ? 2048 : 0) + warp * 128;
  uint4* const pb2 = pbase + (n + (io == 0 ? 2 : io - 1)) * 3072 + (Y ? 2048 : 1024) + warp * 128;
  uint4* const pc = pbase + (Y ? n + 2 : 3 - 3 * n) * 3072 + io * 1024 + warp * (Y ? 128 : 64);
  mbar_wait(BAR(FT + 3));
  wg_fence();
#pragma unroll
  for (int s = 0; s < 6; s++) rs<128>(a1, hf + 88 + 4 * s, desc(20 * U + s * 2048, 12288), false);
  wg_commit();
  if (lane0) mbar_arrive(BAR(LD2));
  mbar_wait(BAR(CLR));
  TS7(26);
  wg_wait<1>();
  if (lane0) mbar_arrive(BAR(ET + 2));
  mbar_wait(BAR(FT + 5));
  g2(0, 0, 7);
  mbar_wait(BAR(FT + 4));
  wg_wait<1>();
  if (lane0) mbar_arrive(BAR(ET + 3));
  pin<64>(a1);
  TS7(27);
  {
    uint32_t w[16];
#pragma unroll
    for (int i = 0; i < 16; i++) w[i] = pack2(a1[2 * i], a1[2 * i + 1]);
#pragma unroll
    for (int q = 0; q < 4; q++) w[4 * q] |= 1u;
    pinr<16>(w);
    g3(0, 0, 7);
    stg4(pa, w); stg4(pa + 32, w + 4);
    BBARI(BB + 11);
    g3(0, 7, 14);
    stg4(pa + 64, w + 8); stg4(pa + 96, w + 12);
  }
  BBARI(BB + 13);
  TS7(28);
  mbar_wait(BAR(FT + 6));
  g2(0, 7, 14);
  wg_wait<1>();
  if (lane0) mbar_arrive(BAR(ET + 4));
  g2(1, 0, 7);
  send_ll<2>(pb2, a1 + 32);
  BBARI(BB + 15);
  wg_wait<1>();
  if (lane0) mbar_arrive(BAR(ET + 5));
  mbar_wait(BAR(FT + 7));
  g2(1, 7, 14);
  g3(1, 0, 7);
  send_ll<2>(pb2 + 64, a1 + 48);
  BBARI(BB + 17);
  wg_wait<1>();
  if (lane0) mbar_arrive(BAR(ET + 6));
  pin<16>(a2);
  g3(1, 7, 14);
  if (!Y) { send_ll<2>(pc, a2); }
  BBARI(BB + 19);
  CTS(16);
  wtile(0);
  wg_wait<1>();
  pin<32>(a3);
  CTS(11);
  wtile(1);
  if (Y) {
    send_ll<4>(pc, a3);
#pragma unroll
    for (int i = 0; i < 16; i++) a3[i] = a2[i];
  }
  pin<32>(a3);
  BBARI(BB + 21);
  const uint32_t lb = sb + (uint32_t)((3 + wg) * U + w4 * 2048);
  const int row = r * 128 + warp * 16, col = Y ? 192 + 32 * n : 192 * n + 64 * kq;
  const uint4* pin_ = pbase + kq * 3072 + warp * (Y ? 64 : 128);
  const uint4* pin2 = pin_ + (Y ? 0 : 64);
  uint32_t v[3][16];
  wg_wait<1>();
  if (lane0) mbar_arrive(BAR(EW0));
#define LP0 2
#define LP1 2
#define LP2 5
#pragma unroll
  for (int t = 2; t < 7; t++) {
    wtile(t);
    if (t == 3) CTS(17);
    if (t == LP0) ld_ll4(v[0], pin_, pin2);
    if (t == LP1) ld_ll4(v[1], pin_ + 1024, pin2 + 1024);
    if (t == LP2) {
      if (LP0 < LP2) ref_ll(v[0], pin_, pin2);
      if (LP1 < LP2) ref_ll(v[1], pin_ + 1024, pin2 + 1024);
      ld_ll4(v[2], pin_ + 2048, pin2 + 2048);
    }
  }
  CTS(18);
  CTS(20);
  LANE();
  const uint32_t sa = lb + (uint32_t)((ln & 15) * 128 + (((ln >> 4) ^ (ln & 7)) << 4));
  uint32_t xr[16];
  mbar_wait(BAR(wg ? XR1 : XR0));
#pragma unroll
  for (int kk = 0; kk < 4; kk++) ldsm4(xr + 4 * kk, sa ^ (kk << 5));
  float xf_[32];
#pragma unroll
  for (int m = 0; m < 16; m++) { xf_[2 * m] = blo(xr[m]); xf_[2 * m + 1] = bhi(xr[m]); }
  pin<32>(xf_);
  BBARI(BB + 23);
  CTS(19);
  chk_ll(v, pin_, pin2);
#pragma unroll
  for (int i = 0; i < 2; i++) {
#pragma unroll
    for (int m = 0; m < 16; m++) { a3[2 * m] += blo(v[i][m]); a3[2 * m + 1] += bhi(v[i][m]); }
  }
  wg_wait<0>();
  pin<32>(aw);
  CTS(12);
#pragma unroll
  for (int kk = 0; kk < 4; kk++) {
    uint32_t o[4];
#pragma unroll
    for (int m = 4 * kk; m < 4 * kk + 4; m++) {
      const float u0 = a3[2 * m] + blo(v[2][m]), u1 = a3[2 * m + 1] + bhi(v[2][m]);
      o[m & 3] = pack2(fmaf(aw[2 * m], fmaf(u0, tanh_(u0), u0), xf_[2 * m]), fmaf(aw[2 * m + 1], fmaf(u1, tanh_(u1), u1), xf_[2 * m + 1]));
    }
    stsm4(sa ^ (kk << 5), o[0], o[1], o[2], o[3]);
  }
  __syncwarp();
  {
    const int c = ln & 7, l8 = ln >> 3;
    uint4* dst = reinterpret_cast<uint4*>(out + (size_t)(row + l8) * DM + col) + c;
    uint32_t w[16];
#pragma unroll
    for (int q = 0; q < 4; q++) lds4(w + 4 * q, lb + (uint32_t)((q * 4 + l8) * 128 + ((c ^ ((q * 4 + l8) & 7)) << 4)));
    if (!Y || c < 4) {
#pragma unroll
      for (int q = 0; q < 4; q++) dst[q * (4 * DM / 8)] = make_uint4(w[4 * q], w[4 * q + 1], w[4 * q + 2], w[4 * q + 3]);
    }
  }
}

__global__ void __cluster_dims__(2, 1, 1) __launch_bounds__(384, 1)
fused_kernel(const __grid_constant__ Maps M, const __grid_constant__ Ptrs P) {
  const __nv_bfloat16* xg = P.x;
  extern __shared__ __align__(1024) uint8_t smem_raw[];
  uint32_t sb = smem_u32(smem_raw);
  asm volatile("" : "+r"(sb));
  const int tid = threadIdx.x;
  const int warp = __shfl_sync(0xffffffffu, tid >> 5, 0);
  const int lane = tid & 31;
  const int wg = warp >> 2;
  const int bid = P.role[blockIdx.x], r = bid >> 3, j = bid & 7, kq = j >> 1, n = j & 1;

  if (warp < 8) CTS(27);
  if (warp < 4) load_x(xg, sb, r, warp, lane);
  if (warp < 8) CTS(28);
  if (elect_one()) {
    if ((warp >> 1) == 4) {
      const uint32_t ba = BAR(FA) + (warp - 8) * 8;
      mbar_init(ba, 1);
      mbar_expect_tx(ba, 2 * U);
      tma3d(sb + (14 + 2 * (warp - 8) + n) * U, &M.kv, j * 56 - 8 * n, (warp - 8) * 64, 1 + n, ba);
      tma3d(sb + (15 + 2 * (warp - 8) - n) * U, &M.kv, j * 56 - 8 * n, (warp - 8) * 64, 2 - n, ba);
    }
    const uint32_t b0 = BAR(2 + 8 * warp), cnt = warp < 6 ? 1u : 8u;
#pragma unroll
    for (int i = 0; i < 8; i++) mbar_init(b0 + 8 * i, cnt);
    if (warp >= 2) { mbar_init(BAR(94 + 2 * warp), 8); mbar_init(BAR(95 + 2 * warp), 8); }
  }
  asm volatile("fence.mbarrier_init.release.cluster;" ::: "memory");
  __syncwarp();
  if (warp < 8) CTS(29);
  asm volatile("barrier.cluster.arrive.relaxed.aligned;" ::: "memory");

  if (wg == 2) {
    asm volatile("setmaxnreg.dec.sync.aligned.u32 24;");
    if (warp == 8) {
      asm volatile("barrier.cluster.wait.acquire.aligned;" ::: "memory");
      if (elect_one()) {
        TS(2, 9);
        const int f0 = j * 224, ca = j * 56 - 8 * n;
#pragma unroll 1
        for (int g = 2; g < 7; g++) {
          mbar_expect_tx(BAR(FA + g), 2 * U);
          tma3d(sb + (14 + 2 * g + n) * U, &M.kv, ca, g * 64, 1 + n, BAR(FA + g));
          tma3d(sb + (15 + 2 * g - n) * U, &M.kv, ca, g * 64, 2 - n, BAR(FA + g));
        }
        TS(2, 1);
        const int ro = f0 + 32 * n, rg = f0 + 192 * (1 - n);
#pragma unroll 1
        for (int p = 0; p < 3; p++) {
          const uint64_t ut = p == 0 ? packtab(unitB) : p == 1 ? packtab(unitC) : packtab(unitD);
          const uint64_t dt = p == 0 ? packtab(depB) : p == 1 ? packtab(depC) : packtab(depD);
          const CUtensorMap* m3 = p == 0 ? &M.wq : p == 1 ? &M.w1b : &M.w3b;
          const int c3 = p == 0 ? ca : rg;
#pragma unroll 1
          for (int g = 0; g < 7; g++) {
            const uint32_t dst = sb + (uint32_t)((ut >> (8 * g)) & 255) * U;
            const uint32_t fb = BAR(FB + 7 * p + g);
            mbar_wait(BAR((uint32_t)((dt >> (8 * g)) & 255)));
            tma2d(dst, &M.w1a, ro + 64 * p, g * 64, fb);
            tma2d(dst + U, &M.w3a, ro + 64 * p, g * 64, fb);
            tma2d(dst + 2 * U, m3, c3, g * 64, fb);
          }
          TS(2, 2 + p);
        }
      }
    } else {
      if (elect_one()) {
        const CUtensorMap* mp = &M.kv + (warp - 9) * 6;
        if ((sb & 0x3FFFFu) != SM_BASE) asm volatile("trap;");
#pragma unroll
        for (int i = 0; i < 6; i++) map_prefetch(mp + i);
      }
      const uint32_t ep = g_epoch[blockIdx.x] + 1;
      const int at = tid - 288;
      if (at < 32) reinterpret_cast<float4*>(g_kv + ((ep & 1) ^ 1) * (8 * 2048) + j * 2048 + r * 128)[at] = make_float4(0.f, 0.f, 0.f, 0.f);
      asm volatile("barrier.cluster.wait.acquire.aligned;" ::: "memory");
      float* kv = g_kv + (ep & 1) * (8 * 2048) + j * 2048;
      if (at < 43) {
        const int b = FB + at;
        const uint32_t kb = b < FC ? 24 : b < FT ? 20 : b < FT + 2 ? 32 : b < FT + 4 ? 24 : b == FT + 4 || b == FT + 7 ? 28 : b < FW ? 14 : b < HF ? (kq == 3 - 3 * n ? 20 : 24) : b < HF + 4 ? 8 : 12;
        mbar_expect_tx(BAR(b), b == KVL ? KV_BYTES : kb << 10);
      }
      if (lane == 0) asm volatile("st.shared.v2.u32 [%0], {%1, %2};" ::"r"(BAR(NBAR)), "r"(bid), "r"(ep) : "memory");
#define CLP 0
      mbar_wait(BAR(XC1));
      if (warp == 11) {
          const bool isy = kq == 3 - 3 * n;
          uint4* ib = g_p + (size_t)((r * 2 + n) * 4 + kq) * 3072 + lane;
#pragma unroll 1
          for (int i = 0; i < 3; i++, ib += 1024) {
#pragma unroll 4
            for (int q = 0; q < (isy ? 512 : 1024); q += 32) asm volatile("st.relaxed.gpu.global.v4.b32 [%0], {%1,%1,%1,%1};" ::"l"(ib + q), "r"(0) : "memory");
          }
          if (lane == 0) { TS(3, 26); }
      }
      mbar_wait(BAR(EA6));
      const uint32_t kvm = sb + KVM_U * U;
#pragma unroll 1
      for (int c = at; c < 512; c += 96) {
        const int d = c >> 3, cc = c & 7;
        const bool used = d < 56 && (cc == 7 || (d < 28 ? cc < 4 : (cc >= 3)));
        if (!used) { const uint32_t z[4] = {0, 0, 0, 0}; sts4(kvm + d * 128 + ((cc ^ (d & 7)) << 4), z); }
      }
      if (warp == 9) {
        mbar_wait(BAR(KVST));
        if (elect_one()) {
          asm volatile("cp.reduce.async.bulk.global.shared::cta.bulk_group.add.f32 [%0], [%1], %2;" ::"l"(kv), "r"(sb + 27 * U), "r"(KV_BYTES) : "memory");
          bulk_commit();
          bulk_wait_all();
          TS(3, 4);
          SIGNAL(&g_f1[j * 32]);
          TS(3, 0);
          poll_flag(&g_f1[j * 32], 16u * ep);
          asm volatile("fence.proxy.async.global;" ::: "memory");
          TS(3, 1);
          asm volatile("cp.async.bulk.shared::cluster.global.mbarrier::complete_tx::bytes [%0], [%1], %2, [%3];" ::"r"(sb + 27 * U), "l"(kv), "r"(KV_BYTES), "r"(BAR(KVL)) : "memory");
        }
        __syncwarp();
      }
      {
        auto cv = [](uint32_t* w, const uint32_t* v, bool z01, bool z23) {
          w[0] = z01 ? 0u : pack2(__uint_as_float(v[0]), __uint_as_float(v[1])); w[1] = z01 ? 0u : pack2(__uint_as_float(v[2]), __uint_as_float(v[3]));
          w[2] = z23 ? 0u : pack2(__uint_as_float(v[4]), __uint_as_float(v[5])); w[3] = z23 ? 0u : pack2(__uint_as_float(v[6]), __uint_as_float(v[7]));
        };
        uint32_t v[8], u[8], w[4];
        const uint32_t s0 = sb + 27 * U + (at >> 2) * (KVP * 4) + (at & 3) * 32;
        mbar_wait(BAR(KVL));
        if (at == 0) TS(3, 20);
        lds4(v, s0); lds4(v + 4, s0 + 16);
        lds4(u, s0 + 24 * KVP * 4); lds4(u + 4, s0 + 24 * KVP * 4 + 16);
        int a2 = at;
        asm volatile("" : "+r"(a2));
        const int m = a2 & 3, d0 = a2 >> 2;
        cv(w, v, false, m == 3);
        sts4(kvm + d0 * 128 + ((m ^ (d0 & 7)) << 4), w);
        const bool zi = a2 >= 32;
        const int d2 = zi ? min(a2 - 32, 55) : 48 + d0;
        const uint32_t s2 = sb + 27 * U + d2 * (KVP * 4) + (zi ? 128 : m * 32);
        lds4(v, s2); lds4(v + 4, s2 + (zi ? 0 : 16));
        const int d1 = d0 + 24;
        cv(w, u, d1 >= 28 && m == 0, d1 < 28 && m == 3);
        sts4(kvm + d1 * 128 + (((m + (d1 >= 28 ? 3 : 0)) ^ (d1 & 7)) << 4), w);
        cv(w, v, m == 0, false);
        if (zi) w[0] = w[1] = w[2] = w[3] = pack2(__uint_as_float(v[0]), 0.f) << (d2 >= 28 ? 16 : 0);
        sts4(kvm + d2 * 128 + (((zi ? 7 : m + 3) ^ (d2 & 7)) << 4), w);
        if (at == 0) TS(3, 21);
      }
      fence_async();
      __syncwarp();
      if (lane == 0) mbar_arrive_n(BAR(KVM), warp < 11 ? 3 : 2);
      if (at == 0) TS(3, 2);
      if (warp < 11) {
        const int h = warp - 9;
        const uint32_t pb = mapa(sb, n ^ 1);
#pragma unroll 1
        for (int b = 0; b < 2; b++) {
          const uint32_t off = (uint32_t)((2 * b + (h ? 0 : 3)) * U + lane * 16), dd = b && h ? 5 * U : U, rb = pb + MISC + 8u * (HF + 2 * b + h);
          mbar_wait(BAR(HS + 2 * b + h));
          mbar_wait(BAR(PF + b));
#pragma unroll 1
          for (int i = 0; i < 8192; i += 1024) {
            uint32_t v[8];
            lds4(v, sb + off + i); lds4(v + 4, sb + off + i + 512);
            sta4(pb + dd + off + i, v, rb); sta4(pb + dd + off + i + 512, v + 4, rb);
          }
          if (h == 1 && lane == 0) { TS(3, 22 + b); }
        }
        __syncwarp();
        if (elect_one()) {
          if (h == 0) { mbar_arrive_n(BAR(LHA), 4); w2_tiles<1>(M, sb, j); }
          else { mbar_wait(BAR(OFREE)); w2_tiles<0>(M, sb, j); }
          const bool isy = kq == 3 - 3 * n;
          const uint32_t xb = BAR(h ? XR1 : XR0);
          mbar_expect_tx(xb, isy ? 4096u : 8192u);
          mbar_arrive_n(xb, 7);
          mbar_wait(BAR(EW0));
#pragma unroll
          for (int i = 0; i < 4; i++) tma2d(sb + (3 + h) * U + i * 2048, isy ? &M.xrb : &M.xra, isy ? 192 + 32 * n : 192 * n + 64 * kq, r * 128 + h * 64 + i * 16, xb);
          if (h == 1) { TS(3, 17); }
        }
      } else {
        if (elect_one()) {
        asm volatile("fence.acq_rel.gpu;" ::: "memory");
        TS(3, 27);
#pragma unroll 1
        for (int h = 0; h < 2; h++) {
          mbar_wait(BAR(OST + h));
          tma2d_store(&M.ost, j * 56, r * 128 + h * 64, sb + 27 * U);
          bulk_commit();
          bulk_wait_read();
          mbar_arrive_n(BAR(h ? OFREE : OF0), 8);
          bulk_wait_all();
          SIGNAL(&g_f2[r * 32]);
          TS(3, 24 + h);
        }
        uint32_t ep2;
        asm volatile("ld.shared.u32 %0, [%1];" : "=r"(ep2) : "r"(BAR(NBAR) + 4) : "memory");
        poll_flag(&g_f2[r * 32], 16u * ep2);
        mbar_arrive_n(BAR(CLR), 8);
        asm volatile("fence.proxy.async.global;" ::: "memory");
        TS(3, 5);
        const bool isy = kq == 3 - 3 * n;
        const int co = isy ? 192 + 32 * n : 192 * n + 64 * kq;
#pragma unroll 1
        for (int t = 0; t < 7; t++) {
          const uint64_t dt = (uint64_t)ED6 | ((uint64_t)LD2 << 8) | ((uint64_t)(ET + 2) << 16) | ((uint64_t)(ET + 3) << 24) | ((uint64_t)(ET + 4) << 32) |
                              ((uint64_t)(ET + 5) << 40) | ((uint64_t)(ET + 6) << 48);
          const uint32_t dst = sb + (uint32_t)((0x1A001714110B03ull >> (8 * t)) & 255) * U;
          mbar_wait(BAR((uint32_t)((dt >> (8 * t)) & 255)));
          tma2d(dst, &M.o, t * 64, r * 128, BAR(FW + t));
          tma2d(t == 6 ? sb + 7 * U : dst + 2 * U, isy ? &M.wob : &M.woa, co, t * 64, BAR(FW + t));
          TS(3, 10 + t);
        }
        uint32_t bx;
        asm volatile("mov.u32 %0, %%ctaid.x;" : "=r"(bx));
        g_epoch[bx] = ep2;
        TS(3, 6);
        }
      }
    }
  } else {
    asm volatile("setmaxnreg.inc.sync.aligned.u32 240;");
    asm volatile("barrier.cluster.wait.acquire.aligned;" ::: "memory");
    CTS(0);
    if (wg == 1) load_x(xg, sb, r, warp, lane);
    const int w4 = warp & 3;
    const bool lane0 = lane == 0;
    const uint32_t pb = mapa(sb, n ^ 1);
    const uint32_t so = sb + (uint32_t)((wg * 64 + w4 * 16 + (lane & 7) + ((lane >> 3) & 1) * 8) * 128 + (((lane >> 4) ^ (lane & 7)) << 4));
    uint32_t xf[112];
    float rs_[2];
    uint32_t pm0, pm1;
    float q0, q1;
    {
      float cm[2][4], ga[2][4], gb[2][4];
#pragma unroll
      for (int i = 0; i < 8; i++) cm[i >> 2][i & 3] = ga[i >> 2][i & 3] = gb[i >> 2][i & 3] = 0.f;
      const uint32_t sx = so + wg * (6 * U);
      uint32_t s0 = 0, s1 = 0;
#pragma unroll
      for (int kb = 0; kb < 7; kb++) {
        if (kb == 0) cp_wait<6>(); else if (kb == 1) cp_wait<5>(); else if (kb == 2) cp_wait<4>(); else if (kb == 3) cp_wait<3>();
        else if (kb == 4) cp_wait<2>(); else if (kb == 5) cp_wait<1>(); else cp_wait<0>();
        __syncwarp();
        if (kb == 0) CTS(14);
        EPI_TS(if (kb == 3) CTS(26));
        if (kb == 6) CTS(15);
#pragma unroll
        for (int kk = 0; kk < 4; kk++) ldsm4(xf + 16 * kb + 4 * kk, (sx ^ (kk << 5)) + kb * U);
#pragma unroll
        for (int kk = 0; kk < 4; kk++) mma16816(cm[kk & 1], xf + 16 * kb + 4 * kk, 0x3F803F80u, 0x3F803F80u);
        if (kb == 0) {
          s0 = __byte_perm(__shfl_sync(0xffffffffu, xf[0], lane & 28), 0, 0x1010);
          s1 = __byte_perm(__shfl_sync(0xffffffffu, xf[1], lane & 28), 0, 0x1010);
        }
        if (kb == 6) {
          const float m0 = (cm[0][0] + cm[1][0]) * (1.0f / 448.0f), m1 = (cm[0][2] + cm[1][2]) * (1.0f / 448.0f);
          pm0 = pack2(m0, m0); pm1 = pack2(m1, m1);
          q0 = m0 - blo(s0); q1 = m1 - blo(s1);
          __syncwarp();
          if (lane0) mbar_arrive_n(BAR(XC0) + wg * 8, 2);
        }
#pragma unroll
        for (int kk = 0; kk < 4; kk++) {
          const uint32_t* a = xf + 16 * kb + 4 * kk;
          uint32_t t[4];
#pragma unroll
          for (int i = 0; i < 4; i++) asm volatile("sub.rn.bf16x2 %0, %1, %2;" : "=r"(t[i]) : "r"(a[i]), "r"((i & 1) ? s1 : s0));
          mma16816(ga[kk & 1], t, t[0], t[2]);
          mma16816(gb[kk & 1], t, t[1], t[3]);
        }
      }
#pragma unroll
      for (int i = 0; i < 16; i++) asm volatile("sub.rn.bf16x2 %0, %0, %1;" : "+r"(xf[i]) : "r"((i & 1) ? pm1 : pm0));
      const bool odd = (lane >> 2) & 1;
      rs_[0] = odd ? ga[0][1] + ga[1][1] : ga[0][0] + ga[1][0];
      rs_[1] = odd ? gb[0][3] + gb[1][3] : gb[0][2] + gb[1][2];
    }
    CTS(1);
    uint32_t pq[14];
    {
      float acc[60];
      if (wg) mbar_wait(BAR(XH));
      pass1<0, 120>(acc, xf, sb, pb, lane0, (uint64_t)n, [&](int g) {
        if (g < 6) {
#pragma unroll
          for (int i = 0; i < 16; i++) asm volatile("sub.rn.bf16x2 %0, %0, %1;" : "+r"(xf[16 * g + 16 + i]) : "r"((i & 1) ? pm1 : pm0));
        }
        if (g == 1) {
          const int src = (lane & 28) | (lane >> 3);
          const float v0 = fmaxf(fmaf(__shfl_sync(0xffffffffu, rs_[0], src), 1.0f / 448.0f, -q0 * q0), 0.f);
          const float v1 = fmaxf(fmaf(__shfl_sync(0xffffffffu, rs_[1], src), 1.0f / 448.0f, -q1 * q1), 0.f);
          rs_[0] = rcp(bfr(sqrt_(bfr(bfr(v0) + 1e-5f))));
          rs_[1] = rcp(bfr(sqrt_(bfr(bfr(v1) + 1e-5f))));
          pin<2>(rs_);
        }
      }, [&](int g) {
        if (g == AHOLD && lane0 && wg == 0) mbar_arrive_n(BAR(XH), 2);
      });
      CTS(2);
      LANE();
      uint32_t pk[16], pv[16];
      float e[28];
      phi1(e, acc, rs_);
#pragma unroll
      for (int m = 0; m < 14; m++) pv[m] = pack2(acc[32 + 2 * m] * rs_[m & 1], acc[33 + 2 * m] * rs_[m & 1]);
      pv[14] = pv[15] = t4 == 0 ? 0x3F803F80u : 0u;
      pinr<16>(pv);
      TS4(21);
      mbar_wait(BAR(XC1));
      TS4(22);
#pragma unroll
      for (int kk = 0; kk < 4; kk++) stsm4((so ^ (kk << 5)) + 11 * U, pv[4 * kk], pv[4 * kk + 1], pv[4 * kk + 2], pv[4 * kk + 3]);
#pragma unroll
      for (int m = 0; m < 14; m++) pk[m] = pack2(e[2 * m] + acc[2 * m], e[2 * m + 1] + acc[2 * m + 1]);
      pk[14] = pk[15] = 0u;
#pragma unroll
      for (int kk = 0; kk < 4; kk++) stsm4((so ^ (kk << 5)) + 6 * U, pk[4 * kk], pk[4 * kk + 1], pk[4 * kk + 2], pk[4 * kk + 3]);
      TS4(23);
      fence_async();
      __syncwarp();
      if (lane0) mbar_arrive(BAR(PKST));
      TS4(24);
      if (wg == 1) {
        float kv[32];
        mbar_wait(BAR(PKST));
        TS4(25);
        wg_fence();
#pragma unroll
        for (int ks = 0; ks < 8; ks++) {
          if (ks == 0) ss64_0(kv, desc(6 * U, U), desc(11 * U, U));
          else ss64_1(kv, desc(6 * U + ks * 2048, U), desc(11 * U + ks * 2048, U));
        }
        wg_commit();
        wg_wait<0>();
        if (lane0) mbar_arrive_n(BAR(KVFREE), 2);
        pin<32>(kv);
        TS4(26);
#pragma unroll
        for (int h = 0; h < 2; h++) {
          const int d = w4 * 16 + g8 + 8 * h;
          const uint32_t lim = d < 28 ? 0u : d < 56 ? 28u : 1000u;
          const uint32_t ka = sb + 27 * U + (uint32_t)d * (KVP * 4) + (uint32_t)(2 * t4) * 4 - (d < 28 ? 0u : 96u);
#pragma unroll
          for (int i = 0; i < 7; i++)
            asm volatile("{ .reg .pred p; setp.lt.u32 p, %0, 28; @p st.shared.v2.f32 [%1], {%2,%3}; }" ::"r"((uint32_t)(8 * i + 2 * t4) - lim), "r"(ka + 32 * i), "f"(kv[4 * i + 2 * h]), "f"(kv[4 * i + 2 * h + 1]) : "memory");
          asm volatile("{ .reg .pred p; setp.lt.u32 p, %0, 56; @p st.shared.f32 [%1], %2; }" ::"r"((uint32_t)(d + 64 * t4)), "r"(sb + 27 * U + (uint32_t)d * (KVP * 4) + 128), "f"(kv[28 + 2 * h]) : "memory");
        }
        TS4(27);
        fence_async();
        __syncwarp();
        if (lane0) mbar_arrive_n(BAR(KVST), 2);
      }
      CTS(3);
    }
    const uint32_t hoff = (uint32_t)((wg ? 0 : 3 * U) + w4 * 2048 + laneid() * 16);
    {
      float acc[92];
      pass1<1, 184>(acc, xf, sb, pb, lane0, (uint64_t)n, [&](int) {}, [&](int) {});
      CTS(4);
      pin<2>(rs_);
      uint32_t h[16];
      hfrag64<1>(h, acc, rs_, sb, wg);
      pinr<16>(h);
      mbar_wait(BAR(EB1));
      EPI_TS(CTS(23));
#pragma unroll
      for (int s = 0; s < 4; s++) sts4(sb + hoff + s * 512, h + 4 * s);
      __syncwarp();
      if (lane0) mbar_arrive_n(BAR(HS) + wg * 8, 2);
      EPI_TS(CTS(24));
      float e[28];
      phi1(e, acc + 64, rs_);
      EPI_TS(CTS(25));
#pragma unroll
      for (int m = 0; m < 14; m++) pq[m] = pack2(e[2 * m] + acc[64 + 2 * m], e[2 * m + 1] + acc[65 + 2 * m]);
      pq[12] ^= sb; pq[13] ^= sb;
      pinr<14>(pq);
      CTS(5);
    }
    uint32_t sg[8];
    {
      float acc[80];
      pass1<2, 160>(acc, xf, sb, pb, lane0, 0, [&](int) {}, [&](int) {});
      CTS(6);
      pin<2>(rs_);
      uint32_t h[16];
      hfrag64<2>(h, acc, rs_, sb, wg);
      pinr<16>(h);
      TS5(21);
      mbar_wait(BAR(EC0 + 1));
      TS5(22);
#pragma unroll
      for (int s = 0; s < 4; s++) sts4(sb + 2 * U + hoff + s * 512, h + 4 * s);
      __syncwarp();
      if (lane0) mbar_arrive_n(BAR(HS + 2) + wg * 8, 2);
      float nm[32];
      TS5(23);
      mbar_wait(BAR(KVM));
      TS5(24);
      {
        uint32_t q3[4];
        asm volatile("xor.b32 %0, %4, %6; xor.b32 %1, %5, %6; mov.b32 %2, 0; mov.b32 %3, 0;" : "=r"(q3[0]), "=r"(q3[1]), "=r"(q3[2]), "=r"(q3[3]) : "r"(pq[12]), "r"(pq[13]), "r"(sb));
        wg_fence();
        rs64_0(nm, pq, desc(KVM_U * U, U));
        rs64_1(nm, pq + 4, desc(KVM_U * U + 2048, U));
        rs64_1(nm, pq + 8, desc(KVM_U * U + 4096, U));
        rs64_1(nm, q3, desc(KVM_U * U + 6144, U));
      }
      wg_commit();
      float th[16];
      {
        const float hr[2] = {0.5f * rs_[0], 0.5f * rs_[1]};
#pragma unroll
        for (int i = 0; i < 16; i++) { acc[64 + i] *= hr[(i >> 1) & 1]; th[i] = tanh_(acc[64 + i]); }
        pin<16>(th); pin<16>(acc + 64);
      }
#pragma unroll
      for (int m = 0; m < 8; m++) sg[m] = pack2(fmaf(acc[64 + 2 * m], th[2 * m], acc[64 + 2 * m]), fmaf(acc[65 + 2 * m], th[2 * m + 1], acc[65 + 2 * m]));
      pinr<8>(sg);
      wg_wait<0>();
      pin<32>(nm);
      TS5(25);
      LANE();
      float rd[4];
#pragma unroll
      for (int i = 0; i < 4; i++) rd[i] = rcp(nm[28 + i] + 1e-6f);
      uint32_t ob[14];
#pragma unroll
      for (int i = 0; i < 7; i++) {
        const bool h0 = i < 3 || (i == 3 && t4 < 2);
        const float ra = h0 ? rd[0] : rd[1], rb = h0 ? rd[2] : rd[3];
        ob[2 * i] = pack2(nm[4 * i] * ra, nm[4 * i + 1] * ra);
        ob[2 * i + 1] = pack2(nm[4 * i + 2] * rb, nm[4 * i + 3] * rb);
      }
      pinr<14>(ob);
      TS5(26);
      if (wg) mbar_wait(BAR(OF0));
      const uint32_t sa = sb + 27 * U + (uint32_t)(w4 * 16 + (ln & 15)) * 112;
#pragma unroll
      for (int kk = 0; kk < 3; kk++) stsm4(sa + (ln >> 4) * 16 + kk * 32, ob[4 * kk], ob[4 * kk + 1], ob[4 * kk + 2], ob[4 * kk + 3]);
      stsm2(sa + 96, ob[12], ob[13]);
      TS5(27);
      fence_async();
      __syncwarp();
      if (lane0) mbar_arrive_n(BAR(OST) + wg * 8, 2);
      CTS(7);
    }
    uint32_t hf[112];
    float acc[80];
    pass1<3, 160>(acc, xf, sb, pb, lane0, 0, [&](int g) {
      if (g >= 5) {
        uint32_t one;
        if (g == 5) {
          BBARI(101);
          asm volatile("{ .reg .b32 t; lop3.b32 t, %1, %2, %3, 0xFE; lop3.b32 t, t, %4, %5, 0xFE; lop3.b32 t, t, %6, %7, 0xFE; lop3.b32 t, t, %8, %9, 0xFE; lop3.b32 t, t, %10, %11, 0xFE;\n"
                       "lop3.b32 t, t, %12, 1, 0xFE; redux.sync.min.u32 t, t, 0xffffffff; min.u32 %0, t, 1; }"
                       : "=r"(one) : "r"(hf[0]), "r"(hf[4]), "r"(hf[8]), "r"(hf[12]), "r"(hf[16]), "r"(hf[20]), "r"(hf[24]), "r"(hf[28]), "r"(hf[56]), "r"(hf[60]), "r"(hf[64]), "r"(hf[68]));
          if (lane0 && wg == 0) mbar_arrive_n(BAR(LHA), one);
        } else {
          BBARI(103);
          asm volatile("{ .reg .b32 t; lop3.b32 t, %1, %2, %3, 0xFE; lop3.b32 t, t, %4, 1, 0xFE; redux.sync.min.u32 t, t, 0xffffffff; min.u32 %0, t, 1; }"
                       : "=r"(one) : "r"(hf[72]), "r"(hf[76]), "r"(hf[80]), "r"(hf[84]));
          if (lane0) mbar_arrive_n(BAR(LH1), one);
        }
      }
      if (g >= 2 && g < 6) {
        const int b = (g >> 1) - 1, pe = g & 1;
        uint32_t* d = hf + 56 * pe + 16 * b;
        if (pe) mbar_wait(BAR(HF + 2 * b) + wg * 8);
#pragma unroll
        for (int s = 0; s < 4; s++) lds4t(d + 4 * s, xf + 16 * (g - 2) + 4 * s, sb + (pe ? (b ? 3 * U + wg * (4 * U) : U) : 2 * b * U) + hoff + s * 512);
        pinr<16>(d);
      }
    }, [&](int) {});
    CTS(8);
    tail(M, P.out, hf, acc, sg, rs_, sb, pb, warp, lane0);
    CTS(13);
    if ((tid & 127) == 0) { GTS(wg, 30); TSDUMP(wg); if (wg == 1) { TSDUMP(3); } }
  }
}

typedef CUresult (*EncodeFn)(CUtensorMap*, CUtensorMapDataType, cuuint32_t, void*, const cuuint64_t*, const cuuint64_t*, const cuuint32_t*,
                             const cuuint32_t*, CUtensorMapInterleave, CUtensorMapSwizzle, CUtensorMapL2promotion, CUtensorMapFloatOOBfill);

void make_map(EncodeFn enc, CUtensorMap* m, const void* base, uint64_t cols, uint64_t rows, uint32_t bc, uint32_t br, bool sw) {
  cuuint64_t dims[2] = {cols, rows}, str[1] = {cols * 2};
  cuuint32_t box[2] = {bc, br}, es[2] = {1, 1};
  enc(m, CU_TENSOR_MAP_DATA_TYPE_BFLOAT16, 2, const_cast<void*>(base), dims, str, box, es, CU_TENSOR_MAP_INTERLEAVE_NONE,
      sw ? CU_TENSOR_MAP_SWIZZLE_128B : CU_TENSOR_MAP_SWIZZLE_NONE, CU_TENSOR_MAP_L2_PROMOTION_L2_128B, CU_TENSOR_MAP_FLOAT_OOB_FILL_NONE);
}
void make_map3(EncodeFn enc, CUtensorMap* m, const void* base, uint64_t sec, uint64_t nsec, uint64_t rows, uint32_t bc, uint32_t br, uint32_t bs) {
  cuuint64_t dims[3] = {sec, rows, nsec}, str[2] = {sec * nsec * 2, sec * 2};
  cuuint32_t box[3] = {bc, br, bs}, es[3] = {1, 1, 1};
  enc(m, CU_TENSOR_MAP_DATA_TYPE_BFLOAT16, 3, const_cast<void*>(base), dims, str, box, es, CU_TENSOR_MAP_INTERLEAVE_NONE,
      CU_TENSOR_MAP_SWIZZLE_128B, CU_TENSOR_MAP_L2_PROMOTION_L2_128B, CU_TENSOR_MAP_FLOAT_OOB_FILL_NONE);
}

}

extern "C" void kernel_launch(void* const* d_in, const int* in_sizes, int n_in, void* d_out, int out_size) {
  (void)in_sizes; (void)n_in; (void)out_size;
  void* fn = nullptr;
  cudaDriverEntryPointQueryResult q;
  cudaGetDriverEntryPoint("cuTensorMapEncodeTiled", &fn, cudaEnableDefault, &q);
  EncodeFn enc = (EncodeFn)fn;
  void* op = nullptr;
  cudaGetSymbolAddress(&op, g_o);
  Maps M;
  make_map3(enc, &M.kv, d_in[1], DM, 3, DM, 64, 64, 1);
  make_map(enc, &M.wq, d_in[1], 3 * DM, DM, 64, 64, true);
  make_map(enc, &M.w1a, d_in[4], FF, DM, 64, 64, true);
  make_map(enc, &M.w3a, d_in[5], FF, DM, 64, 64, true);
  make_map(enc, &M.w1b, d_in[4], FF, DM, 32, 64, true);
  make_map(enc, &M.w3b, d_in[5], FF, DM, 32, 64, true);
  make_map(enc, &M.w2a, d_in[6], DM, FF, 64, 64, true);
  make_map(enc, &M.w2b, d_in[6], DM, FF, 64, 32, true);
  make_map(enc, &M.w2c, d_in[6], DM, FF, 32, 64, true);
  make_map(enc, &M.w2d, d_in[6], DM, FF, 32, 32, true);
  make_map(enc, &M.woa, d_in[2], DM, DM, 64, 64, true);
  make_map(enc, &M.wob, d_in[2], DM, DM, 32, 64, true);
  make_map(enc, &M.o, op, DM, SEQ, 64, 128, true);
  make_map(enc, &M.ost, op, DM, SEQ, 56, 64, false);
  make_map(enc, &M.outa, d_out, DM, SEQ, 64, 16, true);
  make_map(enc, &M.outb, d_out, DM, SEQ, 32, 16, true);
  make_map(enc, &M.xra, d_in[0], DM, SEQ, 64, 16, true);
  make_map(enc, &M.xrb, d_in[0], DM, SEQ, 32, 16, true);
  cudaFuncSetAttribute(fused_kernel, cudaFuncAttributeMaxDynamicSharedMemorySize, (int)SMEM_BYTES);
  Ptrs P;
  P.x = (const __nv_bfloat16*)d_in[0]; P.wqkv = (const __nv_bfloat16*)d_in[1]; P.wo = (const __nv_bfloat16*)d_in[2];
  P.out = (__nv_bfloat16*)d_out;
  P.w1 = (const __nv_bfloat16*)d_in[4]; P.w3 = (const __nv_bfloat16*)d_in[5]; P.w2 = (const __nv_bfloat16*)d_in[6];
  {
    int cnt[4] = {0, 0, 0, 0};
    for (int c = 0; c < 64; c++) {
      const int kq = c < 4 ? 0 : c < 36 ? ((c - 4) & 7) >> 1 : ((c - 36) % 7 + 1) >> 1;
      const int r = cnt[kq]++;
      P.role[2 * c] = (uint32_t)(r * 8 + kq * 2);
      P.role[2 * c + 1] = (uint32_t)(r * 8 + kq * 2 + 1);
    }
  }
  fused_kernel<<<128, 384, SMEM_BYTES>>>(M, P);
}
```

```cpp
#include <cuda_runtime.h>
#include <cuda.h>
#include <cuda_bf16.h>
#include <stdint.h>

namespace {

constexpr int SEQ = 2048, DM = 448, FF = 1792;
constexpr uint32_t U = 8192;
constexpr uint32_t SM_BASE = 1024;
constexpr uint32_t MISC = 28 * U;
constexpr uint32_t SMEM_BYTES = 28 * U + 3072;
constexpr uint32_t KVM_U = 26;

enum : int { FA = 0, FB = 7, FC = 14, FD = 21, FT = 28, FW = 36, HF = 43, KVL = 49,
             LH0 = 50, LH1, EA1 = 52, EA2, EA4, EA5, EA6, EB1 = 57, EC0 = 63, ED1 = 70, OF0, ED4, ED5, ED6, ET = 75,
             PKST = 83, LD2, PF = 85, EW0 = 88, XC0, XC1, KVST, OST = 92, KVM = 94, OFREE, XR0, KVFREE, ED2 = 98, ED3, LHA, XH, FIN = 102, XG = 104, XR1 = 105, CLR = 106, INB = 107, EG3 = 109, EL0 = 110, HS = 112, NBAR = 118 };
constexpr int KVP = 36;
constexpr uint32_t KV_BYTES = 56 * KVP * 4;

struct Maps { CUtensorMap kv, wq, w1a, w3a, w1b, w3b, w2a, w2b, w2c, w2d, woa, wob, o, ost; };

struct Ptrs { const __nv_bfloat16* x; __nv_bfloat16* out; const __nv_bfloat16 *wo, *w1, *w3, *w2, *wqkv; };

__device__ __forceinline__ int role_of(int b) {
  int r;
  asm("{ .reg .pred p, q, z; .reg .b32 c, t, k, u, v, w;\n"
      "shr.u32 c, %1, 1; setp.lt.u32 p, c, 36; setp.lt.u32 q, c, 4;\n"
      "sub.u32 t, c, 35; mad.lo.u32 k, c, 37, -1332; shr.u32 k, k, 8; mad.lo.u32 u, k, -7, t;\n"
      "sub.u32 t, c, 4; shr.u32 v, t, 3; and.b32 t, t, 7; selp.b32 k, v, k, p; selp.b32 u, t, u, p; selp.b32 u, 0, u, q;\n"
      "setp.lt.u32 z, u, 2; and.b32 t, u, 1; mad.lo.u32 t, k, 2, t; add.u32 v, k, 12; add.u32 w, t, 4; selp.b32 v, w, v, p; selp.b32 v, c, v, q;\n"
      "selp.b32 w, 0, 8, p; add.u32 w, w, t; selp.b32 v, v, w, z;\n"
      "and.b32 u, u, 6; and.b32 t, %1, 1; or.b32 u, u, t; mad.lo.u32 %0, v, 8, u; }" : "=r"(r) : "r"(b));
  return r;
}

__device__ uint32_t g_epoch[128];
__device__ uint32_t g_f1[8 * 32];
__device__ uint32_t g_f2[16 * 32];
__device__ __align__(128) float g_kv[2 * 8 * 2048];
__device__ __nv_bfloat16 g_o[SEQ * DM];
__device__ uint4 g_p[16 * 2 * 4 * 3 * 1024];
#define TS(role, i)
#define GTS(role, i)
#define CTS(i)
#define TSDUMP(role)

__device__ __forceinline__ uint32_t smem_u32(const void* p) { return (uint32_t)__cvta_generic_to_shared(p); }
__device__ __forceinline__ void mbar_init(uint32_t bar, uint32_t cnt) { asm volatile("mbarrier.init.shared::cta.b64 [%0], %1;" ::"r"(bar), "r"(cnt) : "memory"); }
__device__ __forceinline__ void mbar_expect_tx(uint32_t bar, uint32_t bytes) { asm volatile("mbarrier.arrive.expect_tx.shared::cta.b64 _, [%0], %1;" ::"r"(bar), "r"(bytes) : "memory"); }
__device__ __forceinline__ void mbar_arrive_n(uint32_t bar, uint32_t n) { asm volatile("mbarrier.arrive.shared::cta.b64 _, [%0], %1;" ::"r"(bar), "r"(n) : "memory"); }
__device__ __forceinline__ void mbar_arrive(uint32_t bar) { asm volatile("mbarrier.arrive.shared::cta.b64 _, [%0];" ::"r"(bar) : "memory"); }
__device__ __forceinline__ void mbar_arrive_remote(uint32_t rbar) { asm volatile("mbarrier.arrive.shared::cluster.b64 _, [%0];" ::"r"(rbar) : "memory"); }
#define WV 2
#define DV 2
#define WD 2
#define HADD 4
#define KVOV 3
#define HX0 4
#define HX1 4
#define AFIRST 1
__device__ __forceinline__ void mbar_wait(uint32_t bar) {
  asm volatile("{ .reg .pred p;\n W_L: mbarrier.try_wait.parity.shared::cta.b64 p, [%0], 0;\n @!p pmevent 1; @!p bra W_L; }" ::"r"(bar) : "memory");
}
__device__ __forceinline__ void mbar_wait_to(uint32_t bar) {
  asm volatile("{ .reg .pred p; .reg .u32 n; mov.u32 n, 0;\n"
               "W_L: mbarrier.try_wait.parity.shared::cta.b64 p, [%0], 0;\n"
               "@p bra W_D;\n add.u32 n, n, 1;\n setp.lt.u32 p, n, 4194304;\n @p bra W_L;\n trap;\n W_D: }" ::"r"(bar) : "memory");
}
__device__ __forceinline__ void tma2d(uint32_t dst, const CUtensorMap* m, int c0, int c1, uint32_t bar) {
  asm volatile("cp.async.bulk.tensor.2d.shared::cluster.global.mbarrier::complete_tx::bytes [%0], [%1, {%3, %4}], [%2];" ::"r"(dst), "l"(m), "r"(bar), "r"(c0), "r"(c1) : "memory");
}
__device__ __forceinline__ void tma3d(uint32_t dst, const CUtensorMap* m, int c0, int c1, int c2, uint32_t bar) {
  asm volatile("cp.async.bulk.tensor.3d.shared::cluster.global.mbarrier::complete_tx::bytes [%0], [%1, {%3, %4, %5}], [%2];" ::"r"(dst), "l"(m), "r"(bar), "r"(c0), "r"(c1), "r"(c2) : "memory");
}
__device__ __forceinline__ void bulk_s2g(void* g, uint32_t src, uint32_t bytes) {
  asm volatile("cp.async.bulk.global.shared::cta.bulk_group [%0], [%1], %2;" ::"l"(g), "r"(src), "r"(bytes) : "memory");
}
__device__ __forceinline__ void bulk_commit() { asm volatile("cp.async.bulk.commit_group;" ::: "memory"); }
__device__ __forceinline__ void bulk_wait_read() { asm volatile("cp.async.bulk.wait_group.read 0;" ::: "memory"); }
__device__ __forceinline__ void bulk_wait_all() { asm volatile("cp.async.bulk.wait_group 0;" ::: "memory"); }
__device__ __forceinline__ void l2_prefetch(const void* g, uint32_t bytes) { asm volatile("cp.async.bulk.prefetch.L2.global [%0], %1;" ::"l"(g), "r"(bytes) : "memory"); }
__device__ __forceinline__ void map_prefetch(const CUtensorMap* m) { asm volatile("prefetch.tensormap [%0];" ::"l"(m) : "memory"); }
__device__ __forceinline__ void tma2d_store(const CUtensorMap* m, int c0, int c1, uint32_t src) {
  asm volatile("cp.async.bulk.tensor.2d.global.shared::cta.bulk_group [%0, {%2, %3}], [%1];" ::"l"(m), "r"(src), "r"(c0), "r"(c1) : "memory");
}
__device__ __forceinline__ void bulk_s2c(uint32_t rdst, uint32_t src, uint32_t bytes, uint32_t rbar) {
  asm volatile("cp.async.bulk.shared::cluster.shared::cta.mbarrier::complete_tx::bytes [%0], [%1], %2, [%3];" ::"r"(rdst), "r"(src), "r"(bytes), "r"(rbar) : "memory");
}
__device__ __forceinline__ uint32_t mapa(uint32_t a, uint32_t cta) { uint32_t r; asm volatile("mapa.shared::cluster.u32 %0, %1, %2;" : "=r"(r) : "r"(a), "r"(cta)); return r; }
__device__ __forceinline__ bool elect_one() { uint32_t p; asm volatile("{ .reg .pred P; elect.sync _|P, 0xffffffff; selp.u32 %0, 1, 0, P; }" : "=r"(p)); return p; }
__device__ __forceinline__ int laneid() { int l; asm volatile("mov.u32 %0, %%laneid;" : "=r"(l)); return l; }
__device__ __forceinline__ void fence_async() { asm volatile("fence.proxy.async.shared::cta;" ::: "memory"); }
__device__ __forceinline__ void wg_fence() { asm volatile("wgmma.fence.sync.aligned;" ::: "memory"); }
__device__ __forceinline__ void wg_commit() { asm volatile("wgmma.commit_group.sync.aligned;" ::: "memory"); }
template <int N> __device__ __forceinline__ void wg_wait() { asm volatile("wgmma.wait_group.sync.aligned %0;" ::"n"(N) : "memory"); }
template <int N> __device__ __forceinline__ void pin(float* a) {
#pragma unroll
  for (int i = 0; i < N; i++) asm volatile("" : "+f"(a[i])::"memory");
}
template <int N> __device__ __forceinline__ void pinr(uint32_t* a) {
#pragma unroll
  for (int i = 0; i < N; i++) asm volatile("" : "+r"(a[i])::"memory");
}
__device__ __forceinline__ void ldsm4(uint32_t* r, uint32_t a) { asm volatile("ldmatrix.sync.aligned.m8n8.x4.shared.b16 {%0,%1,%2,%3}, [%4];" : "=r"(r[0]), "=r"(r[1]), "=r"(r[2]), "=r"(r[3]) : "r"(a) : "memory"); }
__device__ __forceinline__ void stsm4(uint32_t a, uint32_t r0, uint32_t r1, uint32_t r2, uint32_t r3) { asm volatile("stmatrix.sync.aligned.m8n8.x4.shared.b16 [%0], {%1,%2,%3,%4};" ::"r"(a), "r"(r0), "r"(r1), "r"(r2), "r"(r3) : "memory"); }
__device__ __forceinline__ void stsm2(uint32_t a, uint32_t r0, uint32_t r1) { asm volatile("stmatrix.sync.aligned.m8n8.x2.shared.b16 [%0], {%1,%2};" ::"r"(a), "r"(r0), "r"(r1) : "memory"); }
__device__ __forceinline__ void sts4(uint32_t a, const uint32_t* r) { asm volatile("st.shared.v4.b32 [%0], {%1,%2,%3,%4};" ::"r"(a), "r"(r[0]), "r"(r[1]), "r"(r[2]), "r"(r[3]) : "memory"); }
__device__ __forceinline__ void sta4(uint32_t ra, const uint32_t* r, uint32_t rbar) {
  asm volatile("st.async.weak.shared::cluster.mbarrier::complete_tx::bytes.v4.b32 [%0], {%1,%2,%3,%4}, [%5];" ::"r"(ra), "r"(r[0]), "r"(r[1]), "r"(r[2]), "r"(r[3]), "r"(rbar) : "memory");
}
__device__ __forceinline__ void lds4(uint32_t* r, uint32_t a) { asm volatile("ld.shared.v4.b32 {%0,%1,%2,%3}, [%4];" : "=r"(r[0]), "=r"(r[1]), "=r"(r[2]), "=r"(r[3]) : "r"(a) : "memory"); }
__device__ __forceinline__ void lds4t(uint32_t* r, const uint32_t* o, uint32_t a) {
  r[0] = o[0]; r[1] = o[1]; r[2] = o[2]; r[3] = o[3];
  asm volatile("{ .reg .pred p; setp.ne.u32 p, %4, 1; @p ld.shared.v4.b32 {%0,%1,%2,%3}, [%4]; }" : "+r"(r[0]), "+r"(r[1]), "+r"(r[2]), "+r"(r[3]) : "r"(a) : "memory");
}
__device__ __forceinline__ uint32_t pack2(float lo, float hi) { uint32_t r; asm("cvt.rn.bf16x2.f32 %0, %1, %2;" : "=r"(r) : "f"(hi), "f"(lo)); return r; }
__device__ __forceinline__ float blo(uint32_t v) { return __uint_as_float(v << 16); }
__device__ __forceinline__ float bhi(uint32_t v) { return __uint_as_float(v & 0xFFFF0000u); }
__device__ __forceinline__ float ex2(float x) { float y; asm("ex2.approx.ftz.f32 %0, %1;" : "=f"(y) : "f"(x)); return y; }
__device__ __forceinline__ float rcp(float x) { float y; asm("rcp.approx.ftz.f32 %0, %1;" : "=f"(y) : "f"(x)); return y; }
__device__ __forceinline__ float sqrt_(float x) { float y; asm("sqrt.approx.ftz.f32 %0, %1;" : "=f"(y) : "f"(x)); return y; }
__device__ __forceinline__ void mma16816(float* c, const uint32_t* a, uint32_t b0, uint32_t b1) {
  asm volatile("mma.sync.aligned.m16n8k16.row.col.f32.bf16.bf16.f32 {%0,%1,%2,%3}, {%4,%5,%6,%7}, {%8,%9}, {%0,%1,%2,%3};"
               : "+f"(c[0]), "+f"(c[1]), "+f"(c[2]), "+f"(c[3]) : "r"(a[0]), "r"(a[1]), "r"(a[2]), "r"(a[3]), "r"(b0), "r"(b1));
}
__device__ __forceinline__ void mma1688(float* c, uint32_t a0, uint32_t a1, uint32_t b) {
  asm("mma.sync.aligned.m16n8k8.row.col.f32.bf16.bf16.f32 {%0,%1,%2,%3}, {%4,%5}, {%6}, {%0,%1,%2,%3};" : "+f"(c[0]), "+f"(c[1]), "+f"(c[2]), "+f"(c[3]) : "r"(a0), "r"(a1), "r"(b));
}
__device__ __forceinline__ float tanh_(float x) { float y; asm("tanh.approx.f32 %0, %1;" : "=f"(y) : "f"(x)); return y; }
__device__ __forceinline__ float bfr(float x) { return __bfloat162float(__float2bfloat16_rn(x)); }
__device__ __forceinline__ uint32_t ld_acq(const uint32_t* p) { uint32_t v; asm volatile("ld.acquire.gpu.global.u32 %0, [%1];" : "=r"(v) : "l"(p) : "memory"); return v; }
__device__ __forceinline__ void poll_flag(const uint32_t* p, uint32_t target) {
  uint32_t n = 0;
  while ((int)(ld_acq(p) - target) < 0) { if (++n > (1u << 21)) asm volatile("trap;"); }
}
#define SIGNAL(p) asm volatile("red.relaxed.gpu.global.add.u32 [%0], 1;" ::"l"(p) : "memory")
__device__ __forceinline__ void ld_ll(uint32_t* r, const uint4* p) {
  asm volatile("{ .reg .b128 t; .reg .b64 lo, hi; ld.relaxed.gpu.global.b128 t, [%4]; mov.b128 {lo,hi}, t; mov.b64 {%0,%1}, lo; mov.b64 {%2,%3}, hi; }" : "=r"(r[0]), "=r"(r[1]), "=r"(r[2]), "=r"(r[3]) : "l"(p) : "memory");
}
template <int K> __device__ __forceinline__ uint64_t desc_base(uint32_t sb, uint32_t add) {
  uint64_t d;
  asm volatile("{ .reg .b32 lo; shr.u32 lo, %1, 4; and.b32 lo, lo, %3; add.u32 lo, lo, %2; mov.b64 %0, {lo, 0x40000040}; }" : "=l"(d) : "r"(sb), "r"(add), "n"(0x40 | (K << 7)));
  return d;
}
__device__ __forceinline__ constexpr uint64_t dofs(uint32_t off, uint32_t lbo) { return (uint64_t)(off >> 4) | ((uint64_t)(lbo >> 4) << 16); }
#define desc(off, lbo) (dh + dofs(off, lbo))

__device__ __forceinline__ void rs120_0(float* d, const uint32_t* a, uint64_t db){
  asm volatile("{ .reg .pred p; setp.ne.b32 p, 0, 0; wgmma.mma_async.sync.aligned.m64n120k16.f32.bf16.bf16 {%0, %1, %2, %3, %4, %5, %6, %7, %8, %9, %10, %11, %12, %13, %14, %15, %16, %17, %18, %19, %20, %21, %22, %23, %24, %25, %26, %27, %28, %29, %30, %31, %32, %33, %34, %35, %36, %37, %38, %39, %40, %41, %42, %43, %44, %45, %46, %47, %48, %49, %50, %51, %52, %53, %54, %55, %56, %57, %58, %59}, {%60,%61,%62,%63}, %64, p, 1, 1, 1; }"
   : "=f"(d[0]), "=f"(d[1]), "=f"(d[2]), "=f"(d[3]), "=f"(d[4]), "=f"(d[5]), "=f"(d[6]), "=f"(d[7]), "=f"(d[8]), "=f"(d[9]), "=f"(d[10]), "=f"(d[11]), "=f"(d[12]), "=f"(d[13]), "=f"(d[14]), "=f"(d[15]), "=f"(d[16]), "=f"(d[17]), "=f"(d[18]), "=f"(d[19]), "=f"(d[20]), "=f"(d[21]), "=f"(d[22]), "=f"(d[23]), "=f"(d[24]), "=f"(d[25]), "=f"(d[26]), "=f"(d[27]), "=f"(d[28]), "=f"(d[29]), "=f"(d[30]), "=f"(d[31]), "=f"(d[32]), "=f"(d[33]), "=f"(d[34]), "=f"(d[35]), "=f"(d[36]), "=f"(d[37]), "=f"(d[38]), "=f"(d[39]), "=f"(d[40]), "=f"(d[41]), "=f"(d[42]), "=f"(d[43]), "=f"(d[44]), "=f"(d[45]), "=f"(d[46]), "=f"(d[47]), "=f"(d[48]), "=f"(d[49]), "=f"(d[50]), "=f"(d[51]), "=f"(d[52]), "=f"(d[53]), "=f"(d[54]), "=f"(d[55]), "=f"(d[56]), "=f"(d[57]), "=f"(d[58]), "=f"(d[59]) : "r"(a[0]),"r"(a[1]),"r"(a[2]),"r"(a[3]), "l"(db));
}
__device__ __forceinline__ void rs120_1(float* d, const uint32_t* a, uint64_t db){
  asm volatile("{ .reg .pred p; setp.ne.b32 p, 1, 0; wgmma.mma_async.sync.aligned.m64n120k16.f32.bf16.bf16 {%0, %1, %2, %3, %4, %5, %6, %7, %8, %9, %10, %11, %12, %13, %14, %15, %16, %17, %18, %19, %20, %21, %22, %23, %24, %25, %26, %27, %28, %29, %30, %31, %32, %33, %34, %35, %36, %37, %38, %39, %40, %41, %42, %43, %44, %45, %46, %47, %48, %49, %50, %51, %52, %53, %54, %55, %56, %57, %58, %59}, {%60,%61,%62,%63}, %64, p, 1, 1, 1; }"
   : "+f"(d[0]), "+f"(d[1]), "+f"(d[2]), "+f"(d[3]), "+f"(d[4]), "+f"(d[5]), "+f"(d[6]), "+f"(d[7]), "+f"(d[8]), "+f"(d[9]), "+f"(d[10]), "+f"(d[11]), "+f"(d[12]), "+f"(d[13]), "+f"(d[14]), "+f"(d[15]), "+f"(d[16]), "+f"(d[17]), "+f"(d[18]), "+f"(d[19]), "+f"(d[20]), "+f"(d[21]), "+f"(d[22]), "+f"(d[23]), "+f"(d[24]), "+f"(d[25]), "+f"(d[26]), "+f"(d[27]), "+f"(d[28]), "+f"(d[29]), "+f"(d[30]), "+f"(d[31]), "+f"(d[32]), "+f"(d[33]), "+f"(d[34]), "+f"(d[35]), "+f"(d[36]), "+f"(d[37]), "+f"(d[38]), "+f"(d[39]), "+f"(d[40]), "+f"(d[41]), "+f"(d[42]), "+f"(d[43]), "+f"(d[44]), "+f"(d[45]), "+f"(d[46]), "+f"(d[47]), "+f"(d[48]), "+f"(d[49]), "+f"(d[50]), "+f"(d[51]), "+f"(d[52]), "+f"(d[53]), "+f"(d[54]), "+f"(d[55]), "+f"(d[56]), "+f"(d[57]), "+f"(d[58]), "+f"(d[59]) : "r"(a[0]),"r"(a[1]),"r"(a[2]),"r"(a[3]), "l"(db));
}
__device__ __forceinline__ void rs128_0(float* d, const uint32_t* a, uint64_t db){
  asm volatile("{ .reg .pred p; setp.ne.b32 p, 0, 0; wgmma.mma_async.sync.aligned.m64n128k16.f32.bf16.bf16 {%0, %1, %2, %3, %4, %5, %6, %7, %8, %9, %10, %11, %12, %13, %14, %15, %16, %17, %18, %19, %20, %21, %22, %23, %24, %25, %26, %27, %28, %29, %30, %31, %32, %33, %34, %35, %36, %37, %38, %39, %40, %41, %42, %43, %44, %45, %46, %47, %48, %49, %50, %51, %52, %53, %54, %55, %56, %57, %58, %59, %60, %61, %62, %63}, {%64,%65,%66,%67}, %68, p, 1, 1, 1; }"
   : "=f"(d[0]), "=f"(d[1]), "=f"(d[2]), "=f"(d[3]), "=f"(d[4]), "=f"(d[5]), "=f"(d[6]), "=f"(d[7]), "=f"(d[8]), "=f"(d[9]), "=f"(d[10]), "=f"(d[11]), "=f"(d[12]), "=f"(d[13]), "=f"(d[14]), "=f"(d[15]), "=f"(d[16]), "=f"(d[17]), "=f"(d[18]), "=f"(d[19]), "=f"(d[20]), "=f"(d[21]), "=f"(d[22]), "=f"(d[23]), "=f"(d[24]), "=f"(d[25]), "=f"(d[26]), "=f"(d[27]), "=f"(d[28]), "=f"(d[29]), "=f"(d[30]), "=f"(d[31]), "=f"(d[32]), "=f"(d[33]), "=f"(d[34]), "=f"(d[35]), "=f"(d[36]), "=f"(d[37]), "=f"(d[38]), "=f"(d[39]), "=f"(d[40]), "=f"(d[41]), "=f"(d[42]), "=f"(d[43]), "=f"(d[44]), "=f"(d[45]), "=f"(d[46]), "=f"(d[47]), "=f"(d[48]), "=f"(d[49]), "=f"(d[50]), "=f"(d[51]), "=f"(d[52]), "=f"(d[53]), "=f"(d[54]), "=f"(d[55]), "=f"(d[56]), "=f"(d[57]), "=f"(d[58]), "=f"(d[59]), "=f"(d[60]), "=f"(d[61]), "=f"(d[62]), "=f"(d[63]) : "r"(a[0]),"r"(a[1]),"r"(a[2]),"r"(a[3]), "l"(db));
}
__device__ __forceinline__ void rs128_1(float* d, const uint32_t* a, uint64_t db){
  asm volatile("{ .reg .pred p; setp.ne.b32 p, 1, 0; wgmma.mma_async.sync.aligned.m64n128k16.f32.bf16.bf16 {%0, %1, %2, %3, %4, %5, %6, %7, %8, %9, %10, %11, %12, %13, %14, %15, %16, %17, %18, %19, %20, %21, %22, %23, %24, %25, %26, %27, %28, %29, %30, %31, %32, %33, %34, %35, %36, %37, %38, %39, %40, %41, %42, %43, %44, %45, %46, %47, %48, %49, %50, %51, %52, %53, %54, %55, %56, %57, %58, %59, %60, %61, %62, %63}, {%64,%65,%66,%67}, %68, p, 1, 1, 1; }"
   : "+f"(d[0]), "+f"(d[1]), "+f"(d[2]), "+f"(d[3]), "+f"(d[4]), "+f"(d[5]), "+f"(d[6]), "+f"(d[7]), "+f"(d[8]), "+f"(d[9]), "+f"(d[10]), "+f"(d[11]), "+f"(d[12]), "+f"(d[13]), "+f"(d[14]), "+f"(d[15]), "+f"(d[16]), "+f"(d[17]), "+f"(d[18]), "+f"(d[19]), "+f"(d[20]), "+f"(d[21]), "+f"(d[22]), "+f"(d[23]), "+f"(d[24]), "+f"(d[25]), "+f"(d[26]), "+f"(d[27]), "+f"(d[28]), "+f"(d[29]), "+f"(d[30]), "+f"(d[31]), "+f"(d[32]), "+f"(d[33]), "+f"(d[34]), "+f"(d[35]), "+f"(d[36]), "+f"(d[37]), "+f"(d[38]), "+f"(d[39]), "+f"(d[40]), "+f"(d[41]), "+f"(d[42]), "+f"(d[43]), "+f"(d[44]), "+f"(d[45]), "+f"(d[46]), "+f"(d[47]), "+f"(d[48]), "+f"(d[49]), "+f"(d[50]), "+f"(d[51]), "+f"(d[52]), "+f"(d[53]), "+f"(d[54]), "+f"(d[55]), "+f"(d[56]), "+f"(d[57]), "+f"(d[58]), "+f"(d[59]), "+f"(d[60]), "+f"(d[61]), "+f"(d[62]), "+f"(d[63]) : "r"(a[0]),"r"(a[1]),"r"(a[2]),"r"(a[3]), "l"(db));
}
__device__ __forceinline__ void rs160_0(float* d, const uint32_t* a, uint64_t db){
  asm volatile("{ .reg .pred p; setp.ne.b32 p, 0, 0; wgmma.mma_async.sync.aligned.m64n160k16.f32.bf16.bf16 {%0, %1, %2, %3, %4, %5, %6, %7, %8, %9, %10, %11, %12, %13, %14, %15, %16, %17, %18, %19, %20, %21, %22, %23, %24, %25, %26, %27, %28, %29, %30, %31, %32, %33, %34, %35, %36, %37, %38, %39, %40, %41, %42, %43, %44, %45, %46, %47, %48, %49, %50, %51, %52, %53, %54, %55, %56, %57, %58, %59, %60, %61, %62, %63, %64, %65, %66, %67, %68, %69, %70, %71, %72, %73, %74, %75, %76, %77, %78, %79}, {%80,%81,%82,%83}, %84, p, 1, 1, 1; }"
   : "=f"(d[0]), "=f"(d[1]), "=f"(d[2]), "=f"(d[3]), "=f"(d[4]), "=f"(d[5]), "=f"(d[6]), "=f"(d[7]), "=f"(d[8]), "=f"(d[9]), "=f"(d[10]), "=f"(d[11]), "=f"(d[12]), "=f"(d[13]), "=f"(d[14]), "=f"(d[15]), "=f"(d[16]), "=f"(d[17]), "=f"(d[18]), "=f"(d[19]), "=f"(d[20]), "=f"(d[21]), "=f"(d[22]), "=f"(d[23]), "=f"(d[24]), "=f"(d[25]), "=f"(d[26]), "=f"(d[27]), "=f"(d[28]), "=f"(d[29]), "=f"(d[30]), "=f"(d[31]), "=f"(d[32]), "=f"(d[33]), "=f"(d[34]), "=f"(d[35]), "=f"(d[36]), "=f"(d[37]), "=f"(d[38]), "=f"(d[39]), "=f"(d[40]), "=f"(d[41]), "=f"(d[42]), "=f"(d[43]), "=f"(d[44]), "=f"(d[45]), "=f"(d[46]), "=f"(d[47]), "=f"(d[48]), "=f"(d[49]), "=f"(d[50]), "=f"(d[51]), "=f"(d[52]), "=f"(d[53]), "=f"(d[54]), "=f"(d[55]), "=f"(d[56]), "=f"(d[57]), "=f"(d[58]), "=f"(d[59]), "=f"(d[60]), "=f"(d[61]), "=f"(d[62]), "=f"(d[63]), "=f"(d[64]), "=f"(d[65]), "=f"(d[66]), "=f"(d[67]), "=f"(d[68]), "=f"(d[69]), "=f"(d[70]), "=f"(d[71]), "=f"(d[72]), "=f"(d[73]), "=f"(d[74]), "=f"(d[75]), "=f"(d[76]), "=f"(d[77]), "=f"(d[78]), "=f"(d[79]) : "r"(a[0]),"r"(a[1]),"r"(a[2]),"r"(a[3]), "l"(db));
}
__device__ __forceinline__ void rs160_1(float* d, const uint32_t* a, uint64_t db){
  asm volatile("{ .reg .pred p; setp.ne.b32 p, 1, 0; wgmma.mma_async.sync.aligned.m64n160k16.f32.bf16.bf16 {%0, %1, %2, %3, %4, %5, %6, %7, %8, %9, %10, %11, %12, %13, %14, %15, %16, %17, %18, %19, %20, %21, %22, %23, %24, %25, %26, %27, %28, %29, %30, %31, %32, %33, %34, %35, %36, %37, %38, %39, %40, %41, %42, %43, %44, %45, %46, %47, %48, %49, %50, %51, %52, %53, %54, %55, %56, %57, %58, %59, %60, %61, %62, %63, %64, %65, %66, %67, %68, %69, %70, %71, %72, %73, %74, %75, %76, %77, %78, %79}, {%80,%81,%82,%83}, %84, p, 1, 1, 1; }"
   : "+f"(d[0]), "+f"(d[1]), "+f"(d[2]), "+f"(d[3]), "+f"(d[4]), "+f"(d[5]), "+f"(d[6]), "+f"(d[7]), "+f"(d[8]), "+f"(d[9]), "+f"(d[10]), "+f"(d[11]), "+f"(d[12]), "+f"(d[13]), "+f"(d[14]), "+f"(d[15]), "+f"(d[16]), "+f"(d[17]), "+f"(d[18]), "+f"(d[19]), "+f"(d[20]), "+f"(d[21]), "+f"(d[22]), "+f"(d[23]), "+f"(d[24]), "+f"(d[25]), "+f"(d[26]), "+f"(d[27]), "+f"(d[28]), "+f"(d[29]), "+f"(d[30]), "+f"(d[31]), "+f"(d[32]), "+f"(d[33]), "+f"(d[34]), "+f"(d[35]), "+f"(d[36]), "+f"(d[37]), "+f"(d[38]), "+f"(d[39]), "+f"(d[40]), "+f"(d[41]), "+f"(d[42]), "+f"(d[43]), "+f"(d[44]), "+f"(d[45]), "+f"(d[46]), "+f"(d[47]), "+f"(d[48]), "+f"(d[49]), "+f"(d[50]), "+f"(d[51]), "+f"(d[52]), "+f"(d[53]), "+f"(d[54]), "+f"(d[55]), "+f"(d[56]), "+f"(d[57]), "+f"(d[58]), "+f"(d[59]), "+f"(d[60]), "+f"(d[61]), "+f"(d[62]), "+f"(d[63]), "+f"(d[64]), "+f"(d[65]), "+f"(d[66]), "+f"(d[67]), "+f"(d[68]), "+f"(d[69]), "+f"(d[70]), "+f"(d[71]), "+f"(d[72]), "+f"(d[73]), "+f"(d[74]), "+f"(d[75]), "+f"(d[76]), "+f"(d[77]), "+f"(d[78]), "+f"(d[79]) : "r"(a[0]),"r"(a[1]),"r"(a[2]),"r"(a[3]), "l"(db));
}
__device__ __forceinline__ void rs64_0(float* d, const uint32_t* a, uint64_t db){
  asm volatile("{ .reg .pred p; setp.ne.b32 p, 0, 0; wgmma.mma_async.sync.aligned.m64n64k16.f32.bf16.bf16 {%0, %1, %2, %3, %4, %5, %6, %7, %8, %9, %10, %11, %12, %13, %14, %15, %16, %17, %18, %19, %20, %21, %22, %23, %24, %25, %26, %27, %28, %29, %30, %31}, {%32,%33,%34,%35}, %36, p, 1, 1, 1; }"
   : "=f"(d[0]), "=f"(d[1]), "=f"(d[2]), "=f"(d[3]), "=f"(d[4]), "=f"(d[5]), "=f"(d[6]), "=f"(d[7]), "=f"(d[8]), "=f"(d[9]), "=f"(d[10]), "=f"(d[11]), "=f"(d[12]), "=f"(d[13]), "=f"(d[14]), "=f"(d[15]), "=f"(d[16]), "=f"(d[17]), "=f"(d[18]), "=f"(d[19]), "=f"(d[20]), "=f"(d[21]), "=f"(d[22]), "=f"(d[23]), "=f"(d[24]), "=f"(d[25]), "=f"(d[26]), "=f"(d[27]), "=f"(d[28]), "=f"(d[29]), "=f"(d[30]), "=f"(d[31]) : "r"(a[0]),"r"(a[1]),"r"(a[2]),"r"(a[3]), "l"(db));
}
__device__ __forceinline__ void rs64_1(float* d, const uint32_t* a, uint64_t db){
  asm volatile("{ .reg .pred p; setp.ne.b32 p, 1, 0; wgmma.mma_async.sync.aligned.m64n64k16.f32.bf16.bf16 {%0, %1, %2, %3, %4, %5, %6, %7, %8, %9, %10, %11, %12, %13, %14, %15, %16, %17, %18, %19, %20, %21, %22, %23, %24, %25, %26, %27, %28, %29, %30, %31}, {%32,%33,%34,%35}, %36, p, 1, 1, 1; }"
   : "+f"(d[0]), "+f"(d[1]), "+f"(d[2]), "+f"(d[3]), "+f"(d[4]), "+f"(d[5]), "+f"(d[6]), "+f"(d[7]), "+f"(d[8]), "+f"(d[9]), "+f"(d[10]), "+f"(d[11]), "+f"(d[12]), "+f"(d[13]), "+f"(d[14]), "+f"(d[15]), "+f"(d[16]), "+f"(d[17]), "+f"(d[18]), "+f"(d[19]), "+f"(d[20]), "+f"(d[21]), "+f"(d[22]), "+f"(d[23]), "+f"(d[24]), "+f"(d[25]), "+f"(d[26]), "+f"(d[27]), "+f"(d[28]), "+f"(d[29]), "+f"(d[30]), "+f"(d[31]) : "r"(a[0]),"r"(a[1]),"r"(a[2]),"r"(a[3]), "l"(db));
}
__device__ __forceinline__ void rs56_0(float* d, const uint32_t* a, uint64_t db){
  asm volatile("{ .reg .pred p; setp.ne.b32 p, 0, 0; wgmma.mma_async.sync.aligned.m64n56k16.f32.bf16.bf16 {%0, %1, %2, %3, %4, %5, %6, %7, %8, %9, %10, %11, %12, %13, %14, %15, %16, %17, %18, %19, %20, %21, %22, %23, %24, %25, %26, %27}, {%28,%29,%30,%31}, %32, p, 1, 1, 1; }"
   : "=f"(d[0]), "=f"(d[1]), "=f"(d[2]), "=f"(d[3]), "=f"(d[4]), "=f"(d[5]), "=f"(d[6]), "=f"(d[7]), "=f"(d[8]), "=f"(d[9]), "=f"(d[10]), "=f"(d[11]), "=f"(d[12]), "=f"(d[13]), "=f"(d[14]), "=f"(d[15]), "=f"(d[16]), "=f"(d[17]), "=f"(d[18]), "=f"(d[19]), "=f"(d[20]), "=f"(d[21]), "=f"(d[22]), "=f"(d[23]), "=f"(d[24]), "=f"(d[25]), "=f"(d[26]), "=f"(d[27]) : "r"(a[0]),"r"(a[1]),"r"(a[2]),"r"(a[3]), "l"(db));
}
__device__ __forceinline__ void rs56_1(float* d, const uint32_t* a, uint64_t db){
  asm volatile("{ .reg .pred p; setp.ne.b32 p, 1, 0; wgmma.mma_async.sync.aligned.m64n56k16.f32.bf16.bf16 {%0, %1, %2, %3, %4, %5, %6, %7, %8, %9, %10, %11, %12, %13, %14, %15, %16, %17, %18, %19, %20, %21, %22, %23, %24, %25, %26, %27}, {%28,%29,%30,%31}, %32, p, 1, 1, 1; }"
   : "+f"(d[0]), "+f"(d[1]), "+f"(d[2]), "+f"(d[3]), "+f"(d[4]), "+f"(d[5]), "+f"(d[6]), "+f"(d[7]), "+f"(d[8]), "+f"(d[9]), "+f"(d[10]), "+f"(d[11]), "+f"(d[12]), "+f"(d[13]), "+f"(d[14]), "+f"(d[15]), "+f"(d[16]), "+f"(d[17]), "+f"(d[18]), "+f"(d[19]), "+f"(d[20]), "+f"(d[21]), "+f"(d[22]), "+f"(d[23]), "+f"(d[24]), "+f"(d[25]), "+f"(d[26]), "+f"(d[27]) : "r"(a[0]),"r"(a[1]),"r"(a[2]),"r"(a[3]), "l"(db));
}
__device__ __forceinline__ void rs32_0(float* d, const uint32_t* a, uint64_t db){
  asm volatile("{ .reg .pred p; setp.ne.b32 p, 0, 0; wgmma.mma_async.sync.aligned.m64n32k16.f32.bf16.bf16 {%0, %1, %2, %3, %4, %5, %6, %7, %8, %9, %10, %11, %12, %13, %14, %15}, {%16,%17,%18,%19}, %20, p, 1, 1, 1; }"
   : "=f"(d[0]), "=f"(d[1]), "=f"(d[2]), "=f"(d[3]), "=f"(d[4]), "=f"(d[5]), "=f"(d[6]), "=f"(d[7]), "=f"(d[8]), "=f"(d[9]), "=f"(d[10]), "=f"(d[11]), "=f"(d[12]), "=f"(d[13]), "=f"(d[14]), "=f"(d[15]) : "r"(a[0]),"r"(a[1]),"r"(a[2]),"r"(a[3]), "l"(db));
}
__device__ __forceinline__ void rs32_1(float* d, const uint32_t* a, uint64_t db){
  asm volatile("{ .reg .pred p; setp.ne.b32 p, 1, 0; wgmma.mma_async.sync.aligned.m64n32k16.f32.bf16.bf16 {%0, %1, %2, %3, %4, %5, %6, %7, %8, %9, %10, %11, %12, %13, %14, %15}, {%16,%17,%18,%19}, %20, p, 1, 1, 1; }"
   : "+f"(d[0]), "+f"(d[1]), "+f"(d[2]), "+f"(d[3]), "+f"(d[4]), "+f"(d[5]), "+f"(d[6]), "+f"(d[7]), "+f"(d[8]), "+f"(d[9]), "+f"(d[10]), "+f"(d[11]), "+f"(d[12]), "+f"(d[13]), "+f"(d[14]), "+f"(d[15]) : "r"(a[0]),"r"(a[1]),"r"(a[2]),"r"(a[3]), "l"(db));
}
__device__ __forceinline__ void ss64_0(float* d, uint64_t da, uint64_t db){
  asm volatile("{ .reg .pred p; setp.ne.b32 p, 0, 0; wgmma.mma_async.sync.aligned.m64n64k16.f32.bf16.bf16 {%0, %1, %2, %3, %4, %5, %6, %7, %8, %9, %10, %11, %12, %13, %14, %15, %16, %17, %18, %19, %20, %21, %22, %23, %24, %25, %26, %27, %28, %29, %30, %31}, %32, %33, p, 1, 1, 1, 1; }"
   : "=f"(d[0]), "=f"(d[1]), "=f"(d[2]), "=f"(d[3]), "=f"(d[4]), "=f"(d[5]), "=f"(d[6]), "=f"(d[7]), "=f"(d[8]), "=f"(d[9]), "=f"(d[10]), "=f"(d[11]), "=f"(d[12]), "=f"(d[13]), "=f"(d[14]), "=f"(d[15]), "=f"(d[16]), "=f"(d[17]), "=f"(d[18]), "=f"(d[19]), "=f"(d[20]), "=f"(d[21]), "=f"(d[22]), "=f"(d[23]), "=f"(d[24]), "=f"(d[25]), "=f"(d[26]), "=f"(d[27]), "=f"(d[28]), "=f"(d[29]), "=f"(d[30]), "=f"(d[31]) : "l"(da), "l"(db));
}
__device__ __forceinline__ void ss64_1(float* d, uint64_t da, uint64_t db){
  asm volatile("{ .reg .pred p; setp.ne.b32 p, 1, 0; wgmma.mma_async.sync.aligned.m64n64k16.f32.bf16.bf16 {%0, %1, %2, %3, %4, %5, %6, %7, %8, %9, %10, %11, %12, %13, %14, %15, %16, %17, %18, %19, %20, %21, %22, %23, %24, %25, %26, %27, %28, %29, %30, %31}, %32, %33, p, 1, 1, 1, 1; }"
   : "+f"(d[0]), "+f"(d[1]), "+f"(d[2]), "+f"(d[3]), "+f"(d[4]), "+f"(d[5]), "+f"(d[6]), "+f"(d[7]), "+f"(d[8]), "+f"(d[9]), "+f"(d[10]), "+f"(d[11]), "+f"(d[12]), "+f"(d[13]), "+f"(d[14]), "+f"(d[15]), "+f"(d[16]), "+f"(d[17]), "+f"(d[18]), "+f"(d[19]), "+f"(d[20]), "+f"(d[21]), "+f"(d[22]), "+f"(d[23]), "+f"(d[24]), "+f"(d[25]), "+f"(d[26]), "+f"(d[27]), "+f"(d[28]), "+f"(d[29]), "+f"(d[30]), "+f"(d[31]) : "l"(da), "l"(db));
}
__device__ __forceinline__ void rs64_z(float* d, const uint32_t* a, uint64_t db){
  asm volatile("{ .reg .pred p; setp.ne.b32 p, 0, 0; wgmma.mma_async.sync.aligned.m64n64k16.f32.bf16.bf16 {%0, %1, %2, %3, %4, %5, %6, %7, %8, %9, %10, %11, %12, %13, %14, %15, %16, %17, %18, %19, %20, %21, %22, %23, %24, %25, %26, %27, %28, %29, %30, %31}, {%32,%33,%34,%35}, %36, p, 1, 1, 1; }"
   : "+f"(d[0]), "+f"(d[1]), "+f"(d[2]), "+f"(d[3]), "+f"(d[4]), "+f"(d[5]), "+f"(d[6]), "+f"(d[7]), "+f"(d[8]), "+f"(d[9]), "+f"(d[10]), "+f"(d[11]), "+f"(d[12]), "+f"(d[13]), "+f"(d[14]), "+f"(d[15]), "+f"(d[16]), "+f"(d[17]), "+f"(d[18]), "+f"(d[19]), "+f"(d[20]), "+f"(d[21]), "+f"(d[22]), "+f"(d[23]), "+f"(d[24]), "+f"(d[25]), "+f"(d[26]), "+f"(d[27]), "+f"(d[28]), "+f"(d[29]), "+f"(d[30]), "+f"(d[31]) : "r"(a[0]),"r"(a[1]),"r"(a[2]),"r"(a[3]), "l"(db));
}
__device__ __forceinline__ void rs32_z(float* d, const uint32_t* a, uint64_t db){
  asm volatile("{ .reg .pred p; setp.ne.b32 p, 0, 0; wgmma.mma_async.sync.aligned.m64n32k16.f32.bf16.bf16 {%0, %1, %2, %3, %4, %5, %6, %7, %8, %9, %10, %11, %12, %13, %14, %15}, {%16,%17,%18,%19}, %20, p, 1, 1, 1; }"
   : "+f"(d[0]), "+f"(d[1]), "+f"(d[2]), "+f"(d[3]), "+f"(d[4]), "+f"(d[5]), "+f"(d[6]), "+f"(d[7]), "+f"(d[8]), "+f"(d[9]), "+f"(d[10]), "+f"(d[11]), "+f"(d[12]), "+f"(d[13]), "+f"(d[14]), "+f"(d[15]) : "r"(a[0]),"r"(a[1]),"r"(a[2]),"r"(a[3]), "l"(db));
}
__device__ __forceinline__ void sk64_0(float* d, uint64_t da, uint64_t db){
  asm volatile("{ .reg .pred p; setp.ne.b32 p, 0, 0; wgmma.mma_async.sync.aligned.m64n64k16.f32.bf16.bf16 {%0, %1, %2, %3, %4, %5, %6, %7, %8, %9, %10, %11, %12, %13, %14, %15, %16, %17, %18, %19, %20, %21, %22, %23, %24, %25, %26, %27, %28, %29, %30, %31}, %32, %33, p, 1, 1, 0, 1; }"
   : "=f"(d[0]), "=f"(d[1]), "=f"(d[2]), "=f"(d[3]), "=f"(d[4]), "=f"(d[5]), "=f"(d[6]), "=f"(d[7]), "=f"(d[8]), "=f"(d[9]), "=f"(d[10]), "=f"(d[11]), "=f"(d[12]), "=f"(d[13]), "=f"(d[14]), "=f"(d[15]), "=f"(d[16]), "=f"(d[17]), "=f"(d[18]), "=f"(d[19]), "=f"(d[20]), "=f"(d[21]), "=f"(d[22]), "=f"(d[23]), "=f"(d[24]), "=f"(d[25]), "=f"(d[26]), "=f"(d[27]), "=f"(d[28]), "=f"(d[29]), "=f"(d[30]), "=f"(d[31]) : "l"(da), "l"(db));
}
__device__ __forceinline__ void sk64_1(float* d, uint64_t da, uint64_t db){
  asm volatile("{ .reg .pred p; setp.ne.b32 p, 1, 0; wgmma.mma_async.sync.aligned.m64n64k16.f32.bf16.bf16 {%0, %1, %2, %3, %4, %5, %6, %7, %8, %9, %10, %11, %12, %13, %14, %15, %16, %17, %18, %19, %20, %21, %22, %23, %24, %25, %26, %27, %28, %29, %30, %31}, %32, %33, p, 1, 1, 0, 1; }"
   : "+f"(d[0]), "+f"(d[1]), "+f"(d[2]), "+f"(d[3]), "+f"(d[4]), "+f"(d[5]), "+f"(d[6]), "+f"(d[7]), "+f"(d[8]), "+f"(d[9]), "+f"(d[10]), "+f"(d[11]), "+f"(d[12]), "+f"(d[13]), "+f"(d[14]), "+f"(d[15]), "+f"(d[16]), "+f"(d[17]), "+f"(d[18]), "+f"(d[19]), "+f"(d[20]), "+f"(d[21]), "+f"(d[22]), "+f"(d[23]), "+f"(d[24]), "+f"(d[25]), "+f"(d[26]), "+f"(d[27]), "+f"(d[28]), "+f"(d[29]), "+f"(d[30]), "+f"(d[31]) : "l"(da), "l"(db));
}
__device__ __forceinline__ void sk64_z(float* d, uint64_t da, uint64_t db){
  asm volatile("{ .reg .pred p; setp.ne.b32 p, 0, 0; wgmma.mma_async.sync.aligned.m64n64k16.f32.bf16.bf16 {%0, %1, %2, %3, %4, %5, %6, %7, %8, %9, %10, %11, %12, %13, %14, %15, %16, %17, %18, %19, %20, %21, %22, %23, %24, %25, %26, %27, %28, %29, %30, %31}, %32, %33, p, 1, 1, 0, 1; }"
   : "+f"(d[0]), "+f"(d[1]), "+f"(d[2]), "+f"(d[3]), "+f"(d[4]), "+f"(d[5]), "+f"(d[6]), "+f"(d[7]), "+f"(d[8]), "+f"(d[9]), "+f"(d[10]), "+f"(d[11]), "+f"(d[12]), "+f"(d[13]), "+f"(d[14]), "+f"(d[15]), "+f"(d[16]), "+f"(d[17]), "+f"(d[18]), "+f"(d[19]), "+f"(d[20]), "+f"(d[21]), "+f"(d[22]), "+f"(d[23]), "+f"(d[24]), "+f"(d[25]), "+f"(d[26]), "+f"(d[27]), "+f"(d[28]), "+f"(d[29]), "+f"(d[30]), "+f"(d[31]) : "l"(da), "l"(db));
}
__device__ __forceinline__ void sk32_0(float* d, uint64_t da, uint64_t db){
  asm volatile("{ .reg .pred p; setp.ne.b32 p, 0, 0; wgmma.mma_async.sync.aligned.m64n32k16.f32.bf16.bf16 {%0, %1, %2, %3, %4, %5, %6, %7, %8, %9, %10, %11, %12, %13, %14, %15}, %16, %17, p, 1, 1, 0, 1; }"
   : "=f"(d[0]), "=f"(d[1]), "=f"(d[2]), "=f"(d[3]), "=f"(d[4]), "=f"(d[5]), "=f"(d[6]), "=f"(d[7]), "=f"(d[8]), "=f"(d[9]), "=f"(d[10]), "=f"(d[11]), "=f"(d[12]), "=f"(d[13]), "=f"(d[14]), "=f"(d[15]) : "l"(da), "l"(db));
}
__device__ __forceinline__ void sk32_1(float* d, uint64_t da, uint64_t db){
  asm volatile("{ .reg .pred p; setp.ne.b32 p, 1, 0; wgmma.mma_async.sync.aligned.m64n32k16.f32.bf16.bf16 {%0, %1, %2, %3, %4, %5, %6, %7, %8, %9, %10, %11, %12, %13, %14, %15}, %16, %17, p, 1, 1, 0, 1; }"
   : "+f"(d[0]), "+f"(d[1]), "+f"(d[2]), "+f"(d[3]), "+f"(d[4]), "+f"(d[5]), "+f"(d[6]), "+f"(d[7]), "+f"(d[8]), "+f"(d[9]), "+f"(d[10]), "+f"(d[11]), "+f"(d[12]), "+f"(d[13]), "+f"(d[14]), "+f"(d[15]) : "l"(da), "l"(db));
}
__device__ __forceinline__ void sk32_z(float* d, uint64_t da, uint64_t db){
  asm volatile("{ .reg .pred p; setp.ne.b32 p, 0, 0; wgmma.mma_async.sync.aligned.m64n32k16.f32.bf16.bf16 {%0, %1, %2, %3, %4, %5, %6, %7, %8, %9, %10, %11, %12, %13, %14, %15}, %16, %17, p, 1, 1, 0, 1; }"
   : "+f"(d[0]), "+f"(d[1]), "+f"(d[2]), "+f"(d[3]), "+f"(d[4]), "+f"(d[5]), "+f"(d[6]), "+f"(d[7]), "+f"(d[8]), "+f"(d[9]), "+f"(d[10]), "+f"(d[11]), "+f"(d[12]), "+f"(d[13]), "+f"(d[14]), "+f"(d[15]) : "l"(da), "l"(db));
}
template<int N> __device__ __forceinline__ void ssz(float* d, uint64_t da, uint64_t db){
  if constexpr (N==64) sk64_z(d,da,db); else sk32_z(d,da,db);
}
template<int N> __device__ __forceinline__ void rsz(float* d, const uint32_t* a, uint64_t db){
  if constexpr (N==64) rs64_z(d,a,db); else rs32_z(d,a,db);
}
template<int N> __device__ __forceinline__ void ssk(float* d, uint64_t da, uint64_t db, bool first){
  if constexpr (N==64) { if(first) sk64_0(d,da,db); else sk64_1(d,da,db); } else { if(first) sk32_0(d,da,db); else sk32_1(d,da,db); }
}
template<int N> __device__ __forceinline__ void rs(float* d, const uint32_t* a, uint64_t db, bool first){
  if constexpr (N==120) { if(first) rs120_0(d,a,db); else rs120_1(d,a,db); }
  if constexpr (N==128) { if(first) rs128_0(d,a,db); else rs128_1(d,a,db); }
  if constexpr (N==160) { if(first) rs160_0(d,a,db); else rs160_1(d,a,db); }
  if constexpr (N==64) { if(first) rs64_0(d,a,db); else rs64_1(d,a,db); }
  if constexpr (N==56) { if(first) rs56_0(d,a,db); else rs56_1(d,a,db); }
  if constexpr (N==32) { if(first) rs32_0(d,a,db); else rs32_1(d,a,db); }
}

constexpr float LOG2E = 1.4426950408889634f;
#define EPI_TS(x) x
#define TS7(i)
#define TS9(i)
#define TS5(i)
#define TS4(i)
#define BAR(i) (sb + MISC + 8u * (uint32_t)(i))
#define BBARI(k) asm volatile("{ .reg .pred p; setp.ne.u32 p, %0, %1; @p bra B_L; trap; B_L: }" ::"r"(sb), "r"(k) : "memory")
#define BBAR() asm volatile("{ .reg .pred p; setp.ne.u32 p, %0, %1; @p bra B_L; trap; B_L: }" ::"r"(sb), "n"(__LINE__ * 2 + 1) : "memory")

__host__ __device__ constexpr int unitB(int g) { return g == 0 ? 0 : g == 1 ? 3 : g == 2 ? 8 : 14 + 3 * (g - 3); }
__host__ __device__ constexpr int unitC(int g) { return g == 0 ? 11 : g == 1 ? 5 : g == 2 ? 8 : 14 + 3 * (g - 3); }
__host__ __device__ constexpr int unitD(int g) { return g == 0 ? 11 : g == 1 ? 8 : g == 6 ? 3 : 14 + 3 * (g - 2); }
#define OMIN 0
#define AHOLD 4
#define B01DEP XC0
__host__ __device__ constexpr int depB(int g) { return g < 2 ? B01DEP : g == 2 ? XC1 : g == 3 ? EA1 : g == 4 ? EA2 : g == 5 ? EA4 : EA5; }
__host__ __device__ constexpr int depC(int g) { return g == 0 ? KVFREE : EB1 + g - 1; }
__host__ __device__ constexpr int depD(int g) { return g == 0 ? EC0 : g < 6 ? EC0 + g + 1 : LHA; }
__host__ __device__ constexpr int eid(int P, int g) {
  return P == 0 ? (g == 1 ? EA1 : g == 2 ? EA2 : g >= 4 ? EA4 + g - 4 : -1)
       : P == 1 ? (g >= 1 ? EB1 + g - 1 : -1)
       : P == 2 ? EC0 + g
                : (g == 1 ? ED1 : g == 2 ? ED2 : g == 3 ? ED3 : g >= 4 ? ED4 + g - 4 : -1);
}
template <int P> __host__ __device__ constexpr int unitP(int g) { return P == 0 ? 14 + 2 * g : P == 1 ? unitB(g) : P == 2 ? unitC(g) : unitD(g); }
template <typename Fn> __host__ __device__ constexpr uint64_t packtab(Fn f) { uint64_t t = 0; for (int g = 0; g < 7; g++) t |= (uint64_t)f(g) << (8 * g); return t; }

template <int P, int N, typename Fn, typename Fp>
__device__ __forceinline__ void pass1(float* acc, const uint32_t* xf, uint32_t sb, uint32_t pb, bool lane0, uint64_t dh, uint64_t sh, Fn shadow, Fp post) {
#pragma unroll
  for (int g = 0; g < 7; g++) {
    if (P != 1 || g)
    mbar_wait(BAR(FA + 7 * P + g));
    wg_fence();
    if (P == 1 && g == 0) {
#pragma unroll
      for (int kk = 0; kk < 4; kk++) rs<56>(acc + 64, xf + 4 * kk, sh + dofs((unitP<P>(0) + 2) * U + kk * 2048, U), kk == 0);
    } else
#pragma unroll
    for (int kk = 0; kk < 4; kk++) {
      if (P == 1) {
        rs<128>(acc, xf + 16 * g + 4 * kk, desc(unitP<P>(g) * U + kk * 2048, U), g == 0 && kk == 0);
        rs<56>(acc + 64, xf + 16 * g + 4 * kk, sh + dofs((unitP<P>(g) + 2) * U + kk * 2048, U), g == 0 && kk == 0);
      } else {
        rs<N>(acc, xf + 16 * g + 4 * kk, (P == 0 ? sh : dh) + dofs(unitP<P>(g) * U + kk * 2048, U), g == 0 && kk == 0);
      }
    }
    wg_commit();
    shadow(g);
    if (g > 0) {
      wg_wait<1>();
      if (lane0) {
        if (eid(P, g - 1) >= 0) mbar_arrive(BAR(eid(P, g - 1)));
        if ((P == 1 || P == 2) && g == 2) mbar_arrive_remote(pb + MISC + 8u * (PF + P - 1));
        if (P == 3 && g == 1) mbar_arrive_remote(pb + MISC + 8u * (PF + 2));
      }
      post(g);
    }
  }
  wg_wait<0>();
  if (lane0) mbar_arrive(BAR(eid(P, 6)));
  pin<N / 2>(acc);
}

template <int ID> __device__ __forceinline__ void hfrag64(uint32_t* h, float* acc, const float* rs_, uint32_t sb, int wg) {
  const float hr[2] = {0.5f * rs_[0], 0.5f * rs_[1]};
#pragma unroll
  for (int i = 0; i < 32; i++) {
    acc[32 + i] *= acc[i];
    acc[i] *= hr[(i >> 1) & 1];
    if (i < 16) acc[i] = tanh_(acc[i]);
  }
  pin<64>(acc);
  BBARI(ID * 4 + 1);
  EPI_TS(if (ID == 1) CTS(21));
  const float c[2] = {hr[0] * hr[0], hr[1] * hr[1]};
#pragma unroll
  for (int i = 16; i < 32; i++) acc[i] = tanh_(acc[i]);
#pragma unroll
  for (int m = 0; m < 8; m++) h[m] = pack2(acc[32 + 2 * m] * fmaf(acc[2 * m], c[m & 1], c[m & 1]), acc[33 + 2 * m] * fmaf(acc[2 * m + 1], c[m & 1], c[m & 1]));
  pin<16>(acc + 16);
  pinr<8>(h);
  BBARI(ID * 4 + 3);
  EPI_TS(if (ID == 1) CTS(22));
#pragma unroll
  for (int m = 8; m < 16; m++) h[m] = pack2(acc[32 + 2 * m] * fmaf(acc[2 * m], c[m & 1], c[m & 1]), acc[33 + 2 * m] * fmaf(acc[2 * m + 1], c[m & 1], c[m & 1]));
}
__device__ __forceinline__ uint32_t phi2(float e0, float e1, uint32_t r, uint32_t c) {
  uint32_t d;
  asm("{ .reg .b32 m; cvt.rn.bf16x2.f32 m, %2, %1; min.bf16x2 m, m, %5; add.rn.bf16x2 m, m, %6; fma.rn.bf16x2 %0, %3, %4, m; }" : "=r"(d) : "f"(e0), "f"(e1), "r"(r), "r"(c), "r"(0x3F803F80u), "r"(0x35863586u));
  return d;
}
__device__ __forceinline__ uint32_t pack2r(float lo, float hi) { uint32_t r; asm("cvt.rn.relu.bf16x2.f32 %0, %1, %2;" : "=r"(r) : "f"(hi), "f"(lo)); return r; }

template <int NP> __device__ __forceinline__ void send_ll(uint4* dst, const float* a) {
#pragma unroll
  for (int q = 0; q < NP; q++)
    asm volatile("{ .reg .b128 t; .reg .b64 lo, hi; mov.b64 lo, {%1,%2}; mov.b64 hi, {%3,%4}; mov.b128 t, {lo,hi}; st.relaxed.gpu.global.b128 [%0], t; }" ::"l"(dst + q * 32),
                 "r"(pack2(a[8 * q], a[8 * q + 1]) | 1u), "r"(pack2(a[8 * q + 2], a[8 * q + 3])), "r"(pack2(a[8 * q + 4], a[8 * q + 5])), "r"(pack2(a[8 * q + 6], a[8 * q + 7])) : "memory");
}
__device__ __forceinline__ void stg4(uint4* dst, const uint32_t* w) {
  asm volatile("{ .reg .b128 t; .reg .b64 lo, hi; mov.b64 lo, {%1,%2}; mov.b64 hi, {%3,%4}; mov.b128 t, {lo,hi}; st.relaxed.gpu.global.b128 [%0], t; }" ::"l"(dst),
               "r"(w[0]), "r"(w[1]), "r"(w[2]), "r"(w[3]) : "memory");
}
#define LL_LD(g, p, o, a, b, c, d) g "ld.relaxed.gpu.global.v4.b32 {%" #a ",%" #b ",%" #c ",%" #d "}, [%" #p "+" #o "];\n"
#define LL_OPS(c) c(v[0]), c(v[1]), c(v[2]), c(v[3]), c(v[4]), c(v[5]), c(v[6]), c(v[7]), c(v[8]), c(v[9]), c(v[10]), c(v[11]), c(v[12]), c(v[13]), c(v[14]), c(v[15])
__device__ __forceinline__ void ld_ll4(uint32_t* v, const uint4* p, const uint4* p2) {
  asm volatile(LL_LD("", 16, 0, 0, 1, 2, 3) LL_LD("", 16, 512, 4, 5, 6, 7) LL_LD("", 17, 0, 8, 9, 10, 11) LL_LD("", 17, 512, 12, 13, 14, 15) : LL_OPS("=r") : "l"(p), "l"(p2) : "memory");
}
#define LL_CK(q, a, b, c, d) "lop3.b32 t, %" #c ", %" #d ", %49, 0xEA; lop3.b32 t, t, %" #a ", %" #b ", 0x80; and.b32 t, t, 1; setp.ne.u32 " #q ", t, 0; vote.sync.all.pred " #q ", " #q ", 0xffffffff;\n"
#define LL_O16(v) "+r"(v[0]), "+r"(v[1]), "+r"(v[2]), "+r"(v[3]), "+r"(v[4]), "+r"(v[5]), "+r"(v[6]), "+r"(v[7]), "+r"(v[8]), "+r"(v[9]), "+r"(v[10]), "+r"(v[11]), "+r"(v[12]), "+r"(v[13]), "+r"(v[14]), "+r"(v[15])
#define LL_RE3 \
      LL_CK(q, 0, 4, 8, 12) "or.pred z, q, y;\n" \
      LL_LD("@!q ", 48, 0, 0, 1, 2, 3) LL_LD("@!q ", 48, 512, 4, 5, 6, 7) LL_LD("@!z ", 48, 1024, 8, 9, 10, 11) LL_LD("@!z ", 48, 1536, 12, 13, 14, 15) \
      LL_CK(q, 16, 20, 24, 28) "or.pred z, q, y;\n" \
      LL_LD("@!q ", 48, 16384, 16, 17, 18, 19) LL_LD("@!q ", 48, 16896, 20, 21, 22, 23) LL_LD("@!z ", 48, 17408, 24, 25, 26, 27) LL_LD("@!z ", 48, 17920, 28, 29, 30, 31) \
      LL_CK(q, 32, 36, 40, 44) "or.pred z, q, y;\n" \
      LL_LD("@!q ", 48, 32768, 32, 33, 34, 35) LL_LD("@!q ", 48, 33280, 36, 37, 38, 39) LL_LD("@!z ", 48, 33792, 40, 41, 42, 43) LL_LD("@!z ", 48, 34304, 44, 45, 46, 47)
__device__ __forceinline__ void chk_ll(uint32_t (*v)[16], const uint4* p, uint32_t nar) {
  asm volatile(
      "{ .reg .pred p, q, y, z; .reg .b32 t, u, n;\n"
      "mov.u32 n, 0; setp.ne.u32 y, %49, 0;\n"
      "R_L: lop3.b32 t, %0, %4, %16, 0x80; lop3.b32 u, %8, %12, %24, 0x80; lop3.b32 t, t, %20, %32, 0x80; lop3.b32 u, u, %28, %40, 0x80; lop3.b32 t, t, %36, 1, 0x80; lop3.b32 u, u, %44, %49, 0xEA; and.b32 t, t, u;\n"
      "setp.ne.u32 p, t, 0; vote.sync.all.pred p, p, 0xffffffff; @p bra R_D;\n"
      LL_RE3
      "add.u32 n, n, 1; setp.lt.u32 p, n, 262144; @p bra R_L; trap;\n"
      "R_D:\n"
      "}"
      : LL_O16(v[0]), LL_O16(v[1]), LL_O16(v[2])
      : "l"(p), "r"(nar)
      : "memory");
}

template <int NQ> __device__ __forceinline__ void load_x(const __nv_bfloat16* x, uint32_t sb, int r, int warp, int lane) {
  const int l8 = lane >> 3, c = lane & 7;
  const char* src = reinterpret_cast<const char*>(x + (size_t)(r * 128 + warp * 16 + l8) * DM + c * 8);
  const uint32_t dst = sb + (uint32_t)((warp >> 2) * (7 * U) + ((warp & 3) * 16 + l8) * 128 + ((c ^ l8) << 4));
#pragma unroll
  for (int kb = 0; kb < 7; kb++) {
#pragma unroll
    for (int q = 0; q < NQ; q++)
      asm volatile("cp.async.cg.shared.global [%0], [%1], 16;" ::"r"((dst ^ ((q & 1) << 6)) + kb * U + q * 512), "l"(src + q * 4 * DM * 2 + kb * 128) : "memory");
    asm volatile("cp.async.commit_group;" ::: "memory");
  }
}
template <int N> __device__ __forceinline__ void cp_wait() { asm volatile("cp.async.wait_group %0;" ::"n"(N) : "memory"); }

#define ORD 0
#define FETCH 0
#define FD0 (ET + 4)
#define FD1 (ET + 4)
#define FD2 EG3
__device__ __forceinline__ void fetch_slot(uint32_t sb, int slot) {
}

template <int H> __device__ __forceinline__ void w2_tiles(const Maps& M, uint32_t sb, int j) {
  const int kq = j >> 1, n = j & 1;
  const int io = kq == 3 - 3 * n ? 2 : kq - n;
  const int cA = 256 * n + 64 * (io == 2 ? 0 : io + 1), cB = 256 * n + 64 * (io == 0 ? 2 : io - 1);
#pragma unroll 1
  for (int i = 0; i < 4; i++) {
    const uint32_t ut = H == 0 ? (i == 0 ? 0x12103634u : i == 1 ? 0x27252422u : i == 2 ? 0x0C040200u : 0x12103634u)
                               : (i == 0 ? 0x20141E1Cu : i == 1 ? 0x2D2B2A28u : i == 2 ? 0x0D32302Eu : 0x14201E1Cu);
    const uint32_t fb = BAR(FT + (H == 0 ? (0x6520 >> (4 * i)) & 15 : (0x7431 >> (4 * i)) & 15));
    const uint32_t dt = H == 0 ? ED1 | (ED3 << 8) | (LH1 << 16) | ((ET + 0) << 24) : ED2 | (ED4 << 8) | (ED5 << 16) | ((ET + 1) << 24);
    const uint32_t dep = BAR((dt >> (8 * i)) & 255);
    const int pe = i < 2 ? H : i & 1, nn = n ^ pe, fb0 = (j ^ pe) * 224;
    const int r0 = fb0 + 32 * nn, r1 = fb0 + 192 * (1 - nn);
    const CUtensorMap* m = i >= 2 && H == 0 ? &M.w2c : &M.w2a;
    const int c2 = H == 0 ? 192 + 32 * n : 256 * n + 64 * io;
    if (H == 1 || i) mbar_wait(dep);
    tma2d(sb + (ut & 255) * 4096, m, i < 2 ? cA : c2, i == 1 ? r0 + 128 : r0, fb);
    tma2d(sb + ((ut >> 8) & 255) * 4096, i == 1 ? m + 1 : m, i == 0 ? cB : i == 1 ? cA : c2, i == 0 ? r0 : i == 1 ? r1 : r0 + 64, fb);
    if (H == 0 && !i) mbar_wait(dep);
    tma2d(sb + ((ut >> 16) & 255) * 4096, m, i == 0 ? cA : i == 1 ? cB : c2, i == 0 ? r0 + 64 : r0 + 128, fb);
    tma2d(sb + (ut >> 24) * 4096, i == 0 ? m : m + 1, i < 2 ? cB : c2, i == 0 ? r0 + 64 : r1, fb);
    TS(2, 10 + 2 * i + H);
  }
}

#define LANE() const int ln = laneid(), g8 = ln >> 2, t4 = ln & 3; (void)g8; (void)t4
__device__ __forceinline__ void tail(const __nv_bfloat16* x, __nv_bfloat16* out, uint32_t* hf, float* acc, const uint32_t* sg, float* rs_, uint32_t sb, uint32_t pb, int warp, bool lane0) {
  const int wg = warp >> 2, w4 = warp & 3;
  constexpr int BB = 300;
  float a1[64];
  const float hr[2] = {0.5f * rs_[0], 0.5f * rs_[1]}, hc[2] = {hr[0] * hr[0], hr[1] * hr[1]};
  auto e1 = [&](int lo) {
#pragma unroll
    for (int i = lo; i < lo + 16; i++) { acc[32 + i] *= acc[i]; acc[i] = tanh_(acc[i] * hr[(i >> 1) & 1]); }
    pin<16>(acc + lo); pin<16>(acc + 32 + lo);
  };
  auto e2 = [&](int lo) {
#pragma unroll
    for (int m = lo; m < lo + 8; m++) hf[32 + m] = pack2(acc[32 + 2 * m] * fmaf(acc[2 * m], hc[m & 1], hc[m & 1]), acc[33 + 2 * m] * fmaf(acc[2 * m + 1], hc[m & 1], hc[m & 1]));
    pinr<8>(hf + 32 + lo);
  };
  const uint32_t doff = (uint32_t)(wg * 12288 + w4 * 3072 + laneid() * 16);
  auto send = [&](int s) {
    sta4(pb + 11 * U + doff + s * 512, hf + 32 + 4 * s, pb + MISC + 8u * (HF + 4) + wg * 8);
    sta4(pb + 11 * U + doff + s * 512 + 512, hf + 36 + 4 * s, pb + MISC + 8u * (HF + 4) + wg * 8);
  };
  auto e3 = [&]() {
#pragma unroll
    for (int m = 0; m < 8; m++) {
      const int w = m & 1;
      hf[48 + m] = pack2(blo(sg[m]) * (acc[64 + 2 * m] * hr[w]), bhi(sg[m]) * (acc[65 + 2 * m] * hr[w]));
    }
    pinr<8>(hf + 48);
    send(4);
  };
  mbar_wait(BAR(PF + 2));
  e3();
  e1(0);
  BBARI(BB + 1);
  e1(16);
  e2(0); send(0);
  BBARI(BB + 3);
  e2(8); send(2);
  TS7(21);
  uint64_t dh = desc_base<6>(sb, 0);
  mbar_wait(BAR(FT + 0));
  wg_fence();
#pragma unroll
  for (int s = 0; s < 8; s++) rs<128>(a1, hf + 4 * s, desc((s < 4 ? 26 : 7) * U + s * 2048, U), s == 0);
  wg_commit();
  TS7(22);
  mbar_wait(BAR(FT + 1));
  wg_fence();
#pragma unroll
  for (int s = 0; s < 8; s++) rs<128>(a1, hf + 56 + 4 * s, desc((s < 4 ? 14 : 9) * U + s * 2048, s < 4 ? U : 6 * U), false);
  wg_commit();
  TS7(23);
  wg_wait<1>();
  if (lane0) mbar_arrive(BAR(ET + 0));
  mbar_wait(BAR(FT + 2));
  wg_fence();
#pragma unroll
  for (int s = 0; s < 6; s++) rs<128>(a1, hf + 32 + 4 * s, desc(17 * U + s * 2048, 12288), false);
  wg_commit();
  CTS(9);
  uint32_t par;
  asm volatile("ld.shared.u32 %0, [%1];" : "=r"(par) : "r"(BAR(NBAR)) : "memory");
  mbar_wait(BAR(HF + 4) + wg * 8);
#pragma unroll
  for (int s = 0; s < 6; s++) lds4(hf + 88 + 4 * s, sb + 11 * U + doff + s * 512);
  CTS(10);
  wg_wait<1>();
  if (lane0) mbar_arrive(BAR(ET + 1));
  const uint64_t adw = desc_base<5>(sb, wg * 512);
  float aw[32];
  auto wtile = [&](int t) {
    constexpr int wu[7] = {3, 11, 17, 20, ORD ? 0 : 23, ORD ? 26 : 0, !ORD ? 26 : FETCH ? 14 : 23};
    mbar_wait(BAR(FW + t));
    wg_fence();
#pragma unroll
    for (int kk = 0; kk < 4; kk++) {
      const uint64_t da = adw + dofs(wu[t] * U + kk * 32, 16), db = desc((t == (ORD ? 5 : 6) ? 7 : wu[t] + 2) * U + kk * 2048, U);
      ssk<64>(aw, da, db, t == 0 && kk == 0);
    }
    wg_commit();
  };
  float a2[16];
  float* a3 = a1;
  auto g2 = [&](int p, int lo, int hi) {
    wg_fence();
#pragma unroll
    for (int s = lo; s < hi; s++) rs<32>(a2, hf + 56 * p + 4 * s, desc((p ? (s < 8 ? 26 : 6) : (s < 12 ? 0 : 3)) * U + s * 2048, U), p == 0 && s == 0);
    wg_commit();
  };
  auto g3 = [&](int p, int lo, int hi) {
    wg_fence();
#pragma unroll
    for (int s = lo; s < hi; s++) {
      const uint64_t d = desc((p ? (s < 12 ? 14 * U : 7 * U) : (s < 12 ? 23 * U : 3 * U + 4096)) + s * 2048, U);
      if (p == 0 && s == 0) rsz<64>(a3, hf, d); else rs<64>(a3, hf + 56 * p + 4 * s, d, false);
    }
    wg_commit();
  };
  const int bid = par, r = bid >> 3, kq = (bid >> 1) & 3, n = bid & 1;
  const bool Y = kq == 3 - 3 * n;
  auto dest = [&](int c) {
    int b2 = bid;
    asm volatile("" : "+r"(b2));
    const int n2 = b2 & 1, k2 = (b2 >> 1) & 3, i2 = Y ? 2 : k2 - n2;
    const int tgt = c == 0 ? n2 + (i2 == 2 ? 0 : i2 + 1) : c == 1 ? n2 + (i2 == 0 ? 2 : i2 - 1) : Y ? n2 + 2 : 3 - 3 * n2;
    const int slot = c == 2 ? i2 : Y ? 2 : c;
    return g_p + (size_t)((((b2 >> 3) * 2 + n2) * 4 + tgt) * 3072 + slot * 1024 + warp * (c == 2 && !Y ? 64 : 128) + laneid());
  };
#define SORD 0
#define EL0P 1
#define EL1P 3
#define LPX 6
  uint32_t v[3][16], xr[16];
#define LP0 3
#define LP1 4
#define LP2 5
  auto inbox = [&]() {
    int b2 = bid;
    asm volatile("" : "+r"(b2));
    return g_p + (size_t)((((b2 >> 3) * 2 + (b2 & 1)) * 4 + ((b2 >> 1) & 3)) * 3072 + warp * (Y ? 64 : 128) + laneid());
  };
  auto hook = [&](int t) {
    if (t == LP0 || t == LP1 || t == LP2) {
      const uint4* pi = inbox(), *pj = Y ? g_p : pi + 64;
      if (t == LP0) ld_ll4(v[0], pi, pj);
      if (t == LP1) ld_ll4(v[1], pi + 1024, pj + 1024);
      if (t == LP2) ld_ll4(v[2], pi + 2048, pj + 2048);
    }
    if (t == LPX) {
      const int ln = laneid();
      int b2 = bid;
      asm volatile("" : "+r"(b2));
      const uint4* src = reinterpret_cast<const uint4*>(x + (size_t)((b2 >> 3) * 128 + warp * 16 + (ln >> 3)) * DM + (Y ? 192 + 32 * (b2 & 1) : 192 * (b2 & 1) + 32 * (b2 & 6)) + (ln & (Y ? 3 : 7)) * 8);
#pragma unroll
      for (int q = 0; q < 4; q++)
        asm volatile("ld.global.nc.L1::no_allocate.v4.b32 {%0,%1,%2,%3}, [%4];" : "=r"(xr[4 * q]), "=r"(xr[4 * q + 1]), "=r"(xr[4 * q + 2]), "=r"(xr[4 * q + 3]) : "l"(src + q * (4 * DM / 8)) : "memory");
    }
  };
  mbar_wait(BAR(FT + 3));
  wg_fence();
#pragma unroll
  for (int s = 0; s < 6; s++) rs<128>(a1, hf + 88 + 4 * s, desc(20 * U + s * 2048, 12288), false);
  wg_commit();
  if (lane0) mbar_arrive(BAR(LD2));
  mbar_wait(BAR(CLR));
  TS7(26);
  wg_wait<1>();
  if (lane0) mbar_arrive(BAR(ET + 2));
  dh = desc_base<7>(sb, 0);
  mbar_wait(BAR(FT + 5));
  g2(0, 0, 7);
  mbar_wait(BAR(FT + 4));
  wg_wait<1>();
  if (lane0) mbar_arrive(BAR(ET + 3));
  pin<64>(a1);
  TS7(27);
  {
    uint32_t w[16];
#pragma unroll
    for (int i = 0; i < 16; i++) w[i] = pack2(a1[2 * i], a1[2 * i + 1]);
#pragma unroll
    for (int q = 0; q < 4; q++) w[4 * q] |= 1u;
    pinr<16>(w);
    g3(0, 0, 7);
    uint4* const pa = dest(0);
    stg4(pa, w); stg4(pa + 32, w + 4);
    BBARI(BB + 11);
    g3(0, 7, 14);
    stg4(pa + 64, w + 8); stg4(pa + 96, w + 12);
  }
  BBARI(BB + 13);
  TS7(28);
  mbar_wait(BAR(FT + 6));
  g2(0, 7, 14);
  wg_wait<1>();
  if (lane0) mbar_arrive(BAR(ET + 5));
  g2(1, 0, 7);
  send_ll<2>(dest(1), a1 + 32);
  BBARI(BB + 15);
  wg_wait<1>();
  if (lane0) mbar_arrive(BAR(ET + 6));
  mbar_wait(BAR(FT + 7));
  g2(1, 7, 14);
  g3(1, 0, 7);
  send_ll<2>(dest(1) + 64, a1 + 48);
  hook(-2);
  BBARI(BB + 17);
  wg_wait<1>();
  if (lane0) mbar_arrive(BAR(ET + 4));
  pin<16>(a2);
  g3(1, 7, 14);
  hook(-1);
  if (!Y) { send_ll<2>(dest(2), a2); }
  BBARI(BB + 19);
  CTS(16);
  dh = desc_base<8>(sb, 0);
  wtile(0);
  hook(0);
  wg_wait<1>();
  pin<32>(a3);
  CTS(11);
  if (Y) {
    send_ll<4>(dest(2), a3);
#pragma unroll
    for (int i = 0; i < 16; i++) a3[i] = a2[i];
  }
  pin<32>(a3);
  BBARI(BB + 21);
  wtile(1);
  LANE();
  const uint32_t lb = sb + (uint32_t)((3 + wg) * U + w4 * 2048);
  const int row = r * 128 + warp * 16 + (ln >> 3), col = (Y ? 192 + 32 * n : 192 * n + 64 * kq) + (ln & (Y ? 3 : 7)) * 8;
  hook(1);
#pragma unroll
  for (int t = 2; t < 7; t++) {
    wtile(t);
    if (t == 3) CTS(17);
    hook(t);
  }
  wg_wait<5>();
  if (lane0) mbar_arrive_n(BAR(wg ? XR1 : XR0), 2);
  CTS(18);
  uint32_t idm = (g8 >> 1) == t4 ? 0x3F80u << ((g8 & 1) * 16) : 0u;
  pinr<1>(&idm);
  mbar_wait(BAR(wg ? XR1 : XR0));
  CTS(19);
  {
    chk_ll(v, inbox(), Y);
  }
  CTS(20);
  {
#pragma unroll
    for (int b = 0; b < 8; b++)
#pragma unroll
      for (int i = 0; i < 3; i++) mma1688(a3 + 4 * b, v[i][2 * b], v[i][2 * b + 1], idm);
  }
#pragma unroll
  for (int i = 0; i < 32; i++) a3[i] = fmaf(a3[i], tanh_(a3[i]), a3[i]);
  pin<32>(a3);
  wg_wait<0>();
  pin<32>(aw);
  CTS(12);
  const uint32_t sa = lb + (uint32_t)((ln & 15) * 128 + (((ln >> 4) ^ (ln & 7)) << 4));
#pragma unroll
  for (int kk = 0; kk < 4; kk++) {
    uint32_t o[4];
#pragma unroll
    for (int m = 4 * kk; m < 4 * kk + 4; m++) o[m & 3] = pack2(aw[2 * m] * a3[2 * m], aw[2 * m + 1] * a3[2 * m + 1]);
    stsm4(sa ^ (kk << 5), o[0], o[1], o[2], o[3]);
  }
  __syncwarp();
  {
    const int c = ln & 7, l8 = ln >> 3;
    uint4* dst = reinterpret_cast<uint4*>(out + (size_t)row * DM + col);
    uint32_t w[16];
#pragma unroll
    for (int q = 0; q < 4; q++) lds4(w + 4 * q, lb + (uint32_t)((q * 4 + l8) * 128 + ((c ^ ((q * 4 + l8) & 7)) << 4)));
#pragma unroll
    for (int i = 0; i < 16; i++) asm("add.rn.bf16x2 %0, %0, %1;" : "+r"(w[i]) : "r"(xr[i]));
    if (!Y || c < 4) {
#pragma unroll
      for (int q = 0; q < 4; q++) dst[q * (4 * DM / 8)] = make_uint4(w[4 * q], w[4 * q + 1], w[4 * q + 2], w[4 * q + 3]);
    }
  }
}

__global__ void __cluster_dims__(2, 1, 1) __launch_bounds__(384, 1)
fused_kernel(const __grid_constant__ Ptrs P, const __grid_constant__ Maps M) {
  const __nv_bfloat16* xg = (&P.x)[threadIdx.x >> 10];
  asm volatile("{ .reg .pred p; setp.ne.u32 p, %0, 4095; @p bra B_L; trap; B_L: }" ::"r"(threadIdx.x), "l"(xg) : "memory");
  extern __shared__ __align__(1024) uint8_t smem_raw[];
  uint32_t sb = smem_u32(smem_raw);
  asm volatile("" : "+r"(sb));
  const int tid = threadIdx.x;
  const int warp = __shfl_sync(0xffffffffu, tid >> 5, 0);
  const int lane = tid & 31;
  const int wg = warp >> 2;
  const int bid = role_of(blockIdx.x), r = bid >> 3, j = bid & 7, kq = j >> 1, n = j & 1;

  asm volatile("{ .reg .pred p; setp.ne.u32 p, %0, 4095; @p bra B_L; trap; B_L: }" ::"r"(bid) : "memory");
  if (warp < 8) CTS(27);
  if (warp < 4) load_x<HX0>(xg, sb, r, warp, lane);
  if (warp < 8) CTS(28);
  if (elect_one()) {
    if ((warp >> 1) == 4) {
      const uint32_t ba = BAR(FA) + (warp - 8) * 8;
      mbar_init(ba, 1);
      mbar_expect_tx(ba, 2 * U);
      tma3d(sb + (14 + 2 * (warp - 8) + n) * U, &M.kv, j * 56 - 8 * n, (warp - 8) * 64, 1 + n, ba);
      tma3d(sb + (15 + 2 * (warp - 8) - n) * U, &M.kv, j * 56 - 8 * n, (warp - 8) * 64, 2 - n, ba);
    }
    const uint32_t b0 = BAR(2 + 8 * warp), cnt = warp < 6 ? 1u : 8u;
#pragma unroll
    for (int i = 0; i < 8; i++) mbar_init(b0 + 8 * i, cnt);
    if (warp >= 2) { mbar_init(BAR(94 + 2 * warp), 8); mbar_init(BAR(95 + 2 * warp), 8); }
  }
  asm volatile("fence.mbarrier_init.release.cluster;" ::: "memory");
  __syncwarp();
  if (warp < 8) CTS(29);
  asm volatile("barrier.cluster.arrive.relaxed.aligned;" ::: "memory");

  if ((warp & 8) != 0) {
    asm volatile("setmaxnreg.dec.sync.aligned.u32 24;");
    if (warp == 8) {
      asm volatile("barrier.cluster.wait.acquire.aligned;" ::: "memory");
      if (elect_one()) {
        TS(2, 9);
        const int f0 = j * 224, ca = j * 56 - 8 * n;
#pragma unroll 1
        for (int g = 2; g < 7; g++) {
          mbar_expect_tx(BAR(FA + g), 2 * U);
          tma3d(sb + (14 + 2 * g + n) * U, &M.kv, ca, g * 64, 1 + n, BAR(FA + g));
          tma3d(sb + (15 + 2 * g - n) * U, &M.kv, ca, g * 64, 2 - n, BAR(FA + g));
        }
        TS(2, 1);
        const int ro = f0 + 32 * n, rg = f0 + 192 * (1 - n);
#pragma unroll 1
        for (int p = 0; p < 3; p++) {
          const uint64_t ut = p == 0 ? packtab(unitB) : p == 1 ? packtab(unitC) : packtab(unitD);
          const uint64_t dt = p == 0 ? packtab(depB) : p == 1 ? packtab(depC) : packtab(depD);
          const CUtensorMap* m3 = p == 0 ? &M.wq : p == 1 ? &M.w1b : &M.w3b;
          const int c3 = p == 0 ? ca : rg;
#pragma unroll 1
          for (int g = 0; g < 7; g++) {
            const uint32_t dst = sb + (uint32_t)((ut >> (8 * g)) & 255) * U;
            const uint32_t fb = BAR(FB + 7 * p + g);
            mbar_wait_to(BAR((uint32_t)((dt >> (8 * g)) & 255)));
            tma2d(dst, &M.w1a, ro + 64 * p, g * 64, fb);
            tma2d(dst + U, &M.w3a, ro + 64 * p, g * 64, fb);
            tma2d(dst + 2 * U, m3, c3, g * 64, fb);
          }
          TS(2, 2 + p);
        }
        fetch_slot(sb, 2);
        asm volatile("{ .reg .pred p, q; .reg .u32 n; mov.u32 n, 0;\n"
                     "W_L: nanosleep.u32 400; mbarrier.test_wait.parity.shared::cta.b64 p, [%0], 0; mbarrier.test_wait.parity.shared::cta.b64 q, [%1], 0; and.pred p, p, q;\n"
                     "@p bra W_D;\n add.u32 n, n, 1;\n setp.lt.u32 p, n, 2097152;\n @p bra W_L;\n trap;\n W_D: }" ::"r"(BAR(XR0)), "r"(BAR(XR1)) : "memory");
      }
    } else {
      if (elect_one()) {
        const CUtensorMap* mp = &M.kv + (warp - 9) * 4 + 2;
        if ((sb & 0x3FFFFu) != SM_BASE) asm volatile("trap;");
#pragma unroll
        for (int i = 0; i < 4; i++) map_prefetch(mp + i);
        if (warp == 9) map_prefetch(&M.wq);
      }
      const uint32_t ep = g_epoch[blockIdx.x] + 1;
      const int at = tid - 288;
      if (at < 32) reinterpret_cast<float4*>(g_kv + ((ep & 1) ^ 1) * (8 * 2048) + j * 2048 + r * 128)[at] = make_float4(0.f, 0.f, 0.f, 0.f);
      asm volatile("barrier.cluster.wait.acquire.aligned;" ::: "memory");
      float* kv = g_kv + (ep & 1) * (8 * 2048) + j * 2048;
      if (at < 43) {
        const int b = FB + at;
        const uint32_t kb = b < FC ? 24 : b < FT ? 20 : b < FT + 2 ? 32 : b < FT + 4 ? 24 : b == FT + 4 || b == FT + 7 ? 28 : b < FW ? 14 : b < HF ? (kq == 3 - 3 * n ? 20 : 24) - OMIN : b < HF + 4 ? 8 : 12;
        mbar_expect_tx(BAR(b), b == KVL ? KV_BYTES : kb << 10);
      }
      if (lane == 0) asm volatile("st.shared.v2.u32 [%0], {%1, %2};" ::"r"(BAR(NBAR)), "r"(bid), "r"(ep) : "memory");
#define CLP 0
      mbar_wait(BAR(XC1));
      if (warp == 11) {
          const bool isy = kq == 3 - 3 * n;
          uint4* ib = g_p + (size_t)((r * 2 + n) * 4 + kq) * 3072 + lane;
#pragma unroll 1
          for (int i = 0; i < 3; i++, ib += 1024) {
#pragma unroll 4
            for (int q = 0; q < (isy ? 512 : 1024); q += 32) asm volatile("st.relaxed.gpu.global.v4.b32 [%0], {%1,%1,%1,%1};" ::"l"(ib + q), "r"(0) : "memory");
          }
      }
      mbar_wait(BAR(EA6));
      const uint32_t kvm = sb + KVM_U * U;
#pragma unroll 1
      for (int c = at; c < 512; c += 96) {
        const int d = c >> 3, cc = c & 7;
        const bool used = d < 56 && (cc == 7 || (d < 28 ? cc < 4 : (cc >= 3)));
        if (!used) { const uint32_t z[4] = {0, 0, 0, 0}; sts4(kvm + d * 128 + ((cc ^ (d & 7)) << 4), z); }
      }
      if (warp == 9) {
        mbar_wait(BAR(KVST));
        if (elect_one()) {
          asm volatile("cp.reduce.async.bulk.global.shared::cta.bulk_group.add.f32 [%0], [%1], %2;" ::"l"(kv), "r"(sb + 27 * U), "r"(KV_BYTES) : "memory");
          bulk_commit();
          bulk_wait_all();
          TS(3, 4);
          SIGNAL(&g_f1[j * 32]);
          TS(3, 0);
          poll_flag(&g_f1[j * 32], 16u * ep);
          asm volatile("fence.proxy.async.global;" ::: "memory");
          TS(3, 1);
          asm volatile("cp.async.bulk.shared::cluster.global.mbarrier::complete_tx::bytes [%0], [%1], %2, [%3];" ::"r"(sb + 27 * U), "l"(kv), "r"(KV_BYTES), "r"(BAR(KVL)) : "memory");
        }
        __syncwarp();
      }
      {
        auto cv = [](uint32_t* w, const uint32_t* v, bool z01, bool z23) {
          w[0] = z01 ? 0u : pack2(__uint_as_float(v[0]), __uint_as_float(v[1])); w[1] = z01 ? 0u : pack2(__uint_as_float(v[2]), __uint_as_float(v[3]));
          w[2] = z23 ? 0u : pack2(__uint_as_float(v[4]), __uint_as_float(v[5])); w[3] = z23 ? 0u : pack2(__uint_as_float(v[6]), __uint_as_float(v[7]));
        };
        uint32_t v[8], u[8], w[4];
        const uint32_t s0 = sb + 27 * U + (at >> 2) * (KVP * 4) + (at & 3) * 32;
        mbar_wait(BAR(KVL));
        if (at == 0) TS(3, 20);
        lds4(v, s0); lds4(v + 4, s0 + 16);
        lds4(u, s0 + 24 * KVP * 4); lds4(u + 4, s0 + 24 * KVP * 4 + 16);
        int a2 = at;
        asm volatile("" : "+r"(a2));
        const int m = a2 & 3, d0 = a2 >> 2;
        cv(w, v, false, m == 3);
        sts4(kvm + d0 * 128 + ((m ^ (d0 & 7)) << 4), w);
        const bool zi = a2 >= 32;
        const int d2 = zi ? min(a2 - 32, 55) : 48 + d0;
        const uint32_t s2 = sb + 27 * U + d2 * (KVP * 4) + (zi ? 128 : m * 32);
        lds4(v, s2); lds4(v + 4, s2 + (zi ? 0 : 16));
        const int d1 = d0 + 24;
        cv(w, u, d1 >= 28 && m == 0, d1 < 28 && m == 3);
        sts4(kvm + d1 * 128 + (((m + (d1 >= 28 ? 3 : 0)) ^ (d1 & 7)) << 4), w);
        cv(w, v, m == 0, false);
        if (zi) w[0] = w[1] = w[2] = w[3] = pack2(__uint_as_float(v[0]), 0.f) << (d2 >= 28 ? 16 : 0);
        sts4(kvm + d2 * 128 + (((zi ? 7 : m + 3) ^ (d2 & 7)) << 4), w);
        if (at == 0) TS(3, 21);
      }
      fence_async();
      __syncwarp();
      if (lane == 0) mbar_arrive_n(BAR(KVM), warp < 11 ? 3 : 2);
      if (at == 0) TS(3, 2);
      if (warp < 11) {
        const int h = warp - 9;
        const uint32_t pb = mapa(sb, n ^ 1);
#pragma unroll 1
        for (int b = 0; b < 2; b++) {
          const uint32_t off = (uint32_t)((2 * b + (h ? 0 : 3)) * U + lane * 16), dd = b && h ? 5 * U : U, rb = pb + MISC + 8u * (HF + 2 * b + h);
          mbar_wait(BAR(HS + 2 * b + h));
          mbar_wait(BAR(PF + b));
#pragma unroll 1
          for (int i = 0; i < 8192; i += 1024) {
            uint32_t v[8];
            lds4(v, sb + off + i); lds4(v + 4, sb + off + i + 512);
            sta4(pb + dd + off + i, v, rb); sta4(pb + dd + off + i + 512, v + 4, rb);
          }
          if (h == 1 && lane == 0) { TS(3, 22 + b); }
        }
        __syncwarp();
        if (elect_one()) {
          if (h == 0) { mbar_arrive_n(BAR(LHA), 4); w2_tiles<1>(M, sb, j); }
          else { mbar_wait(BAR(OFREE)); w2_tiles<0>(M, sb, j); }
          fetch_slot(sb, h);
        }
      } else {
        if (elect_one()) {
        asm volatile("fence.acq_rel.gpu;" ::: "memory");
#pragma unroll 1
        for (int h = 0; h < 2; h++) {
          mbar_wait(BAR(OST + h));
          tma2d_store(&M.ost, j * 56, r * 128 + h * 64, sb + 27 * U);
          bulk_commit();
          bulk_wait_read();
          mbar_arrive_n(BAR(h ? OFREE : OF0), 8);
          bulk_wait_all();
          SIGNAL(&g_f2[r * 32]);
          TS(3, 24 + h);
        }
        uint32_t ep2;
        asm volatile("ld.shared.u32 %0, [%1];" : "=r"(ep2) : "r"(BAR(NBAR) + 4) : "memory");
        poll_flag(&g_f2[r * 32], 16u * ep2);
        mbar_arrive_n(BAR(CLR), 8);
        asm volatile("fence.proxy.async.global;" ::: "memory");
        TS(3, 5);
        const bool isy = kq == 3 - 3 * n;
        const int co = isy ? 192 + 32 * n : 192 * n + 64 * kq;
#pragma unroll 1
        for (int t = 0; t < 7; t++) {
          const uint64_t dt = (uint64_t)ED6 | ((uint64_t)LD2 << 8) | ((uint64_t)(ET + 2) << 16) | ((uint64_t)(ET + 3) << 24) | ((uint64_t)(ET + 5) << 32) |
                              ((uint64_t)(ET + 6) << 40) | ((uint64_t)(FETCH ? EG3 : ET + 4) << 48);
          const uint32_t dst = sb + (uint32_t)(((!ORD ? 0x1A001714110B03ull : FETCH ? 0x0E1A0014110B03ull : 0x171A0014110B03ull) >> (8 * t)) & 255) * U;
          mbar_wait(BAR((uint32_t)((dt >> (8 * t)) & 255)));
          tma2d(dst, &M.o, t * 64, r * 128, BAR(FW + t));
          tma2d(t == (ORD ? 5 : 6) ? sb + 7 * U : dst + 2 * U, isy ? &M.wob : &M.woa, co, t * 64, BAR(FW + t));
          TS(3, 10 + t);
        }
        uint32_t bx;
        asm volatile("mov.u32 %0, %%ctaid.x;" : "=r"(bx));
        g_epoch[bx] = ep2;
        TS(3, 6);
        }
      }
    }
  } else {
    asm volatile("setmaxnreg.inc.sync.aligned.u32 240;");
    asm volatile("barrier.cluster.wait.acquire.aligned;" ::: "memory");
    CTS(0);
    if (wg == 1) load_x<HX1>(xg, sb, r, warp, lane);
    const int w4 = warp & 3;
    const bool lane0 = lane == 0;
    const uint32_t pb = mapa(sb, n ^ 1);
    const uint32_t so = sb + (uint32_t)((wg * 64 + w4 * 16 + (lane & 7) + ((lane >> 3) & 1) * 8) * 128 + (((lane >> 4) ^ (lane & 7)) << 4));
    uint32_t xf[112];
    float rs_[2];
    uint32_t pm0, pm1;
    float q0, q1;
    {
      float cm[2][4], ga[2][4], gb[2][4];
#pragma unroll
      for (int i = 0; i < 8; i++) cm[i >> 2][i & 3] = ga[i >> 2][i & 3] = gb[i >> 2][i & 3] = 0.f;
      const uint32_t sx = so + wg * (6 * U);
      uint32_t s0 = 0, s1 = 0;
#pragma unroll
      for (int kb = 0; kb < 7; kb++) {
        if (kb == 0) cp_wait<6>(); else if (kb == 1) cp_wait<5>(); else if (kb == 2) cp_wait<4>(); else if (kb == 3) cp_wait<3>();
        else if (kb == 4) cp_wait<2>(); else if (kb == 5) cp_wait<1>(); else cp_wait<0>();
        __syncwarp();
        if (kb == 0) CTS(14);
        EPI_TS(if (kb == 3) CTS(26));
        if (kb == 6) CTS(15);
#pragma unroll
        for (int kk = 0; kk < 4; kk++) ldsm4(xf + 16 * kb + 4 * kk, (sx ^ (kk << 5)) + kb * U);
#pragma unroll
        for (int kk = 0; kk < 4; kk++) mma16816(cm[kk & 1], xf + 16 * kb + 4 * kk, 0x3F803F80u, 0x3F803F80u);
        if (kb == 0) {
          s0 = __byte_perm(__shfl_sync(0xffffffffu, xf[0], lane & 28), 0, 0x1010);
          s1 = __byte_perm(__shfl_sync(0xffffffffu, xf[1], lane & 28), 0, 0x1010);
        }
        if (kb == 6) {
          const float m0 = (cm[0][0] + cm[1][0]) * (1.0f / 448.0f), m1 = (cm[0][2] + cm[1][2]) * (1.0f / 448.0f);
          pm0 = pack2(m0, m0); pm1 = pack2(m1, m1);
          q0 = m0 - blo(s0); q1 = m1 - blo(s1);
          __syncwarp();
          if (lane0) mbar_arrive_n(BAR(XC0) + wg * 8, 2);
        }
#pragma unroll
        for (int kk = 0; kk < 4; kk++) {
          const uint32_t* a = xf + 16 * kb + 4 * kk;
          uint32_t t[4];
#pragma unroll
          for (int i = 0; i < 4; i++) asm volatile("sub.rn.bf16x2 %0, %1, %2;" : "=r"(t[i]) : "r"(a[i]), "r"((i & 1) ? s1 : s0));
          mma16816(ga[kk & 1], t, t[0], t[2]);
          mma16816(gb[kk & 1], t, t[1], t[3]);
        }
      }
#pragma unroll
      for (int i = 0; i < 16; i++) asm volatile("sub.rn.bf16x2 %0, %0, %1;" : "+r"(xf[i]) : "r"((i & 1) ? pm1 : pm0));
      const bool odd = (lane >> 2) & 1;
      rs_[0] = odd ? ga[0][1] + ga[1][1] : ga[0][0] + ga[1][0];
      rs_[1] = odd ? gb[0][3] + gb[1][3] : gb[0][2] + gb[1][2];
    }
    CTS(1);
    uint32_t pq[14];
    {
      float acc[60];
      if (wg) mbar_wait(BAR(XH));
      pass1<0, 120>(acc, xf, sb, pb, lane0, 0, desc_base<0>(sb, n), [&](int g) {
        if (g < 6) {
#pragma unroll
          for (int i = 0; i < 16; i++) asm volatile("sub.rn.bf16x2 %0, %0, %1;" : "+r"(xf[16 * g + 16 + i]) : "r"((i & 1) ? pm1 : pm0));
        }
        if (g == 1) {
          const int src = (lane & 28) | (lane >> 3);
          const float v0 = fmaxf(fmaf(__shfl_sync(0xffffffffu, rs_[0], src), 1.0f / 448.0f, -q0 * q0), 0.f);
          const float v1 = fmaxf(fmaf(__shfl_sync(0xffffffffu, rs_[1], src), 1.0f / 448.0f, -q1 * q1), 0.f);
          rs_[0] = rcp(bfr(sqrt_(bfr(bfr(v0) + 1e-5f))));
          rs_[1] = rcp(bfr(sqrt_(bfr(bfr(v1) + 1e-5f))));
          pin<2>(rs_);
        }
      }, [&](int g) {
        if (g == AHOLD && lane0 && wg == 0) mbar_arrive_n(BAR(XH), 2);
      });
      CTS(2);
      LANE();
      uint32_t pk[16], pv[16];
      float e[28];
      {
        const float rl[2] = {rs_[0] * LOG2E, rs_[1] * LOG2E};
#pragma unroll
        for (int i = 0; i < 28; i++) e[i] = ex2(acc[i] * rl[(i >> 1) & 1]);
#pragma unroll
        for (int m = 0; m < 14; m++) pk[m] = pack2r(acc[2 * m] * rs_[m & 1], acc[2 * m + 1] * rs_[m & 1]);
        pin<28>(e); pinr<14>(pk);
      }
#pragma unroll
      for (int m = 0; m < 14; m++) pv[m] = pack2(acc[32 + 2 * m] * rs_[m & 1], acc[33 + 2 * m] * rs_[m & 1]);
      pv[14] = pv[15] = t4 == 0 ? 0x3F803F80u : 0u;
      pinr<16>(pv);
      TS4(21);
      mbar_wait(BAR(XC1));
      TS4(22);
#pragma unroll
      for (int kk = 0; kk < 4; kk++) stsm4((so ^ (kk << 5)) + 11 * U, pv[4 * kk], pv[4 * kk + 1], pv[4 * kk + 2], pv[4 * kk + 3]);
#pragma unroll
      for (int m = 0; m < 14; m++) pk[m] = phi2(e[2 * m], e[2 * m + 1], pk[m], 0x3F803F80u);
      pk[14] = pk[15] = 0u;
#pragma unroll
      for (int kk = 0; kk < 4; kk++) stsm4((so ^ (kk << 5)) + 6 * U, pk[4 * kk], pk[4 * kk + 1], pk[4 * kk + 2], pk[4 * kk + 3]);
      TS4(23);
      fence_async();
      __syncwarp();
      if (lane0) mbar_arrive(BAR(PKST));
      TS4(24);
      CTS(3);
    }
    const uint32_t hoff = (uint32_t)((wg ? 0 : 3 * U) + w4 * 2048 + laneid() * 16);
    {
      float acc[92];
      auto kvout = [&](float* kv) {
          wg_wait<1>();
          if (lane0 && wg) mbar_arrive_n(BAR(KVFREE), 2);
          pin<32>(kv);
          TS4(26);
          LANE();
#pragma unroll
          for (int h = 0; h < 2; h++) {
            const int d = w4 * 16 + g8 + 8 * h + (KVOV == 4 ? 64 - 64 * wg : 0);
            const uint32_t lim = d < 28 ? 0u : d < 56 ? 28u : 1000u;
            const uint32_t ka = sb + 27 * U + (uint32_t)d * (KVP * 4) + (uint32_t)(2 * t4) * 4 - (d < 28 ? 0u : 96u);
#pragma unroll
            for (int i = 0; i < 7; i++)
              asm volatile("{ .reg .pred p; setp.lt.u32 p, %0, 28; @p st.shared.v2.f32 [%1], {%2,%3}; }" ::"r"((uint32_t)(8 * i + 2 * t4) - lim), "r"(ka + 32 * i), "f"(kv[4 * i + 2 * h]), "f"(kv[4 * i + 2 * h + 1]) : "memory");
            asm volatile("{ .reg .pred p; setp.lt.u32 p, %0, 56; @p st.shared.f32 [%1], %2; }" ::"r"((uint32_t)(d + 64 * t4)), "r"(sb + 27 * U + (uint32_t)d * (KVP * 4) + 128), "f"(kv[28 + 2 * h]) : "memory");
          }
          TS4(27);
          fence_async();
          __syncwarp();
          if (lane0 && wg) mbar_arrive_n(BAR(KVST), 2);
      };
      {
        const uint64_t dh = desc_base<11>(sb, 0);
        if (wg == 1) {
          float kv[32];
          mbar_wait(BAR(PKST));
          wg_fence();
#pragma unroll
          for (int ks = 0; ks < 8; ks++) {
            if (ks == 0) ss64_0(kv, desc(6 * U, U), desc(11 * U, U));
            else ss64_1(kv, desc(6 * U + ks * 2048, U), desc(11 * U + ks * 2048, U));
          }
          wg_commit();
          mbar_wait(BAR(FB));
          wg_fence();
#pragma unroll
          for (int kk = 0; kk < 4; kk++) rs<128>(acc, xf + 4 * kk, desc(unitB(0) * U + kk * 2048, U), kk == 0);
          wg_commit();
          kvout(kv);
          if (KVOV == 3) { wg_wait<0>(); pin<64>(acc); }
        } else {
          mbar_wait(BAR(FB));
          wg_fence();
#pragma unroll
          for (int kk = 0; kk < 4; kk++) rs<128>(acc, xf + 4 * kk, desc(unitB(0) * U + kk * 2048, U), kk == 0);
          wg_commit();
          if (KVOV == 3) { wg_wait<0>(); pin<64>(acc); }
        }
      }

      pass1<1, 184>(acc, xf, sb, pb, lane0, desc_base<1>(sb, 0), desc_base<2>(sb, n), [&](int) {}, [&](int g) {
      });
      CTS(4);
      pin<2>(rs_);
      uint32_t h[16];
      hfrag64<1>(h, acc, rs_, sb, wg);
      pinr<16>(h);
      mbar_wait(BAR(EB1));
      EPI_TS(CTS(23));
#pragma unroll
      for (int s = 0; s < 4; s++) sts4(sb + hoff + s * 512, h + 4 * s);
      __syncwarp();
      if (lane0) mbar_arrive_n(BAR(HS) + wg * 8, 2);
      EPI_TS(CTS(24));
      float e[28];
      {
        const float rl[2] = {rs_[0] * LOG2E, rs_[1] * LOG2E};
#pragma unroll
        for (int i = 0; i < 28; i++) e[i] = ex2(acc[64 + i] * rl[(i >> 1) & 1]);
#pragma unroll
        for (int m = 0; m < 14; m++) pq[m] = pack2r(acc[64 + 2 * m] * rs_[m & 1], acc[65 + 2 * m] * rs_[m & 1]);
        pin<28>(e); pinr<14>(pq);
      }
      EPI_TS(CTS(25));
#pragma unroll
      for (int m = 0; m < 14; m++) pq[m] = phi2(e[2 * m], e[2 * m + 1], pq[m], 0x3F803F80u);
      pq[12] ^= sb; pq[13] ^= sb;
      pinr<14>(pq);
      CTS(5);
    }
    uint32_t sg[8];
    {
      float acc[80];
      pass1<2, 160>(acc, xf, sb, pb, lane0, desc_base<3>(sb, 0), 0, [&](int) {}, [&](int) {});
      CTS(6);
      pin<2>(rs_);
      uint32_t h[16];
      hfrag64<2>(h, acc, rs_, sb, wg);
      pinr<16>(h);
      TS5(21);
      mbar_wait(BAR(EC0 + 1));
      TS5(22);
#pragma unroll
      for (int s = 0; s < 4; s++) sts4(sb + 2 * U + hoff + s * 512, h + 4 * s);
      __syncwarp();
      if (lane0) mbar_arrive_n(BAR(HS + 2) + wg * 8, 2);
      float nm[32];
      TS5(23);
      mbar_wait(BAR(KVM));
      TS5(24);
      {
        uint32_t q3[4];
        const uint64_t dh = desc_base<10>(sb, 0);
        asm volatile("xor.b32 %0, %4, %6; xor.b32 %1, %5, %6; mov.b32 %2, 0; mov.b32 %3, 0;" : "=r"(q3[0]), "=r"(q3[1]), "=r"(q3[2]), "=r"(q3[3]) : "r"(pq[12]), "r"(pq[13]), "r"(sb));
        wg_fence();
        rs64_0(nm, pq, desc(KVM_U * U, U));
        rs64_1(nm, pq + 4, desc(KVM_U * U + 2048, U));
        rs64_1(nm, pq + 8, desc(KVM_U * U + 4096, U));
        rs64_1(nm, q3, desc(KVM_U * U + 6144, U));
      }
      wg_commit();
      float th[16];
      {
        const float hr[2] = {0.5f * rs_[0], 0.5f * rs_[1]};
#pragma unroll
        for (int i = 0; i < 16; i++) { acc[64 + i] *= hr[(i >> 1) & 1]; th[i] = tanh_(acc[64 + i]); }
        pin<16>(th); pin<16>(acc + 64);
      }
#pragma unroll
      for (int m = 0; m < 8; m++) sg[m] = pack2(fmaf(acc[64 + 2 * m], th[2 * m], acc[64 + 2 * m]), fmaf(acc[65 + 2 * m], th[2 * m + 1], acc[65 + 2 * m]));
      pinr<8>(sg);
      wg_wait<0>();
      pin<32>(nm);
      TS5(25);
      LANE();
      float rd[4];
#pragma unroll
      for (int i = 0; i < 4; i++) rd[i] = rcp(nm[28 + i] + 1e-6f);
      uint32_t ob[14];
#pragma unroll
      for (int i = 0; i < 7; i++) {
        const bool h0 = i < 3 || (i == 3 && t4 < 2);
        const float ra = h0 ? rd[0] : rd[1], rb = h0 ? rd[2] : rd[3];
        ob[2 * i] = pack2(nm[4 * i] * ra, nm[4 * i + 1] * ra);
        ob[2 * i + 1] = pack2(nm[4 * i + 2] * rb, nm[4 * i + 3] * rb);
      }
      pinr<14>(ob);
      TS5(26);
      if (wg) mbar_wait(BAR(OF0));
      const uint32_t sa = sb + 27 * U + (uint32_t)(w4 * 16 + (ln & 15)) * 112;
#pragma unroll
      for (int kk = 0; kk < 3; kk++) stsm4(sa + (ln >> 4) * 16 + kk * 32, ob[4 * kk], ob[4 * kk + 1], ob[4 * kk + 2], ob[4 * kk + 3]);
      stsm2(sa + 96, ob[12], ob[13]);
      TS5(27);
      fence_async();
      __syncwarp();
      if (lane0) mbar_arrive_n(BAR(OST) + wg * 8, 2);
      CTS(7);
    }
    uint32_t hf[112];
    float acc[80];
    pass1<3, 160>(acc, xf, sb, pb, lane0, desc_base<4>(sb, 0), 0, [&](int g) {
      if (g >= 5) {
        uint32_t one;
        if (g == 5) {
          BBARI(101);
          asm volatile("{ .reg .b32 t; lop3.b32 t, %1, %2, %3, 0xFE; lop3.b32 t, t, %4, %5, 0xFE; lop3.b32 t, t, %6, %7, 0xFE; lop3.b32 t, t, %8, %9, 0xFE; lop3.b32 t, t, %10, %11, 0xFE;\n"
                       "lop3.b32 t, t, %12, 1, 0xFE; redux.sync.min.u32 t, t, 0xffffffff; min.u32 %0, t, 1; }"
                       : "=r"(one) : "r"(hf[0]), "r"(hf[4]), "r"(hf[8]), "r"(hf[12]), "r"(hf[16]), "r"(hf[20]), "r"(hf[24]), "r"(hf[28]), "r"(hf[56]), "r"(hf[60]), "r"(hf[64]), "r"(hf[68]));
          if (lane0 && wg == 0) mbar_arrive_n(BAR(LHA), one);
        } else {
          BBARI(103);
          asm volatile("{ .reg .b32 t; lop3.b32 t, %1, %2, %3, 0xFE; lop3.b32 t, t, %4, 1, 0xFE; redux.sync.min.u32 t, t, 0xffffffff; min.u32 %0, t, 1; }"
                       : "=r"(one) : "r"(hf[72]), "r"(hf[76]), "r"(hf[80]), "r"(hf[84]));
          if (lane0) mbar_arrive_n(BAR(LH1), one);
        }
      }
      if (g >= 2 && g < 6) {
        const int b = (g >> 1) - 1, pe = g & 1;
        uint32_t* d = hf + 56 * pe + 16 * b;
        if (pe) mbar_wait(BAR(HF + 2 * b) + wg * 8);
#pragma unroll
        for (int s = 0; s < 4; s++) lds4t(d + 4 * s, xf + 16 * (g - 2) + 4 * s, sb + (pe ? (b ? 3 * U + wg * (4 * U) : U) : 2 * b * U) + hoff + s * 512);
        pinr<16>(d);
      }
    }, [&](int) {});
    CTS(8);
    tail(P.x, P.out, hf, acc, sg, rs_, sb, pb, warp, lane0);
    CTS(13);
    if ((tid & 127) == 0) { GTS(wg, 30); TSDUMP(wg); if (wg == 1) { TSDUMP(3); } }
  }
}

typedef CUresult (*EncodeFn)(CUtensorMap*, CUtensorMapDataType, cuuint32_t, void*, const cuuint64_t*, const cuuint64_t*, const cuuint32_t*,
                             const cuuint32_t*, CUtensorMapInterleave, CUtensorMapSwizzle, CUtensorMapL2promotion, CUtensorMapFloatOOBfill);

void make_map(EncodeFn enc, CUtensorMap* m, const void* base, uint64_t cols, uint64_t rows, uint32_t bc, uint32_t br, bool sw) {
  cuuint64_t dims[2] = {cols, rows}, str[1] = {cols * 2};
  cuuint32_t box[2] = {bc, br}, es[2] = {1, 1};
  enc(m, CU_TENSOR_MAP_DATA_TYPE_BFLOAT16, 2, const_cast<void*>(base), dims, str, box, es, CU_TENSOR_MAP_INTERLEAVE_NONE,
      sw ? CU_TENSOR_MAP_SWIZZLE_128B : CU_TENSOR_MAP_SWIZZLE_NONE, CU_TENSOR_MAP_L2_PROMOTION_L2_128B, CU_TENSOR_MAP_FLOAT_OOB_FILL_NONE);
}
void make_map3(EncodeFn enc, CUtensorMap* m, const void* base, uint64_t sec, uint64_t nsec, uint64_t rows, uint32_t bc, uint32_t br, uint32_t bs) {
  cuuint64_t dims[3] = {sec, rows, nsec}, str[2] = {sec * nsec * 2, sec * 2};
  cuuint32_t box[3] = {bc, br, bs}, es[3] = {1, 1, 1};
  enc(m, CU_TENSOR_MAP_DATA_TYPE_BFLOAT16, 3, const_cast<void*>(base), dims, str, box, es, CU_TENSOR_MAP_INTERLEAVE_NONE,
      CU_TENSOR_MAP_SWIZZLE_128B, CU_TENSOR_MAP_L2_PROMOTION_L2_128B, CU_TENSOR_MAP_FLOAT_OOB_FILL_NONE);
}

}

extern "C" void kernel_launch(void* const* d_in, const int* in_sizes, int n_in, void* d_out, int out_size) {
  (void)in_sizes; (void)n_in; (void)out_size;
  void* fn = nullptr;
  cudaDriverEntryPointQueryResult q;
  cudaGetDriverEntryPoint("cuTensorMapEncodeTiled", &fn, cudaEnableDefault, &q);
  EncodeFn enc = (EncodeFn)fn;
  void* op = nullptr;
  cudaGetSymbolAddress(&op, g_o);
  Maps M;
  make_map3(enc, &M.kv, d_in[1], DM, 3, DM, 64, 64, 1);
  make_map(enc, &M.wq, d_in[1], 3 * DM, DM, 64, 64, true);
  make_map(enc, &M.w1a, d_in[4], FF, DM, 64, 64, true);
  make_map(enc, &M.w3a, d_in[5], FF, DM, 64, 64, true);
  make_map(enc, &M.w1b, d_in[4], FF, DM, 32, 64, true);
  make_map(enc, &M.w3b, d_in[5], FF, DM, 32, 64, true);
  make_map(enc, &M.w2a, d_in[6], DM, FF, 64, 64, true);
  make_map(enc, &M.w2b, d_in[6], DM, FF, 64, 32, true);
  make_map(enc, &M.w2c, d_in[6], DM, FF, 32, 64, true);
  make_map(enc, &M.w2d, d_in[6], DM, FF, 32, 32, true);
  make_map(enc, &M.woa, d_in[2], DM, DM, 64, 64, true);
  make_map(enc, &M.wob, d_in[2], DM, DM, 32, 64, true);
  make_map(enc, &M.o, op, DM, SEQ, 64, 128 - OMIN * 8, true);
  make_map(enc, &M.ost, op, DM, SEQ, 56, 64, false);
  cudaFuncSetAttribute(fused_kernel, cudaFuncAttributeMaxDynamicSharedMemorySize, (int)SMEM_BYTES);
  Ptrs P;
  P.x = (const __nv_bfloat16*)d_in[0]; P.wo = (const __nv_bfloat16*)d_in[2];
  P.out = (__nv_bfloat16*)d_out;
  P.wqkv = (const __nv_bfloat16*)d_in[1];
  P.w1 = (const __nv_bfloat16*)d_in[4]; P.w3 = (const __nv_bfloat16*)d_in[5]; P.w2 = (const __nv_bfloat16*)d_in[6];
  fused_kernel<<<128, 384, SMEM_BYTES>>>(P, M);
}
```

```cpp
#include <cuda_runtime.h>
#include <cuda.h>
#include <cuda_bf16.h>
#include <stdint.h>

namespace {

constexpr int SEQ = 2048, DM = 448, FF = 1792;
constexpr uint32_t U = 8192;
constexpr uint32_t SM_BASE = 1024;
constexpr uint32_t MISC = 28 * U;
constexpr uint32_t SMEM_BYTES = 28 * U + 3072;
constexpr uint32_t KVM_U = 26;

enum : int { FA = 0, FB = 7, FC = 14, FD = 21, FT = 28, FW = 36, HF = 43, KVL = 49,
             LH0 = 50, LH1, EA1 = 52, EA2, EA4, EA5, EA6, EB1 = 57, EC0 = 63, ED1 = 70, OF0, ED4, ED5, ED6, ET = 75,
             PKST = 83, LD2, PF = 85, EW0 = 88, XC0, XC1, KVST, OST = 92, KVM = 94, OFREE, XR0, KVFREE, ED2 = 98, ED3, LHA, XH, FIN = 102, XG = 104, XR1 = 105, CLR = 106, INB = 107, EG3 = 109, EL0 = 110, HS = 112, NBAR = 118 };
constexpr int KVP = 36;
constexpr uint32_t KV_BYTES = 56 * KVP * 4;

struct Maps { CUtensorMap kv, wq, w1a, w3a, w1b, w3b, w2a, w2b, w2c, w2d, woa, wob, o, ost; };

struct Ptrs { const __nv_bfloat16* x; __nv_bfloat16* out; const __nv_bfloat16 *wo, *w1, *w3, *w2, *wqkv; };

__device__ __forceinline__ int role_of(int b) {
  int r;
  asm("{ .reg .pred p, q, z; .reg .b32 c, t, k, u, v, w;\n"
      "shr.u32 c, %1, 1; setp.lt.u32 p, c, 36; setp.lt.u32 q, c, 4;\n"
      "sub.u32 t, c, 35; mad.lo.u32 k, c, 37, -1332; shr.u32 k, k, 8; mad.lo.u32 u, k, -7, t;\n"
      "sub.u32 t, c, 4; shr.u32 v, t, 3; and.b32 t, t, 7; selp.b32 k, v, k, p; selp.b32 u, t, u, p; selp.b32 u, 0, u, q;\n"
      "setp.lt.u32 z, u, 2; and.b32 t, u, 1; mad.lo.u32 t, k, 2, t; add.u32 v, k, 12; add.u32 w, t, 4; selp.b32 v, w, v, p; selp.b32 v, c, v, q;\n"
      "selp.b32 w, 0, 8, p; add.u32 w, w, t; selp.b32 v, v, w, z;\n"
      "and.b32 u, u, 6; and.b32 t, %1, 1; or.b32 u, u, t; mad.lo.u32 %0, v, 8, u; }" : "=r"(r) : "r"(b));
  return r;
}

__device__ uint32_t g_epoch[128];
__device__ uint32_t g_f1[8 * 32];
__device__ uint32_t g_f2[16 * 32];
__device__ __align__(128) float g_kv[2 * 8 * 2048];
__device__ __nv_bfloat16 g_o[SEQ * DM];
__device__ uint4 g_p[16 * 2 * 4 * 3 * 1024];
#define TS(role, i)
#define GTS(role, i)
#define CTS(i)
#define TSDUMP(role)

__device__ __forceinline__ uint32_t smem_u32(const void* p) { return (uint32_t)__cvta_generic_to_shared(p); }
__device__ __forceinline__ void mbar_init(uint32_t bar, uint32_t cnt) { asm volatile("mbarrier.init.shared::cta.b64 [%0], %1;" ::"r"(bar), "r"(cnt) : "memory"); }
__device__ __forceinline__ void mbar_expect_tx(uint32_t bar, uint32_t bytes) { asm volatile("mbarrier.arrive.expect_tx.shared::cta.b64 _, [%0], %1;" ::"r"(bar), "r"(bytes) : "memory"); }
__device__ __forceinline__ void mbar_arrive_n(uint32_t bar, uint32_t n) { asm volatile("mbarrier.arrive.shared::cta.b64 _, [%0], %1;" ::"r"(bar), "r"(n) : "memory"); }
__device__ __forceinline__ void mbar_arrive(uint32_t bar) { asm volatile("mbarrier.arrive.shared::cta.b64 _, [%0];" ::"r"(bar) : "memory"); }
__device__ __forceinline__ void mbar_arrive_remote(uint32_t rbar) { asm volatile("mbarrier.arrive.shared::cluster.b64 _, [%0];" ::"r"(rbar) : "memory"); }
#define WV 2
#define DV 2
#define WD 2
#define HADD 4
#define KVOV 3
#define HX0 4
#define HX1 4
#define AFIRST 1
__device__ __forceinline__ void mbar_wait(uint32_t bar) {
  asm volatile("{ .reg .pred p;\n W_L: mbarrier.try_wait.parity.shared::cta.b64 p, [%0], 0;\n @!p pmevent 1; @!p bra W_L; }" ::"r"(bar) : "memory");
}
__device__ __forceinline__ void mbar_wait_to(uint32_t bar) {
  asm volatile("{ .reg .pred p; .reg .u32 n; mov.u32 n, 0;\n"
               "W_L: mbarrier.try_wait.parity.shared::cta.b64 p, [%0], 0;\n"
               "@p bra W_D;\n add.u32 n, n, 1;\n setp.lt.u32 p, n, 4194304;\n @p bra W_L;\n trap;\n W_D: }" ::"r"(bar) : "memory");
}
__device__ __forceinline__ void tma2d(uint32_t dst, const CUtensorMap* m, int c0, int c1, uint32_t bar) {
  asm volatile("cp.async.bulk.tensor.2d.shared::cluster.global.mbarrier::complete_tx::bytes [%0], [%1, {%3, %4}], [%2];" ::"r"(dst), "l"(m), "r"(bar), "r"(c0), "r"(c1) : "memory");
}
__device__ __forceinline__ void tma3d(uint32_t dst, const CUtensorMap* m, int c0, int c1, int c2, uint32_t bar) {
  asm volatile("cp.async.bulk.tensor.3d.shared::cluster.global.mbarrier::complete_tx::bytes [%0], [%1, {%3, %4, %5}], [%2];" ::"r"(dst), "l"(m), "r"(bar), "r"(c0), "r"(c1), "r"(c2) : "memory");
}
__device__ __forceinline__ void bulk_s2g(void* g, uint32_t src, uint32_t bytes) {
  asm volatile("cp.async.bulk.global.shared::cta.bulk_group [%0], [%1], %2;" ::"l"(g), "r"(src), "r"(bytes) : "memory");
}
__device__ __forceinline__ void bulk_commit() { asm volatile("cp.async.bulk.commit_group;" ::: "memory"); }
__device__ __forceinline__ void bulk_wait_read() { asm volatile("cp.async.bulk.wait_group.read 0;" ::: "memory"); }
__device__ __forceinline__ void bulk_wait_all() { asm volatile("cp.async.bulk.wait_group 0;" ::: "memory"); }
__device__ __forceinline__ void l2_prefetch(const void* g, uint32_t bytes) { asm volatile("cp.async.bulk.prefetch.L2.global [%0], %1;" ::"l"(g), "r"(bytes) : "memory"); }
__device__ __forceinline__ void map_prefetch(const CUtensorMap* m) { asm volatile("prefetch.tensormap [%0];" ::"l"(m) : "memory"); }
__device__ __forceinline__ void tma2d_store(const CUtensorMap* m, int c0, int c1, uint32_t src) {
  asm volatile("cp.async.bulk.tensor.2d.global.shared::cta.bulk_group [%0, {%2, %3}], [%1];" ::"l"(m), "r"(src), "r"(c0), "r"(c1) : "memory");
}
__device__ __forceinline__ void bulk_s2c(uint32_t rdst, uint32_t src, uint32_t bytes, uint32_t rbar) {
  asm volatile("cp.async.bulk.shared::cluster.shared::cta.mbarrier::complete_tx::bytes [%0], [%1], %2, [%3];" ::"r"(rdst), "r"(src), "r"(bytes), "r"(rbar) : "memory");
}
__device__ __forceinline__ uint32_t mapa(uint32_t a, uint32_t cta) { uint32_t r; asm volatile("mapa.shared::cluster.u32 %0, %1, %2;" : "=r"(r) : "r"(a), "r"(cta)); return r; }
__device__ __forceinline__ bool elect_one() { uint32_t p; asm volatile("{ .reg .pred P; elect.sync _|P, 0xffffffff; selp.u32 %0, 1, 0, P; }" : "=r"(p)); return p; }
__device__ __forceinline__ int laneid() { int l; asm volatile("mov.u32 %0, %%laneid;" : "=r"(l)); return l; }
__device__ __forceinline__ void fence_async() { asm volatile("fence.proxy.async.shared::cta;" ::: "memory"); }
__device__ __forceinline__ void wg_fence() { asm volatile("wgmma.fence.sync.aligned;" ::: "memory"); }
__device__ __forceinline__ void wg_commit() { asm volatile("wgmma.commit_group.sync.aligned;" ::: "memory"); }
template <int N> __device__ __forceinline__ void wg_wait() { asm volatile("wgmma.wait_group.sync.aligned %0;" ::"n"(N) : "memory"); }
template <int N> __device__ __forceinline__ void pin(float* a) {
#pragma unroll
  for (int i = 0; i < N; i++) asm volatile("" : "+f"(a[i])::"memory");
}
template <int N> __device__ __forceinline__ void pinr(uint32_t* a) {
#pragma unroll
  for (int i = 0; i < N; i++) asm volatile("" : "+r"(a[i])::"memory");
}
__device__ __forceinline__ void ldsm4(uint32_t* r, uint32_t a) { asm volatile("ldmatrix.sync.aligned.m8n8.x4.shared.b16 {%0,%1,%2,%3}, [%4];" : "=r"(r[0]), "=r"(r[1]), "=r"(r[2]), "=r"(r[3]) : "r"(a) : "memory"); }
__device__ __forceinline__ void stsm4(uint32_t a, uint32_t r0, uint32_t r1, uint32_t r2, uint32_t r3) { asm volatile("stmatrix.sync.aligned.m8n8.x4.shared.b16 [%0], {%1,%2,%3,%4};" ::"r"(a), "r"(r0), "r"(r1), "r"(r2), "r"(r3) : "memory"); }
__device__ __forceinline__ void stsm2(uint32_t a, uint32_t r0, uint32_t r1) { asm volatile("stmatrix.sync.aligned.m8n8.x2.shared.b16 [%0], {%1,%2};" ::"r"(a), "r"(r0), "r"(r1) : "memory"); }
__device__ __forceinline__ void sts4(uint32_t a, const uint32_t* r) { asm volatile("st.shared.v4.b32 [%0], {%1,%2,%3,%4};" ::"r"(a), "r"(r[0]), "r"(r[1]), "r"(r[2]), "r"(r[3]) : "memory"); }
__device__ __forceinline__ void sta4(uint32_t ra, const uint32_t* r, uint32_t rbar) {
  asm volatile("st.async.weak.shared::cluster.mbarrier::complete_tx::bytes.v4.b32 [%0], {%1,%2,%3,%4}, [%5];" ::"r"(ra), "r"(r[0]), "r"(r[1]), "r"(r[2]), "r"(r[3]), "r"(rbar) : "memory");
}
__device__ __forceinline__ void lds4(uint32_t* r, uint32_t a) { asm volatile("ld.shared.v4.b32 {%0,%1,%2,%3}, [%4];" : "=r"(r[0]), "=r"(r[1]), "=r"(r[2]), "=r"(r[3]) : "r"(a) : "memory"); }
__device__ __forceinline__ void lds4t(uint32_t* r, const uint32_t* o, uint32_t a) {
  r[0] = o[0]; r[1] = o[1]; r[2] = o[2]; r[3] = o[3];
  asm volatile("{ .reg .pred p; setp.ne.u32 p, %4, 1; @p ld.shared.v4.b32 {%0,%1,%2,%3}, [%4]; }" : "+r"(r[0]), "+r"(r[1]), "+r"(r[2]), "+r"(r[3]) : "r"(a) : "memory");
}
__device__ __forceinline__ uint32_t pack2(float lo, float hi) { uint32_t r; asm("cvt.rn.bf16x2.f32 %0, %1, %2;" : "=r"(r) : "f"(hi), "f"(lo)); return r; }
__device__ __forceinline__ float blo(uint32_t v) { return __uint_as_float(v << 16); }
__device__ __forceinline__ float bhi(uint32_t v) { return __uint_as_float(v & 0xFFFF0000u); }
__device__ __forceinline__ float ex2(float x) { float y; asm("ex2.approx.ftz.f32 %0, %1;" : "=f"(y) : "f"(x)); return y; }
__device__ __forceinline__ float rcp(float x) { float y; asm("rcp.approx.ftz.f32 %0, %1;" : "=f"(y) : "f"(x)); return y; }
__device__ __forceinline__ float sqrt_(float x) { float y; asm("sqrt.approx.ftz.f32 %0, %1;" : "=f"(y) : "f"(x)); return y; }
__device__ __forceinline__ void mma16816(float* c, const uint32_t* a, uint32_t b0, uint32_t b1) {
  asm volatile("mma.sync.aligned.m16n8k16.row.col.f32.bf16.bf16.f32 {%0,%1,%2,%3}, {%4,%5,%6,%7}, {%8,%9}, {%0,%1,%2,%3};"
               : "+f"(c[0]), "+f"(c[1]), "+f"(c[2]), "+f"(c[3]) : "r"(a[0]), "r"(a[1]), "r"(a[2]), "r"(a[3]), "r"(b0), "r"(b1));
}
__device__ __forceinline__ void mma1688(float* c, uint32_t a0, uint32_t a1, uint32_t b) {
  asm("mma.sync.aligned.m16n8k8.row.col.f32.bf16.bf16.f32 {%0,%1,%2,%3}, {%4,%5}, {%6}, {%0,%1,%2,%3};" : "+f"(c[0]), "+f"(c[1]), "+f"(c[2]), "+f"(c[3]) : "r"(a0), "r"(a1), "r"(b));
}
__device__ __forceinline__ float tanh_(float x) { float y; asm("tanh.approx.f32 %0, %1;" : "=f"(y) : "f"(x)); return y; }
__device__ __forceinline__ float bfr(float x) { return __bfloat162float(__float2bfloat16_rn(x)); }
__device__ __forceinline__ uint32_t ld_acq(const uint32_t* p) { uint32_t v; asm volatile("ld.acquire.gpu.global.u32 %0, [%1];" : "=r"(v) : "l"(p) : "memory"); return v; }
__device__ __forceinline__ void poll_flag(const uint32_t* p, uint32_t target) {
  uint32_t n = 0;
  while ((int)(ld_acq(p) - target) < 0) { if (++n > (1u << 21)) asm volatile("trap;"); }
}
#define SIGNAL(p) asm volatile("red.relaxed.gpu.global.add.u32 [%0], 1;" ::"l"(p) : "memory")
__device__ __forceinline__ void ld_ll(uint32_t* r, const uint4* p) {
  asm volatile("{ .reg .b128 t; .reg .b64 lo, hi; ld.relaxed.gpu.global.b128 t, [%4]; mov.b128 {lo,hi}, t; mov.b64 {%0,%1}, lo; mov.b64 {%2,%3}, hi; }" : "=r"(r[0]), "=r"(r[1]), "=r"(r[2]), "=r"(r[3]) : "l"(p) : "memory");
}
template <int K, uint32_t HI = 0x40000040u> __device__ __forceinline__ uint64_t desc_base(uint32_t sb, uint32_t add) {
  uint64_t d;
  asm volatile("{ .reg .b32 lo; shr.u32 lo, %1, 4; and.b32 lo, lo, %3; add.u32 lo, lo, %2; mov.b64 %0, {lo, %4}; }" : "=l"(d) : "r"(sb), "r"(add), "n"(0x40 | (K << 7)), "n"(HI));
  return d;
}
__device__ __forceinline__ constexpr uint64_t dofs(uint32_t off, uint32_t lbo) { return (uint64_t)(off >> 4) | ((uint64_t)(lbo >> 4) << 16); }
#define desc(off, lbo) (dh + dofs(off, lbo))

__device__ __forceinline__ void rs120_0(float* d, const uint32_t* a, uint64_t db){
  asm volatile("{ .reg .pred p; setp.ne.b32 p, 0, 0; wgmma.mma_async.sync.aligned.m64n120k16.f32.bf16.bf16 {%0, %1, %2, %3, %4, %5, %6, %7, %8, %9, %10, %11, %12, %13, %14, %15, %16, %17, %18, %19, %20, %21, %22, %23, %24, %25, %26, %27, %28, %29, %30, %31, %32, %33, %34, %35, %36, %37, %38, %39, %40, %41, %42, %43, %44, %45, %46, %47, %48, %49, %50, %51, %52, %53, %54, %55, %56, %57, %58, %59}, {%60,%61,%62,%63}, %64, p, 1, 1, 1; }"
   : "=f"(d[0]), "=f"(d[1]), "=f"(d[2]), "=f"(d[3]), "=f"(d[4]), "=f"(d[5]), "=f"(d[6]), "=f"(d[7]), "=f"(d[8]), "=f"(d[9]), "=f"(d[10]), "=f"(d[11]), "=f"(d[12]), "=f"(d[13]), "=f"(d[14]), "=f"(d[15]), "=f"(d[16]), "=f"(d[17]), "=f"(d[18]), "=f"(d[19]), "=f"(d[20]), "=f"(d[21]), "=f"(d[22]), "=f"(d[23]), "=f"(d[24]), "=f"(d[25]), "=f"(d[26]), "=f"(d[27]), "=f"(d[28]), "=f"(d[29]), "=f"(d[30]), "=f"(d[31]), "=f"(d[32]), "=f"(d[33]), "=f"(d[34]), "=f"(d[35]), "=f"(d[36]), "=f"(d[37]), "=f"(d[38]), "=f"(d[39]), "=f"(d[40]), "=f"(d[41]), "=f"(d[42]), "=f"(d[43]), "=f"(d[44]), "=f"(d[45]), "=f"(d[46]), "=f"(d[47]), "=f"(d[48]), "=f"(d[49]), "=f"(d[50]), "=f"(d[51]), "=f"(d[52]), "=f"(d[53]), "=f"(d[54]), "=f"(d[55]), "=f"(d[56]), "=f"(d[57]), "=f"(d[58]), "=f"(d[59]) : "r"(a[0]),"r"(a[1]),"r"(a[2]),"r"(a[3]), "l"(db));
}
__device__ __forceinline__ void rs120_1(float* d, const uint32_t* a, uint64_t db){
  asm volatile("{ .reg .pred p; setp.ne.b32 p, 1, 0; wgmma.mma_async.sync.aligned.m64n120k16.f32.bf16.bf16 {%0, %1, %2, %3, %4, %5, %6, %7, %8, %9, %10, %11, %12, %13, %14, %15, %16, %17, %18, %19, %20, %21, %22, %23, %24, %25, %26, %27, %28, %29, %30, %31, %32, %33, %34, %35, %36, %37, %38, %39, %40, %41, %42, %43, %44, %45, %46, %47, %48, %49, %50, %51, %52, %53, %54, %55, %56, %57, %58, %59}, {%60,%61,%62,%63}, %64, p, 1, 1, 1; }"
   : "+f"(d[0]), "+f"(d[1]), "+f"(d[2]), "+f"(d[3]), "+f"(d[4]), "+f"(d[5]), "+f"(d[6]), "+f"(d[7]), "+f"(d[8]), "+f"(d[9]), "+f"(d[10]), "+f"(d[11]), "+f"(d[12]), "+f"(d[13]), "+f"(d[14]), "+f"(d[15]), "+f"(d[16]), "+f"(d[17]), "+f"(d[18]), "+f"(d[19]), "+f"(d[20]), "+f"(d[21]), "+f"(d[22]), "+f"(d[23]), "+f"(d[24]), "+f"(d[25]), "+f"(d[26]), "+f"(d[27]), "+f"(d[28]), "+f"(d[29]), "+f"(d[30]), "+f"(d[31]), "+f"(d[32]), "+f"(d[33]), "+f"(d[34]), "+f"(d[35]), "+f"(d[36]), "+f"(d[37]), "+f"(d[38]), "+f"(d[39]), "+f"(d[40]), "+f"(d[41]), "+f"(d[42]), "+f"(d[43]), "+f"(d[44]), "+f"(d[45]), "+f"(d[46]), "+f"(d[47]), "+f"(d[48]), "+f"(d[49]), "+f"(d[50]), "+f"(d[51]), "+f"(d[52]), "+f"(d[53]), "+f"(d[54]), "+f"(d[55]), "+f"(d[56]), "+f"(d[57]), "+f"(d[58]), "+f"(d[59]) : "r"(a[0]),"r"(a[1]),"r"(a[2]),"r"(a[3]), "l"(db));
}
__device__ __forceinline__ void rs128_0(float* d, const uint32_t* a, uint64_t db){
  asm volatile("{ .reg .pred p; setp.ne.b32 p, 0, 0; wgmma.mma_async.sync.aligned.m64n128k16.f32.bf16.bf16 {%0, %1, %2, %3, %4, %5, %6, %7, %8, %9, %10, %11, %12, %13, %14, %15, %16, %17, %18, %19, %20, %21, %22, %23, %24, %25, %26, %27, %28, %29, %30, %31, %32, %33, %34, %35, %36, %37, %38, %39, %40, %41, %42, %43, %44, %45, %46, %47, %48, %49, %50, %51, %52, %53, %54, %55, %56, %57, %58, %59, %60, %61, %62, %63}, {%64,%65,%66,%67}, %68, p, 1, 1, 1; }"
   : "=f"(d[0]), "=f"(d[1]), "=f"(d[2]), "=f"(d[3]), "=f"(d[4]), "=f"(d[5]), "=f"(d[6]), "=f"(d[7]), "=f"(d[8]), "=f"(d[9]), "=f"(d[10]), "=f"(d[11]), "=f"(d[12]), "=f"(d[13]), "=f"(d[14]), "=f"(d[15]), "=f"(d[16]), "=f"(d[17]), "=f"(d[18]), "=f"(d[19]), "=f"(d[20]), "=f"(d[21]), "=f"(d[22]), "=f"(d[23]), "=f"(d[24]), "=f"(d[25]), "=f"(d[26]), "=f"(d[27]), "=f"(d[28]), "=f"(d[29]), "=f"(d[30]), "=f"(d[31]), "=f"(d[32]), "=f"(d[33]), "=f"(d[34]), "=f"(d[35]), "=f"(d[36]), "=f"(d[37]), "=f"(d[38]), "=f"(d[39]), "=f"(d[40]), "=f"(d[41]), "=f"(d[42]), "=f"(d[43]), "=f"(d[44]), "=f"(d[45]), "=f"(d[46]), "=f"(d[47]), "=f"(d[48]), "=f"(d[49]), "=f"(d[50]), "=f"(d[51]), "=f"(d[52]), "=f"(d[53]), "=f"(d[54]), "=f"(d[55]), "=f"(d[56]), "=f"(d[57]), "=f"(d[58]), "=f"(d[59]), "=f"(d[60]), "=f"(d[61]), "=f"(d[62]), "=f"(d[63]) : "r"(a[0]),"r"(a[1]),"r"(a[2]),"r"(a[3]), "l"(db));
}
__device__ __forceinline__ void rs128_1(float* d, const uint32_t* a, uint64_t db){
  asm volatile("{ .reg .pred p; setp.ne.b32 p, 1, 0; wgmma.mma_async.sync.aligned.m64n128k16.f32.bf16.bf16 {%0, %1, %2, %3, %4, %5, %6, %7, %8, %9, %10, %11, %12, %13, %14, %15, %16, %17, %18, %19, %20, %21, %22, %23, %24, %25, %26, %27, %28, %29, %30, %31, %32, %33, %34, %35, %36, %37, %38, %39, %40, %41, %42, %43, %44, %45, %46, %47, %48, %49, %50, %51, %52, %53, %54, %55, %56, %57, %58, %59, %60, %61, %62, %63}, {%64,%65,%66,%67}, %68, p, 1, 1, 1; }"
   : "+f"(d[0]), "+f"(d[1]), "+f"(d[2]), "+f"(d[3]), "+f"(d[4]), "+f"(d[5]), "+f"(d[6]), "+f"(d[7]), "+f"(d[8]), "+f"(d[9]), "+f"(d[10]), "+f"(d[11]), "+f"(d[12]), "+f"(d[13]), "+f"(d[14]), "+f"(d[15]), "+f"(d[16]), "+f"(d[17]), "+f"(d[18]), "+f"(d[19]), "+f"(d[20]), "+f"(d[21]), "+f"(d[22]), "+f"(d[23]), "+f"(d[24]), "+f"(d[25]), "+f"(d[26]), "+f"(d[27]), "+f"(d[28]), "+f"(d[29]), "+f"(d[30]), "+f"(d[31]), "+f"(d[32]), "+f"(d[33]), "+f"(d[34]), "+f"(d[35]), "+f"(d[36]), "+f"(d[37]), "+f"(d[38]), "+f"(d[39]), "+f"(d[40]), "+f"(d[41]), "+f"(d[42]), "+f"(d[43]), "+f"(d[44]), "+f"(d[45]), "+f"(d[46]), "+f"(d[47]), "+f"(d[48]), "+f"(d[49]), "+f"(d[50]), "+f"(d[51]), "+f"(d[52]), "+f"(d[53]), "+f"(d[54]), "+f"(d[55]), "+f"(d[56]), "+f"(d[57]), "+f"(d[58]), "+f"(d[59]), "+f"(d[60]), "+f"(d[61]), "+f"(d[62]), "+f"(d[63]) : "r"(a[0]),"r"(a[1]),"r"(a[2]),"r"(a[3]), "l"(db));
}
__device__ __forceinline__ void rs160_0(float* d, const uint32_t* a, uint64_t db){
  asm volatile("{ .reg .pred p; setp.ne.b32 p, 0, 0; wgmma.mma_async.sync.aligned.m64n160k16.f32.bf16.bf16 {%0, %1, %2, %3, %4, %5, %6, %7, %8, %9, %10, %11, %12, %13, %14, %15, %16, %17, %18, %19, %20, %21, %22, %23, %24, %25, %26, %27, %28, %29, %30, %31, %32, %33, %34, %35, %36, %37, %38, %39, %40, %41, %42, %43, %44, %45, %46, %47, %48, %49, %50, %51, %52, %53, %54, %55, %56, %57, %58, %59, %60, %61, %62, %63, %64, %65, %66, %67, %68, %69, %70, %71, %72, %73, %74, %75, %76, %77, %78, %79}, {%80,%81,%82,%83}, %84, p, 1, 1, 1; }"
   : "=f"(d[0]), "=f"(d[1]), "=f"(d[2]), "=f"(d[3]), "=f"(d[4]), "=f"(d[5]), "=f"(d[6]), "=f"(d[7]), "=f"(d[8]), "=f"(d[9]), "=f"(d[10]), "=f"(d[11]), "=f"(d[12]), "=f"(d[13]), "=f"(d[14]), "=f"(d[15]), "=f"(d[16]), "=f"(d[17]), "=f"(d[18]), "=f"(d[19]), "=f"(d[20]), "=f"(d[21]), "=f"(d[22]), "=f"(d[23]), "=f"(d[24]), "=f"(d[25]), "=f"(d[26]), "=f"(d[27]), "=f"(d[28]), "=f"(d[29]), "=f"(d[30]), "=f"(d[31]), "=f"(d[32]), "=f"(d[33]), "=f"(d[34]), "=f"(d[35]), "=f"(d[36]), "=f"(d[37]), "=f"(d[38]), "=f"(d[39]), "=f"(d[40]), "=f"(d[41]), "=f"(d[42]), "=f"(d[43]), "=f"(d[44]), "=f"(d[45]), "=f"(d[46]), "=f"(d[47]), "=f"(d[48]), "=f"(d[49]), "=f"(d[50]), "=f"(d[51]), "=f"(d[52]), "=f"(d[53]), "=f"(d[54]), "=f"(d[55]), "=f"(d[56]), "=f"(d[57]), "=f"(d[58]), "=f"(d[59]), "=f"(d[60]), "=f"(d[61]), "=f"(d[62]), "=f"(d[63]), "=f"(d[64]), "=f"(d[65]), "=f"(d[66]), "=f"(d[67]), "=f"(d[68]), "=f"(d[69]), "=f"(d[70]), "=f"(d[71]), "=f"(d[72]), "=f"(d[73]), "=f"(d[74]), "=f"(d[75]), "=f"(d[76]), "=f"(d[77]), "=f"(d[78]), "=f"(d[79]) : "r"(a[0]),"r"(a[1]),"r"(a[2]),"r"(a[3]), "l"(db));
}
__device__ __forceinline__ void rs160_1(float* d, const uint32_t* a, uint64_t db){
  asm volatile("{ .reg .pred p; setp.ne.b32 p, 1, 0; wgmma.mma_async.sync.aligned.m64n160k16.f32.bf16.bf16 {%0, %1, %2, %3, %4, %5, %6, %7, %8, %9, %10, %11, %12, %13, %14, %15, %16, %17, %18, %19, %20, %21, %22, %23, %24, %25, %26, %27, %28, %29, %30, %31, %32, %33, %34, %35, %36, %37, %38, %39, %40, %41, %42, %43, %44, %45, %46, %47, %48, %49, %50, %51, %52, %53, %54, %55, %56, %57, %58, %59, %60, %61, %62, %63, %64, %65, %66, %67, %68, %69, %70, %71, %72, %73, %74, %75, %76, %77, %78, %79}, {%80,%81,%82,%83}, %84, p, 1, 1, 1; }"
   : "+f"(d[0]), "+f"(d[1]), "+f"(d[2]), "+f"(d[3]), "+f"(d[4]), "+f"(d[5]), "+f"(d[6]), "+f"(d[7]), "+f"(d[8]), "+f"(d[9]), "+f"(d[10]), "+f"(d[11]), "+f"(d[12]), "+f"(d[13]), "+f"(d[14]), "+f"(d[15]), "+f"(d[16]), "+f"(d[17]), "+f"(d[18]), "+f"(d[19]), "+f"(d[20]), "+f"(d[21]), "+f"(d[22]), "+f"(d[23]), "+f"(d[24]), "+f"(d[25]), "+f"(d[26]), "+f"(d[27]), "+f"(d[28]), "+f"(d[29]), "+f"(d[30]), "+f"(d[31]), "+f"(d[32]), "+f"(d[33]), "+f"(d[34]), "+f"(d[35]), "+f"(d[36]), "+f"(d[37]), "+f"(d[38]), "+f"(d[39]), "+f"(d[40]), "+f"(d[41]), "+f"(d[42]), "+f"(d[43]), "+f"(d[44]), "+f"(d[45]), "+f"(d[46]), "+f"(d[47]), "+f"(d[48]), "+f"(d[49]), "+f"(d[50]), "+f"(d[51]), "+f"(d[52]), "+f"(d[53]), "+f"(d[54]), "+f"(d[55]), "+f"(d[56]), "+f"(d[57]), "+f"(d[58]), "+f"(d[59]), "+f"(d[60]), "+f"(d[61]), "+f"(d[62]), "+f"(d[63]), "+f"(d[64]), "+f"(d[65]), "+f"(d[66]), "+f"(d[67]), "+f"(d[68]), "+f"(d[69]), "+f"(d[70]), "+f"(d[71]), "+f"(d[72]), "+f"(d[73]), "+f"(d[74]), "+f"(d[75]), "+f"(d[76]), "+f"(d[77]), "+f"(d[78]), "+f"(d[79]) : "r"(a[0]),"r"(a[1]),"r"(a[2]),"r"(a[3]), "l"(db));
}
__device__ __forceinline__ void rs64_0(float* d, const uint32_t* a, uint64_t db){
  asm volatile("{ .reg .pred p; setp.ne.b32 p, 0, 0; wgmma.mma_async.sync.aligned.m64n64k16.f32.bf16.bf16 {%0, %1, %2, %3, %4, %5, %6, %7, %8, %9, %10, %11, %12, %13, %14, %15, %16, %17, %18, %19, %20, %21, %22, %23, %24, %25, %26, %27, %28, %29, %30, %31}, {%32,%33,%34,%35}, %36, p, 1, 1, 1; }"
   : "=f"(d[0]), "=f"(d[1]), "=f"(d[2]), "=f"(d[3]), "=f"(d[4]), "=f"(d[5]), "=f"(d[6]), "=f"(d[7]), "=f"(d[8]), "=f"(d[9]), "=f"(d[10]), "=f"(d[11]), "=f"(d[12]), "=f"(d[13]), "=f"(d[14]), "=f"(d[15]), "=f"(d[16]), "=f"(d[17]), "=f"(d[18]), "=f"(d[19]), "=f"(d[20]), "=f"(d[21]), "=f"(d[22]), "=f"(d[23]), "=f"(d[24]), "=f"(d[25]), "=f"(d[26]), "=f"(d[27]), "=f"(d[28]), "=f"(d[29]), "=f"(d[30]), "=f"(d[31]) : "r"(a[0]),"r"(a[1]),"r"(a[2]),"r"(a[3]), "l"(db));
}
__device__ __forceinline__ void rs64_1(float* d, const uint32_t* a, uint64_t db){
  asm volatile("{ .reg .pred p; setp.ne.b32 p, 1, 0; wgmma.mma_async.sync.aligned.m64n64k16.f32.bf16.bf16 {%0, %1, %2, %3, %4, %5, %6, %7, %8, %9, %10, %11, %12, %13, %14, %15, %16, %17, %18, %19, %20, %21, %22, %23, %24, %25, %26, %27, %28, %29, %30, %31}, {%32,%33,%34,%35}, %36, p, 1, 1, 1; }"
   : "+f"(d[0]), "+f"(d[1]), "+f"(d[2]), "+f"(d[3]), "+f"(d[4]), "+f"(d[5]), "+f"(d[6]), "+f"(d[7]), "+f"(d[8]), "+f"(d[9]), "+f"(d[10]), "+f"(d[11]), "+f"(d[12]), "+f"(d[13]), "+f"(d[14]), "+f"(d[15]), "+f"(d[16]), "+f"(d[17]), "+f"(d[18]), "+f"(d[19]), "+f"(d[20]), "+f"(d[21]), "+f"(d[22]), "+f"(d[23]), "+f"(d[24]), "+f"(d[25]), "+f"(d[26]), "+f"(d[27]), "+f"(d[28]), "+f"(d[29]), "+f"(d[30]), "+f"(d[31]) : "r"(a[0]),"r"(a[1]),"r"(a[2]),"r"(a[3]), "l"(db));
}
__device__ __forceinline__ void rs56_0(float* d, const uint32_t* a, uint64_t db){
  asm volatile("{ .reg .pred p; setp.ne.b32 p, 0, 0; wgmma.mma_async.sync.aligned.m64n56k16.f32.bf16.bf16 {%0, %1, %2, %3, %4, %5, %6, %7, %8, %9, %10, %11, %12, %13, %14, %15, %16, %17, %18, %19, %20, %21, %22, %23, %24, %25, %26, %27}, {%28,%29,%30,%31}, %32, p, 1, 1, 1; }"
   : "=f"(d[0]), "=f"(d[1]), "=f"(d[2]), "=f"(d[3]), "=f"(d[4]), "=f"(d[5]), "=f"(d[6]), "=f"(d[7]), "=f"(d[8]), "=f"(d[9]), "=f"(d[10]), "=f"(d[11]), "=f"(d[12]), "=f"(d[13]), "=f"(d[14]), "=f"(d[15]), "=f"(d[16]), "=f"(d[17]), "=f"(d[18]), "=f"(d[19]), "=f"(d[20]), "=f"(d[21]), "=f"(d[22]), "=f"(d[23]), "=f"(d[24]), "=f"(d[25]), "=f"(d[26]), "=f"(d[27]) : "r"(a[0]),"r"(a[1]),"r"(a[2]),"r"(a[3]), "l"(db));
}
__device__ __forceinline__ void rs56_1(float* d, const uint32_t* a, uint64_t db){
  asm volatile("{ .reg .pred p; setp.ne.b32 p, 1, 0; wgmma.mma_async.sync.aligned.m64n56k16.f32.bf16.bf16 {%0, %1, %2, %3, %4, %5, %6, %7, %8, %9, %10, %11, %12, %13, %14, %15, %16, %17, %18, %19, %20, %21, %22, %23, %24, %25, %26, %27}, {%28,%29,%30,%31}, %32, p, 1, 1, 1; }"
   : "+f"(d[0]), "+f"(d[1]), "+f"(d[2]), "+f"(d[3]), "+f"(d[4]), "+f"(d[5]), "+f"(d[6]), "+f"(d[7]), "+f"(d[8]), "+f"(d[9]), "+f"(d[10]), "+f"(d[11]), "+f"(d[12]), "+f"(d[13]), "+f"(d[14]), "+f"(d[15]), "+f"(d[16]), "+f"(d[17]), "+f"(d[18]), "+f"(d[19]), "+f"(d[20]), "+f"(d[21]), "+f"(d[22]), "+f"(d[23]), "+f"(d[24]), "+f"(d[25]), "+f"(d[26]), "+f"(d[27]) : "r"(a[0]),"r"(a[1]),"r"(a[2]),"r"(a[3]), "l"(db));
}
__device__ __forceinline__ void rs32_0(float* d, const uint32_t* a, uint64_t db){
  asm volatile("{ .reg .pred p; setp.ne.b32 p, 0, 0; wgmma.mma_async.sync.aligned.m64n32k16.f32.bf16.bf16 {%0, %1, %2, %3, %4, %5, %6, %7, %8, %9, %10, %11, %12, %13, %14, %15}, {%16,%17,%18,%19}, %20, p, 1, 1, 1; }"
   : "=f"(d[0]), "=f"(d[1]), "=f"(d[2]), "=f"(d[3]), "=f"(d[4]), "=f"(d[5]), "=f"(d[6]), "=f"(d[7]), "=f"(d[8]), "=f"(d[9]), "=f"(d[10]), "=f"(d[11]), "=f"(d[12]), "=f"(d[13]), "=f"(d[14]), "=f"(d[15]) : "r"(a[0]),"r"(a[1]),"r"(a[2]),"r"(a[3]), "l"(db));
}
__device__ __forceinline__ void rs32_1(float* d, const uint32_t* a, uint64_t db){
  asm volatile("{ .reg .pred p; setp.ne.b32 p, 1, 0; wgmma.mma_async.sync.aligned.m64n32k16.f32.bf16.bf16 {%0, %1, %2, %3, %4, %5, %6, %7, %8, %9, %10, %11, %12, %13, %14, %15}, {%16,%17,%18,%19}, %20, p, 1, 1, 1; }"
   : "+f"(d[0]), "+f"(d[1]), "+f"(d[2]), "+f"(d[3]), "+f"(d[4]), "+f"(d[5]), "+f"(d[6]), "+f"(d[7]), "+f"(d[8]), "+f"(d[9]), "+f"(d[10]), "+f"(d[11]), "+f"(d[12]), "+f"(d[13]), "+f"(d[14]), "+f"(d[15]) : "r"(a[0]),"r"(a[1]),"r"(a[2]),"r"(a[3]), "l"(db));
}
__device__ __forceinline__ void ss64_0(float* d, uint64_t da, uint64_t db){
  asm volatile("{ .reg .pred p; setp.ne.b32 p, 0, 0; wgmma.mma_async.sync.aligned.m64n64k16.f32.bf16.bf16 {%0, %1, %2, %3, %4, %5, %6, %7, %8, %9, %10, %11, %12, %13, %14, %15, %16, %17, %18, %19, %20, %21, %22, %23, %24, %25, %26, %27, %28, %29, %30, %31}, %32, %33, p, 1, 1, 1, 1; }"
   : "=f"(d[0]), "=f"(d[1]), "=f"(d[2]), "=f"(d[3]), "=f"(d[4]), "=f"(d[5]), "=f"(d[6]), "=f"(d[7]), "=f"(d[8]), "=f"(d[9]), "=f"(d[10]), "=f"(d[11]), "=f"(d[12]), "=f"(d[13]), "=f"(d[14]), "=f"(d[15]), "=f"(d[16]), "=f"(d[17]), "=f"(d[18]), "=f"(d[19]), "=f"(d[20]), "=f"(d[21]), "=f"(d[22]), "=f"(d[23]), "=f"(d[24]), "=f"(d[25]), "=f"(d[26]), "=f"(d[27]), "=f"(d[28]), "=f"(d[29]), "=f"(d[30]), "=f"(d[31]) : "l"(da), "l"(db));
}
__device__ __forceinline__ void ss64_1(float* d, uint64_t da, uint64_t db){
  asm volatile("{ .reg .pred p; setp.ne.b32 p, 1, 0; wgmma.mma_async.sync.aligned.m64n64k16.f32.bf16.bf16 {%0, %1, %2, %3, %4, %5, %6, %7, %8, %9, %10, %11, %12, %13, %14, %15, %16, %17, %18, %19, %20, %21, %22, %23, %24, %25, %26, %27, %28, %29, %30, %31}, %32, %33, p, 1, 1, 1, 1; }"
   : "+f"(d[0]), "+f"(d[1]), "+f"(d[2]), "+f"(d[3]), "+f"(d[4]), "+f"(d[5]), "+f"(d[6]), "+f"(d[7]), "+f"(d[8]), "+f"(d[9]), "+f"(d[10]), "+f"(d[11]), "+f"(d[12]), "+f"(d[13]), "+f"(d[14]), "+f"(d[15]), "+f"(d[16]), "+f"(d[17]), "+f"(d[18]), "+f"(d[19]), "+f"(d[20]), "+f"(d[21]), "+f"(d[22]), "+f"(d[23]), "+f"(d[24]), "+f"(d[25]), "+f"(d[26]), "+f"(d[27]), "+f"(d[28]), "+f"(d[29]), "+f"(d[30]), "+f"(d[31]) : "l"(da), "l"(db));
}
__device__ __forceinline__ void rs64_z(float* d, const uint32_t* a, uint64_t db){
  asm volatile("{ .reg .pred p; setp.ne.b32 p, 0, 0; wgmma.mma_async.sync.aligned.m64n64k16.f32.bf16.bf16 {%0, %1, %2, %3, %4, %5, %6, %7, %8, %9, %10, %11, %12, %13, %14, %15, %16, %17, %18, %19, %20, %21, %22, %23, %24, %25, %26, %27, %28, %29, %30, %31}, {%32,%33,%34,%35}, %36, p, 1, 1, 1; }"
   : "+f"(d[0]), "+f"(d[1]), "+f"(d[2]), "+f"(d[3]), "+f"(d[4]), "+f"(d[5]), "+f"(d[6]), "+f"(d[7]), "+f"(d[8]), "+f"(d[9]), "+f"(d[10]), "+f"(d[11]), "+f"(d[12]), "+f"(d[13]), "+f"(d[14]), "+f"(d[15]), "+f"(d[16]), "+f"(d[17]), "+f"(d[18]), "+f"(d[19]), "+f"(d[20]), "+f"(d[21]), "+f"(d[22]), "+f"(d[23]), "+f"(d[24]), "+f"(d[25]), "+f"(d[26]), "+f"(d[27]), "+f"(d[28]), "+f"(d[29]), "+f"(d[30]), "+f"(d[31]) : "r"(a[0]),"r"(a[1]),"r"(a[2]),"r"(a[3]), "l"(db));
}
__device__ __forceinline__ void rs32_z(float* d, const uint32_t* a, uint64_t db){
  asm volatile("{ .reg .pred p; setp.ne.b32 p, 0, 0; wgmma.mma_async.sync.aligned.m64n32k16.f32.bf16.bf16 {%0, %1, %2, %3, %4, %5, %6, %7, %8, %9, %10, %11, %12, %13, %14, %15}, {%16,%17,%18,%19}, %20, p, 1, 1, 1; }"
   : "+f"(d[0]), "+f"(d[1]), "+f"(d[2]), "+f"(d[3]), "+f"(d[4]), "+f"(d[5]), "+f"(d[6]), "+f"(d[7]), "+f"(d[8]), "+f"(d[9]), "+f"(d[10]), "+f"(d[11]), "+f"(d[12]), "+f"(d[13]), "+f"(d[14]), "+f"(d[15]) : "r"(a[0]),"r"(a[1]),"r"(a[2]),"r"(a[3]), "l"(db));
}
__device__ __forceinline__ void sk64_0(float* d, uint64_t da, uint64_t db){
  asm volatile("{ .reg .pred p; setp.ne.b32 p, 0, 0; wgmma.mma_async.sync.aligned.m64n64k16.f32.bf16.bf16 {%0, %1, %2, %3, %4, %5, %6, %7, %8, %9, %10, %11, %12, %13, %14, %15, %16, %17, %18, %19, %20, %21, %22, %23, %24, %25, %26, %27, %28, %29, %30, %31}, %32, %33, p, 1, 1, 0, 1; }"
   : "=f"(d[0]), "=f"(d[1]), "=f"(d[2]), "=f"(d[3]), "=f"(d[4]), "=f"(d[5]), "=f"(d[6]), "=f"(d[7]), "=f"(d[8]), "=f"(d[9]), "=f"(d[10]), "=f"(d[11]), "=f"(d[12]), "=f"(d[13]), "=f"(d[14]), "=f"(d[15]), "=f"(d[16]), "=f"(d[17]), "=f"(d[18]), "=f"(d[19]), "=f"(d[20]), "=f"(d[21]), "=f"(d[22]), "=f"(d[23]), "=f"(d[24]), "=f"(d[25]), "=f"(d[26]), "=f"(d[27]), "=f"(d[28]), "=f"(d[29]), "=f"(d[30]), "=f"(d[31]) : "l"(da), "l"(db));
}
__device__ __forceinline__ void sk64_1(float* d, uint64_t da, uint64_t db){
  asm volatile("{ .reg .pred p; setp.ne.b32 p, 1, 0; wgmma.mma_async.sync.aligned.m64n64k16.f32.bf16.bf16 {%0, %1, %2, %3, %4, %5, %6, %7, %8, %9, %10, %11, %12, %13, %14, %15, %16, %17, %18, %19, %20, %21, %22, %23, %24, %25, %26, %27, %28, %29, %30, %31}, %32, %33, p, 1, 1, 0, 1; }"
   : "+f"(d[0]), "+f"(d[1]), "+f"(d[2]), "+f"(d[3]), "+f"(d[4]), "+f"(d[5]), "+f"(d[6]), "+f"(d[7]), "+f"(d[8]), "+f"(d[9]), "+f"(d[10]), "+f"(d[11]), "+f"(d[12]), "+f"(d[13]), "+f"(d[14]), "+f"(d[15]), "+f"(d[16]), "+f"(d[17]), "+f"(d[18]), "+f"(d[19]), "+f"(d[20]), "+f"(d[21]), "+f"(d[22]), "+f"(d[23]), "+f"(d[24]), "+f"(d[25]), "+f"(d[26]), "+f"(d[27]), "+f"(d[28]), "+f"(d[29]), "+f"(d[30]), "+f"(d[31]) : "l"(da), "l"(db));
}
__device__ __forceinline__ void sk64_z(float* d, uint64_t da, uint64_t db){
  asm volatile("{ .reg .pred p; setp.ne.b32 p, 0, 0; wgmma.mma_async.sync.aligned.m64n64k16.f32.bf16.bf16 {%0, %1, %2, %3, %4, %5, %6, %7, %8, %9, %10, %11, %12, %13, %14, %15, %16, %17, %18, %19, %20, %21, %22, %23, %24, %25, %26, %27, %28, %29, %30, %31}, %32, %33, p, 1, 1, 0, 1; }"
   : "+f"(d[0]), "+f"(d[1]), "+f"(d[2]), "+f"(d[3]), "+f"(d[4]), "+f"(d[5]), "+f"(d[6]), "+f"(d[7]), "+f"(d[8]), "+f"(d[9]), "+f"(d[10]), "+f"(d[11]), "+f"(d[12]), "+f"(d[13]), "+f"(d[14]), "+f"(d[15]), "+f"(d[16]), "+f"(d[17]), "+f"(d[18]), "+f"(d[19]), "+f"(d[20]), "+f"(d[21]), "+f"(d[22]), "+f"(d[23]), "+f"(d[24]), "+f"(d[25]), "+f"(d[26]), "+f"(d[27]), "+f"(d[28]), "+f"(d[29]), "+f"(d[30]), "+f"(d[31]) : "l"(da), "l"(db));
}
__device__ __forceinline__ void sk32_0(float* d, uint64_t da, uint64_t db){
  asm volatile("{ .reg .pred p; setp.ne.b32 p, 0, 0; wgmma.mma_async.sync.aligned.m64n32k16.f32.bf16.bf16 {%0, %1, %2, %3, %4, %5, %6, %7, %8, %9, %10, %11, %12, %13, %14, %15}, %16, %17, p, 1, 1, 0, 1; }"
   : "=f"(d[0]), "=f"(d[1]), "=f"(d[2]), "=f"(d[3]), "=f"(d[4]), "=f"(d[5]), "=f"(d[6]), "=f"(d[7]), "=f"(d[8]), "=f"(d[9]), "=f"(d[10]), "=f"(d[11]), "=f"(d[12]), "=f"(d[13]), "=f"(d[14]), "=f"(d[15]) : "l"(da), "l"(db));
}
__device__ __forceinline__ void sk32_1(float* d, uint64_t da, uint64_t db){
  asm volatile("{ .reg .pred p; setp.ne.b32 p, 1, 0; wgmma.mma_async.sync.aligned.m64n32k16.f32.bf16.bf16 {%0, %1, %2, %3, %4, %5, %6, %7, %8, %9, %10, %11, %12, %13, %14, %15}, %16, %17, p, 1, 1, 0, 1; }"
   : "+f"(d[0]), "+f"(d[1]), "+f"(d[2]), "+f"(d[3]), "+f"(d[4]), "+f"(d[5]), "+f"(d[6]), "+f"(d[7]), "+f"(d[8]), "+f"(d[9]), "+f"(d[10]), "+f"(d[11]), "+f"(d[12]), "+f"(d[13]), "+f"(d[14]), "+f"(d[15]) : "l"(da), "l"(db));
}
__device__ __forceinline__ void sk32_z(float* d, uint64_t da, uint64_t db){
  asm volatile("{ .reg .pred p; setp.ne.b32 p, 0, 0; wgmma.mma_async.sync.aligned.m64n32k16.f32.bf16.bf16 {%0, %1, %2, %3, %4, %5, %6, %7, %8, %9, %10, %11, %12, %13, %14, %15}, %16, %17, p, 1, 1, 0, 1; }"
   : "+f"(d[0]), "+f"(d[1]), "+f"(d[2]), "+f"(d[3]), "+f"(d[4]), "+f"(d[5]), "+f"(d[6]), "+f"(d[7]), "+f"(d[8]), "+f"(d[9]), "+f"(d[10]), "+f"(d[11]), "+f"(d[12]), "+f"(d[13]), "+f"(d[14]), "+f"(d[15]) : "l"(da), "l"(db));
}
template<int N> __device__ __forceinline__ void ssz(float* d, uint64_t da, uint64_t db){
  if constexpr (N==64) sk64_z(d,da,db); else sk32_z(d,da,db);
}
template<int N> __device__ __forceinline__ void rsz(float* d, const uint32_t* a, uint64_t db){
  if constexpr (N==64) rs64_z(d,a,db); else rs32_z(d,a,db);
}
template<int N> __device__ __forceinline__ void ssk(float* d, uint64_t da, uint64_t db, bool first){
  if constexpr (N==64) { if(first) sk64_0(d,da,db); else sk64_1(d,da,db); } else { if(first) sk32_0(d,da,db); else sk32_1(d,da,db); }
}
template<int N> __device__ __forceinline__ void rs(float* d, const uint32_t* a, uint64_t db, bool first){
  if constexpr (N==120) { if(first) rs120_0(d,a,db); else rs120_1(d,a,db); }
  if constexpr (N==128) { if(first) rs128_0(d,a,db); else rs128_1(d,a,db); }
  if constexpr (N==160) { if(first) rs160_0(d,a,db); else rs160_1(d,a,db); }
  if constexpr (N==64) { if(first) rs64_0(d,a,db); else rs64_1(d,a,db); }
  if constexpr (N==56) { if(first) rs56_0(d,a,db); else rs56_1(d,a,db); }
  if constexpr (N==32) { if(first) rs32_0(d,a,db); else rs32_1(d,a,db); }
}

constexpr float LOG2E = 1.4426950408889634f;
#define EPI_TS(x) x
#define TS7(i)
#define TS9(i)
#define TS5(i)
#define TS4(i)
#define BAR(i) (sb + MISC + 8u * (uint32_t)(i))
#define BBARI(k) asm volatile("{ .reg .pred p; setp.ne.u32 p, %0, %1; @p bra B_L; trap; B_L: }" ::"r"(sb), "r"(k) : "memory")
#define BBAR() asm volatile("{ .reg .pred p; setp.ne.u32 p, %0, %1; @p bra B_L; trap; B_L: }" ::"r"(sb), "n"(__LINE__ * 2 + 1) : "memory")

__host__ __device__ constexpr int unitB(int g) { return g == 0 ? 0 : g == 1 ? 3 : g == 2 ? 8 : 14 + 3 * (g - 3); }
__host__ __device__ constexpr int unitC(int g) { return g == 0 ? 11 : g == 1 ? 5 : g == 2 ? 8 : 14 + 3 * (g - 3); }
__host__ __device__ constexpr int unitD(int g) { return g == 0 ? 11 : g == 1 ? 8 : g == 6 ? 3 : 14 + 3 * (g - 2); }
#define OMIN 0
#define AHOLD 4
#define B01DEP XC0
__host__ __device__ constexpr int depB(int g) { return g < 2 ? B01DEP : g == 2 ? XC1 : g == 3 ? EA1 : g == 4 ? EA2 : g == 5 ? EA4 : EA5; }
__host__ __device__ constexpr int depC(int g) { return g == 0 ? KVFREE : EB1 + g - 1; }
__host__ __device__ constexpr int depD(int g) { return g == 0 ? EC0 : g < 6 ? EC0 + g + 1 : LHA; }
__host__ __device__ constexpr int eid(int P, int g) {
  return P == 0 ? (g == 1 ? EA1 : g == 2 ? EA2 : g >= 4 ? EA4 + g - 4 : -1)
       : P == 1 ? (g >= 1 ? EB1 + g - 1 : -1)
       : P == 2 ? EC0 + g
                : (g == 1 ? ED1 : g == 2 ? ED2 : g == 3 ? ED3 : g >= 4 ? ED4 + g - 4 : -1);
}
template <int P> __host__ __device__ constexpr int unitP(int g) { return P == 0 ? 14 + 2 * g : P == 1 ? unitB(g) : P == 2 ? unitC(g) : unitD(g); }
template <typename Fn> __host__ __device__ constexpr uint64_t packtab(Fn f) { uint64_t t = 0; for (int g = 0; g < 7; g++) t |= (uint64_t)f(g) << (8 * g); return t; }

struct NoPre { __device__ __forceinline__ void operator()(int, int) const {} };
template <int P, int N, typename Fn, typename Fp, typename Fq = NoPre>
__device__ __forceinline__ void pass1(float* acc, const uint32_t* xf, uint32_t sb, uint32_t pb, bool lane0, uint64_t dh, uint64_t sh, Fn shadow, Fp post, Fq pre = Fq()) {
#pragma unroll
  for (int g = 0; g < 7; g++) {
    if (P != 1 || g)
    mbar_wait(BAR(FA + 7 * P + g));
    wg_fence();
    pre(g, -1);
    if (P == 1 && g == 0) {
#pragma unroll
      for (int kk = 0; kk < 4; kk++) rs<56>(acc + 64, xf + 4 * kk, sh + dofs((unitP<P>(0) + 2) * U + kk * 2048, U), kk == 0);
    } else
#pragma unroll
    for (int kk = 0; kk < 4; kk++) {
      if (P == 1) {
        rs<128>(acc, xf + 16 * g + 4 * kk, desc(unitP<P>(g) * U + kk * 2048, U), g == 0 && kk == 0);
        rs<56>(acc + 64, xf + 16 * g + 4 * kk, sh + dofs((unitP<P>(g) + 2) * U + kk * 2048, U), g == 0 && kk == 0);
      } else {
        rs<N>(acc, xf + 16 * g + 4 * kk, (P == 0 ? sh : dh) + dofs(unitP<P>(g) * U + kk * 2048, U), g == 0 && kk == 0);
      }
      pre(g, kk);
    }
    wg_commit();
    shadow(g);
    if (g > 0) {
      wg_wait<1>();
      if (lane0) {
        if (eid(P, g - 1) >= 0) mbar_arrive(BAR(eid(P, g - 1)));
        if ((P == 1 || P == 2) && g == 2) mbar_arrive_remote(pb + MISC + 8u * (PF + P - 1));
        if (P == 3 && g == 1) mbar_arrive_remote(pb + MISC + 8u * (PF + 2));
      }
      post(g);
    }
  }
  wg_wait<0>();
  if (lane0) mbar_arrive(BAR(eid(P, 6)));
  pin<N / 2>(acc);
}

template <int ID> __device__ __forceinline__ void hfrag64(uint32_t* h, float* acc, const float* rs_, uint32_t sb, int wg) {
  const float hr[2] = {0.5f * rs_[0], 0.5f * rs_[1]};
#pragma unroll
  for (int i = 0; i < 32; i++) {
    acc[32 + i] *= acc[i];
    acc[i] *= hr[(i >> 1) & 1];
    if (i < 16) acc[i] = tanh_(acc[i]);
  }
  pin<64>(acc);
  BBARI(ID * 4 + 1);
  EPI_TS(if (ID == 1) CTS(21));
  const float c[2] = {hr[0] * hr[0], hr[1] * hr[1]};
#pragma unroll
  for (int i = 16; i < 32; i++) acc[i] = tanh_(acc[i]);
#pragma unroll
  for (int m = 0; m < 8; m++) h[m] = pack2(acc[32 + 2 * m] * fmaf(acc[2 * m], c[m & 1], c[m & 1]), acc[33 + 2 * m] * fmaf(acc[2 * m + 1], c[m & 1], c[m & 1]));
  pin<16>(acc + 16);
  pinr<8>(h);
  BBARI(ID * 4 + 3);
  EPI_TS(if (ID == 1) CTS(22));
#pragma unroll
  for (int m = 8; m < 16; m++) h[m] = pack2(acc[32 + 2 * m] * fmaf(acc[2 * m], c[m & 1], c[m & 1]), acc[33 + 2 * m] * fmaf(acc[2 * m + 1], c[m & 1], c[m & 1]));
}
__device__ __forceinline__ uint32_t phi2(float e0, float e1, uint32_t r, uint32_t c) {
  uint32_t d;
  asm("{ .reg .b32 m; cvt.rn.bf16x2.f32 m, %2, %1; min.bf16x2 m, m, %5; add.rn.bf16x2 m, m, %6; fma.rn.bf16x2 %0, %3, %4, m; }" : "=r"(d) : "f"(e0), "f"(e1), "r"(r), "r"(c), "r"(0x3F803F80u), "r"(0x35863586u));
  return d;
}
__device__ __forceinline__ uint32_t pack2r(float lo, float hi) { uint32_t r; asm("cvt.rn.relu.bf16x2.f32 %0, %1, %2;" : "=r"(r) : "f"(hi), "f"(lo)); return r; }

template <int NP> __device__ __forceinline__ void send_ll(uint4* dst, const float* a) {
#pragma unroll
  for (int q = 0; q < NP; q++)
    asm volatile("{ .reg .b128 t; .reg .b64 lo, hi; mov.b64 lo, {%1,%2}; mov.b64 hi, {%3,%4}; mov.b128 t, {lo,hi}; st.relaxed.gpu.global.b128 [%0], t; }" ::"l"(dst + q * 32),
                 "r"(pack2(a[8 * q], a[8 * q + 1]) | 1u), "r"(pack2(a[8 * q + 2], a[8 * q + 3])), "r"(pack2(a[8 * q + 4], a[8 * q + 5])), "r"(pack2(a[8 * q + 6], a[8 * q + 7])) : "memory");
}
template <int NP> __device__ __forceinline__ void send_llp(uint4* dst, const float* a, bool on) {
#pragma unroll
  for (int q = 0; q < NP; q++)
    asm volatile("{ .reg .pred p; .reg .b128 t; .reg .b64 lo, hi; setp.ne.u32 p, %5, 0; mov.b64 lo, {%1,%2}; mov.b64 hi, {%3,%4}; mov.b128 t, {lo,hi}; @p st.relaxed.gpu.global.b128 [%0], t; }" ::"l"(dst + q * 32),
                 "r"(pack2(a[8 * q], a[8 * q + 1]) | 1u), "r"(pack2(a[8 * q + 2], a[8 * q + 3])), "r"(pack2(a[8 * q + 4], a[8 * q + 5])), "r"(pack2(a[8 * q + 6], a[8 * q + 7])), "r"((uint32_t)on) : "memory");
}
__device__ __forceinline__ void stg4(uint4* dst, const uint32_t* w) {
  asm volatile("{ .reg .b128 t; .reg .b64 lo, hi; mov.b64 lo, {%1,%2}; mov.b64 hi, {%3,%4}; mov.b128 t, {lo,hi}; st.relaxed.gpu.global.b128 [%0], t; }" ::"l"(dst),
               "r"(w[0]), "r"(w[1]), "r"(w[2]), "r"(w[3]) : "memory");
}
#define LL_LD(g, p, o, a, b, c, d) g "ld.relaxed.gpu.global.v4.b32 {%" #a ",%" #b ",%" #c ",%" #d "}, [%" #p "+" #o "];\n"
#define LL_OPS(c) c(v[0]), c(v[1]), c(v[2]), c(v[3]), c(v[4]), c(v[5]), c(v[6]), c(v[7]), c(v[8]), c(v[9]), c(v[10]), c(v[11]), c(v[12]), c(v[13]), c(v[14]), c(v[15])
__device__ __forceinline__ void ld_ll4(uint32_t* v, const uint4* p, const uint4* p2) {
  asm volatile(LL_LD("", 16, 0, 0, 1, 2, 3) LL_LD("", 16, 512, 4, 5, 6, 7) LL_LD("", 17, 0, 8, 9, 10, 11) LL_LD("", 17, 512, 12, 13, 14, 15) : LL_OPS("=r") : "l"(p), "l"(p2) : "memory");
}
#define LL_CK(q, a, b, c, d) "lop3.b32 t, %" #c ", %" #d ", %49, 0xEA; lop3.b32 t, t, %" #a ", %" #b ", 0x80; and.b32 t, t, 1; setp.ne.u32 " #q ", t, 0; vote.sync.all.pred " #q ", " #q ", 0xffffffff;\n"
#define LL_O16(v) "+r"(v[0]), "+r"(v[1]), "+r"(v[2]), "+r"(v[3]), "+r"(v[4]), "+r"(v[5]), "+r"(v[6]), "+r"(v[7]), "+r"(v[8]), "+r"(v[9]), "+r"(v[10]), "+r"(v[11]), "+r"(v[12]), "+r"(v[13]), "+r"(v[14]), "+r"(v[15])
#define LL_RE3 \
      LL_CK(q, 0, 4, 8, 12) "or.pred z, q, y;\n" \
      LL_LD("@!q ", 48, 0, 0, 1, 2, 3) LL_LD("@!q ", 48, 512, 4, 5, 6, 7) LL_LD("@!z ", 48, 1024, 8, 9, 10, 11) LL_LD("@!z ", 48, 1536, 12, 13, 14, 15) \
      LL_CK(q, 16, 20, 24, 28) "or.pred z, q, y;\n" \
      LL_LD("@!q ", 48, 16384, 16, 17, 18, 19) LL_LD("@!q ", 48, 16896, 20, 21, 22, 23) LL_LD("@!z ", 48, 17408, 24, 25, 26, 27) LL_LD("@!z ", 48, 17920, 28, 29, 30, 31) \
      LL_CK(q, 32, 36, 40, 44) "or.pred z, q, y;\n" \
      LL_LD("@!q ", 48, 32768, 32, 33, 34, 35) LL_LD("@!q ", 48, 33280, 36, 37, 38, 39) LL_LD("@!z ", 48, 33792, 40, 41, 42, 43) LL_LD("@!z ", 48, 34304, 44, 45, 46, 47)
__device__ __forceinline__ void chk_ll(uint32_t (*v)[16], const uint4* p, uint32_t nar) {
  asm volatile(
      "{ .reg .pred p, q, y, z; .reg .b32 t, u, n;\n"
      "mov.u32 n, 0; setp.ne.u32 y, %49, 0;\n"
      "R_L: lop3.b32 t, %0, %4, %16, 0x80; lop3.b32 u, %8, %12, %24, 0x80; lop3.b32 t, t, %20, %32, 0x80; lop3.b32 u, u, %28, %40, 0x80; lop3.b32 t, t, %36, 1, 0x80; lop3.b32 u, u, %44, %49, 0xEA; and.b32 t, t, u;\n"
      "setp.ne.u32 p, t, 0; vote.sync.all.pred p, p, 0xffffffff; @p bra R_D;\n"
      LL_RE3
      "add.u32 n, n, 1; setp.lt.u32 p, n, 262144; @p bra R_L; trap;\n"
      "R_D:\n"
      "}"
      : LL_O16(v[0]), LL_O16(v[1]), LL_O16(v[2])
      : "l"(p), "r"(nar)
      : "memory");
}

template <int NQ> __device__ __forceinline__ void load_x(const __nv_bfloat16* x, uint32_t sb, int r, int warp, int lane) {
  const int l8 = lane >> 3, c = lane & 7;
  const char* src = reinterpret_cast<const char*>(x + (size_t)(r * 128 + warp * 16 + l8) * DM + c * 8);
  const uint32_t dst = sb + (uint32_t)((warp >> 2) * (7 * U) + ((warp & 3) * 16 + l8) * 128 + ((c ^ l8) << 4));
#pragma unroll
  for (int kb = 0; kb < 7; kb++) {
#pragma unroll
    for (int q = 0; q < NQ; q++)
      asm volatile("cp.async.cg.shared.global [%0], [%1], 16;" ::"r"((dst ^ ((q & 1) << 6)) + kb * U + q * 512), "l"(src + q * 4 * DM * 2 + kb * 128) : "memory");
    asm volatile("cp.async.commit_group;" ::: "memory");
  }
}
template <int N> __device__ __forceinline__ void cp_wait() { asm volatile("cp.async.wait_group %0;" ::"n"(N) : "memory"); }

#define ORD 0
#define D64 1
#define QSH 7
#define WHOLD 5
#define WHT 2
#define FETCH 0
#define FD0 (ET + 4)
#define FD1 (ET + 4)
#define FD2 EG3
__device__ __forceinline__ void fetch_slot(uint32_t sb, int slot) {
}

template <int H> __device__ __forceinline__ void w2_tiles(const Maps& M, uint32_t sb, int j) {
  const int kq = j >> 1, n = j & 1;
  const int io = kq == 3 - 3 * n ? 2 : kq - n;
  const int cA = 256 * n + 64 * (io == 2 ? 0 : io + 1), cB = 256 * n + 64 * (io == 0 ? 2 : io - 1);
#pragma unroll 1
  for (int i = 0; i < 4; i++) {
    const uint32_t ut = H == 0 ? (i == 0 ? 0x12103634u : i == 1 ? 0x27252422u : i == 2 ? (D64 ? 0x03020100u : 0x0C040200u) : (D64 ? 0x37363534u : 0x12103634u))
                               : (i == 0 ? 0x20141E1Cu : i == 1 ? 0x2D2B2A28u : i == 2 ? 0x0D32302Eu : 0x14201E1Cu);
    const uint32_t fb = BAR(FT + (H == 0 ? (0x6520 >> (4 * i)) & 15 : (0x7431 >> (4 * i)) & 15));
    const uint32_t dt = H == 0 ? ED1 | (ED3 << 8) | (LH1 << 16) | ((ET + 0) << 24) : ED2 | (ED4 << 8) | (ED5 << 16) | ((ET + 1) << 24);
    const uint32_t dep = BAR((dt >> (8 * i)) & 255);
    const int pe = i < 2 ? H : i & 1, nn = n ^ pe, fb0 = (j ^ pe) * 224;
    const int r0 = fb0 + 32 * nn, r1 = fb0 + 192 * (1 - nn);
    const CUtensorMap* m = i >= 2 && H == 0 ? &M.w2c : &M.w2a;
    const int c2 = H == 0 ? 192 + 32 * n : 256 * n + 64 * io;
    if (H == 1 || i) mbar_wait(dep);
    tma2d(sb + (ut & 255) * 4096, m, i < 2 ? cA : c2, i == 1 ? r0 + 128 : r0, fb);
    tma2d(sb + ((ut >> 8) & 255) * 4096, i == 1 ? m + 1 : m, i == 0 ? cB : i == 1 ? cA : c2, i == 0 ? r0 : i == 1 ? r1 : r0 + 64, fb);
    if (H == 0 && !i) mbar_wait(dep);
    tma2d(sb + ((ut >> 16) & 255) * 4096, m, i == 0 ? cA : i == 1 ? cB : c2, i == 0 ? r0 + 64 : r0 + 128, fb);
    tma2d(sb + (ut >> 24) * 4096, i == 0 ? m : m + 1, i < 2 ? cB : c2, i == 0 ? r0 + 64 : r1, fb);
    TS(2, 10 + 2 * i + H);
  }
}

#define LANE() const int ln = laneid(), g8 = ln >> 2, t4 = ln & 3; (void)g8; (void)t4
__device__ __forceinline__ void tail(const __nv_bfloat16* x, __nv_bfloat16* out, uint32_t* hf, float* acc, const uint32_t* sg, float* rs_, uint32_t sb, uint32_t pb, int warp, bool lane0) {
  const int wg = warp >> 2, w4 = warp & 3;
  constexpr int BB = 300;
  float a1[64];
  const float hr[2] = {0.5f * rs_[0], 0.5f * rs_[1]}, hc[2] = {hr[0] * hr[0], hr[1] * hr[1]};
  auto e1 = [&](int lo) {
#pragma unroll
    for (int i = lo; i < lo + 16; i++) { acc[32 + i] *= acc[i]; acc[i] = tanh_(acc[i] * hr[(i >> 1) & 1]); }
    pin<16>(acc + lo); pin<16>(acc + 32 + lo);
  };
  auto e2 = [&](int lo) {
#pragma unroll
    for (int m = lo; m < lo + 8; m++) hf[32 + m] = pack2(acc[32 + 2 * m] * fmaf(acc[2 * m], hc[m & 1], hc[m & 1]), acc[33 + 2 * m] * fmaf(acc[2 * m + 1], hc[m & 1], hc[m & 1]));
    pinr<8>(hf + 32 + lo);
  };
  const uint32_t doff = (uint32_t)(wg * 12288 + w4 * 3072 + laneid() * 16);
  auto send = [&](int s) {
    sta4(pb + 11 * U + doff + s * 512, hf + 32 + 4 * s, pb + MISC + 8u * (HF + 4) + wg * 8);
    sta4(pb + 11 * U + doff + s * 512 + 512, hf + 36 + 4 * s, pb + MISC + 8u * (HF + 4) + wg * 8);
  };
  auto e3 = [&]() {
#pragma unroll
    for (int m = 0; m < 8; m++) {
      const int w = m & 1;
      hf[48 + m] = pack2(blo(sg[m]) * (acc[64 + 2 * m] * hr[w]), bhi(sg[m]) * (acc[65 + 2 * m] * hr[w]));
    }
    pinr<8>(hf + 48);
    send(4);
  };
  mbar_wait(BAR(PF + 2));
  e3();
  e1(0);
  BBARI(BB + 1);
  e1(16);
  e2(0); send(0);
  BBARI(BB + 3);
  e2(8); send(2);
  TS7(21);
  uint64_t dh = desc_base<6>(sb, 0);
  mbar_wait(BAR(FT + 0));
  wg_fence();
#pragma unroll
  for (int s = 0; s < 8; s++) rs<128>(a1, hf + 4 * s, desc((s < 4 ? 26 : 7) * U + s * 2048, U), s == 0);
  wg_commit();
  TS7(22);
  mbar_wait(BAR(FT + 1));
  wg_fence();
#pragma unroll
  for (int s = 0; s < 8; s++) rs<128>(a1, hf + 56 + 4 * s, desc((s < 4 ? 14 : 9) * U + s * 2048, s < 4 ? U : 6 * U), false);
  wg_commit();
  TS7(23);
  wg_wait<1>();
  if (lane0) mbar_arrive(BAR(ET + 0));
  mbar_wait(BAR(FT + 2));
  wg_fence();
#pragma unroll
  for (int s = 0; s < 6; s++) rs<128>(a1, hf + 32 + 4 * s, desc(17 * U + s * 2048, 12288), false);
  wg_commit();
  CTS(9);
  uint32_t par;
  asm volatile("ld.shared.u32 %0, [%1];" : "=r"(par) : "r"(BAR(NBAR)) : "memory");
  mbar_wait(BAR(HF + 4) + wg * 8);
#pragma unroll
  for (int s = 0; s < 6; s++) lds4(hf + 88 + 4 * s, sb + 11 * U + doff + s * 512);
  CTS(10);
  wg_wait<1>();
  if (lane0) mbar_arrive(BAR(ET + 1));
  const uint64_t adw = desc_base<5>(sb, wg * 512);
  float aw[32];
  auto wtile = [&](int t) {
    constexpr int wu[7] = {3, 11, 7, 17, 20, 23, 0};
    if (t == WHT) mbar_wait(BAR(wg ? EG3 : XC0));
    mbar_wait(BAR(FW + t));
    wg_fence();
#pragma unroll
    for (int kk = 0; kk < 4; kk++) {
      const uint64_t da = adw + dofs(wu[t] * U + kk * 32, 16), db = desc((ORD != 2 && !D64 && t == (ORD ? 5 : 6) ? 7 : wu[t] + 2) * U + kk * 2048, U);
      ssk<64>(aw, da, db, t == 0 && kk == 0);
    }
    wg_commit();
    if (t == WHOLD && lane0 && !wg) mbar_arrive_n(BAR(EG3), 2);
  };
  float a2[16];
  float* a3 = a1;
  const uint64_t d64 = desc_base<13, 0x80000020u>(sb, 0);
  auto g2 = [&](int p, int lo, int hi) {
    wg_fence();
#pragma unroll
    for (int s = lo; s < hi; s++) rs<32>(a2, hf + 56 * p + 4 * s, d64 + dofs((p ? 26 * U : 0) + s * 1024, 0), p == 0 && s == 0);
    wg_commit();
  };
  auto g3 = [&](int p, int lo, int hi) {
    wg_fence();
#pragma unroll
    for (int s = lo; s < hi; s++) {
      const uint64_t d = desc((p ? (s < 12 ? 14 * U : 7 * U) : (s < 12 ? 23 * U : 3 * U + 4096)) + s * 2048, U);
      if (p == 0 && s == 0) rsz<64>(a3, hf, d); else rs<64>(a3, hf + 56 * p + 4 * s, d, false);
    }
    wg_commit();
  };
  const int bid = par, r = bid >> 3, kq = (bid >> 1) & 3, n = bid & 1;
  const bool Y = kq == 3 - 3 * n;
  auto dest = [&](int c) {
    int b2 = bid;
    asm volatile("" : "+r"(b2));
    const int n2 = b2 & 1, k2 = (b2 >> 1) & 3, i2 = Y ? 2 : k2 - n2;
    const int tgt = c == 0 ? n2 + (i2 == 2 ? 0 : i2 + 1) : c == 1 ? n2 + (i2 == 0 ? 2 : i2 - 1) : Y ? n2 + 2 : 3 - 3 * n2;
    const int slot = c == 2 ? i2 : Y ? 2 : c;
    return g_p + (size_t)((((b2 >> 3) * 2 + n2) * 4 + tgt) * 3072 + slot * 1024 + warp * (c == 2 && !Y ? 64 : 128) + laneid());
  };
#define IBK
#define PRX 6
#define IBX ibx
#define GSP 8
#define G2A 7
#define G2B 7
#define SORD 0
#define EL0P 1
#define EL1P 3
#define LPX 7
  uint32_t v[3][16], xr[16];
#define LP0 5
#define LP1 5
#define LP2 5
  auto inbox = [&]() {
    int b2 = bid;
    asm volatile("" : "+r"(b2));
    return g_p + (size_t)((((b2 >> 3) * 2 + (b2 & 1)) * 4 + ((b2 >> 1) & 3)) * 3072 + warp * (Y ? 64 : 128) + laneid());
  };
  const uint4* ibx = nullptr;
  const uint4 *jbx = nullptr, *xsrc = nullptr;
  uint4* odst = nullptr;
  auto hook = [&](int t) {
    if (t == LP0 || t == LP1 || t == LP2) {
      const uint4* pi = inbox(), *pj = Y ? g_p : pi + 64;
      if (t == LP2) { ibx = pi; asm volatile("" : "+l"(ibx)); }
      if (t == LP0) ld_ll4(v[0], pi, pj);
      if (t == LP1) ld_ll4(v[1], pi + 1024, pj + 1024);
      if (t == LP2) ld_ll4(v[2], pi + 2048, pj + 2048);
    }
    if (t == PRX) {
      const int ln = laneid();
      int b2 = bid;
      asm volatile("" : "+r"(b2));
      const size_t e = (size_t)((b2 >> 3) * 128 + warp * 16 + (ln >> 3)) * DM + (Y ? 192 + 32 * (b2 & 1) : 192 * (b2 & 1) + 32 * (b2 & 6)) + (ln & (Y ? 3 : 7)) * 8;
      xsrc = reinterpret_cast<const uint4*>(x + e); odst = reinterpret_cast<uint4*>(out + e);
      asm volatile("" : "+l"(xsrc), "+l"(odst));
    }
    if (t == LPX) {
#pragma unroll
      for (int q = 0; q < 4; q++)
        asm volatile("ld.global.nc.L1::no_allocate.v4.b32 {%0,%1,%2,%3}, [%4];" : "=r"(xr[4 * q]), "=r"(xr[4 * q + 1]), "=r"(xr[4 * q + 2]), "=r"(xr[4 * q + 3]) : "l"(xsrc + q * (4 * DM / 8)) : "memory");
    }
    return;
    if (t == LPX) {
      const int ln = laneid();
      int b2 = bid;
      asm volatile("" : "+r"(b2));
      const uint4* src = reinterpret_cast<const uint4*>(x + (size_t)((b2 >> 3) * 128 + warp * 16 + (ln >> 3)) * DM + (Y ? 192 + 32 * (b2 & 1) : 192 * (b2 & 1) + 32 * (b2 & 6)) + (ln & (Y ? 3 : 7)) * 8);
#pragma unroll
      for (int q = 0; q < 4; q++)
        asm volatile("ld.global.nc.L1::no_allocate.v4.b32 {%0,%1,%2,%3}, [%4];" : "=r"(xr[4 * q]), "=r"(xr[4 * q + 1]), "=r"(xr[4 * q + 2]), "=r"(xr[4 * q + 3]) : "l"(src + q * (4 * DM / 8)) : "memory");
    }
  };
  mbar_wait(BAR(FT + 3));
  wg_fence();
#pragma unroll
  for (int s = 0; s < 6; s++) rs<128>(a1, hf + 88 + 4 * s, desc(20 * U + s * 2048, 12288), false);
  wg_commit();
  if (lane0) mbar_arrive(BAR(LD2));
  mbar_wait(BAR(CLR));
  TS7(26);
  wg_wait<1>();
  if (lane0) mbar_arrive(BAR(ET + 2));
  dh = desc_base<7>(sb, 0);
  mbar_wait(BAR(FT + 5));
  g2(0, 0, 7);
  mbar_wait(BAR(FT + 4));
  wg_wait<1>();
  if (lane0) mbar_arrive(BAR(ET + 3));
  pin<64>(a1);
  TS7(27);
  {
    uint32_t w[16];
#pragma unroll
    for (int i = 0; i < 16; i++) w[i] = pack2(a1[2 * i], a1[2 * i + 1]);
#pragma unroll
    for (int q = 0; q < 4; q++) w[4 * q] |= 1u;
    pinr<16>(w);
    g3(0, 0, 7);
    uint4* const pa = dest(0);
    stg4(pa, w); stg4(pa + 32, w + 4);
    BBARI(BB + 11);
    g3(0, 7, 14);
    stg4(pa + 64, w + 8); stg4(pa + 96, w + 12);
  }
  BBARI(BB + 13);
  TS7(28);
  mbar_wait(BAR(FT + 6));
  g2(0, 7, 14);
  wg_wait<1>();
  if (lane0) mbar_arrive(BAR(ET + 5));
  g2(1, 0, 7);
  send_ll<2>(dest(1), a1 + 32);
  BBARI(BB + 15);
  wg_wait<1>();
  if (lane0) mbar_arrive(BAR(ET + 6));
  mbar_wait(BAR(FT + 7));
  g2(1, 7, 14);
  g3(1, 0, 7);
  send_ll<2>(dest(1) + 64, a1 + 48);
  hook(-2);
  BBARI(BB + 17);
  wg_wait<1>();
  pin<16>(a2);
  g3(1, 7, 14);
  hook(-1);
  if (!Y) { send_ll<2>(dest(2), a2); }
  BBARI(BB + 19);
  CTS(16);
  dh = desc_base<8>(sb, 0);
  wtile(0);
  hook(0);
  wg_wait<1>();
  pin<32>(a3);
  CTS(11);
  if (Y) {
    send_ll<4>(dest(2), a3);
#pragma unroll
    for (int i = 0; i < 16; i++) a3[i] = a2[i];
  }
  pin<32>(a3);
  BBARI(BB + 21);
  wtile(1);
  LANE();
  const uint32_t lb = sb + (uint32_t)((3 + wg) * U + w4 * 2048);
  const int row = r * 128 + warp * 16 + (ln >> 3), col = (Y ? 192 + 32 * n : 192 * n + 64 * kq) + (ln & (Y ? 3 : 7)) * 8;
  hook(1);
#pragma unroll
  for (int t = 2; t < 7; t++) {
    wtile(t);
    if (t == 3) CTS(17);
    hook(t);
  }
  wg_wait<5>();
  if (lane0) mbar_arrive_n(BAR(wg ? XR1 : XR0), 2);
  CTS(18);
  uint32_t idm = (g8 >> 1) == t4 ? 0x3F80u << ((g8 & 1) * 16) : 0u;
  pinr<1>(&idm);
  mbar_wait(BAR(wg ? XR1 : XR0));
  CTS(19);
  {
    chk_ll(v, IBX, Y);
    hook(7);
  }
  CTS(20);
  {
#pragma unroll
    for (int b = 0; b < 8; b++)
#pragma unroll
      for (int i = 0; i < 3; i++) mma1688((ORD == 2 && b < 4 ? a2 : a3) + 4 * b, v[i][2 * b], v[i][2 * b + 1], idm);
  }
#pragma unroll
  for (int i = 0; i < 32; i++) { const float u = ORD == 2 && i < 16 ? a2[i & 15] : a3[i]; a3[i] = fmaf(u, tanh_(u), u); }
  pin<32>(a3);
  wg_wait<0>();
  pin<32>(aw);
  CTS(12);
  const uint32_t sa = lb + (uint32_t)((ln & 15) * 128 + (((ln >> 4) ^ (ln & 7)) << 4));
#pragma unroll
  for (int kk = 0; kk < 4; kk++) {
    uint32_t o[4];
#pragma unroll
    for (int m = 4 * kk; m < 4 * kk + 4; m++) o[m & 3] = pack2(aw[2 * m] * a3[2 * m], aw[2 * m + 1] * a3[2 * m + 1]);
    stsm4(sa ^ (kk << 5), o[0], o[1], o[2], o[3]);
  }
  __syncwarp();
  {
    const int c = ln & 7, l8 = ln >> 3;
    uint4* dst = odst;
    uint32_t w[16];
#pragma unroll
    for (int q = 0; q < 4; q++) lds4(w + 4 * q, lb + (uint32_t)((q * 4 + l8) * 128 + ((c ^ ((q * 4 + l8) & 7)) << 4)));
#pragma unroll
    for (int i = 0; i < 16; i++) asm("add.rn.bf16x2 %0, %0, %1;" : "+r"(w[i]) : "r"(xr[i]));
    if (!Y || c < 4) {
#pragma unroll
      for (int q = 0; q < 4; q++) dst[q * (4 * DM / 8)] = make_uint4(w[4 * q], w[4 * q + 1], w[4 * q + 2], w[4 * q + 3]);
    }
  }
}

__global__ void __cluster_dims__(2, 1, 1) __launch_bounds__(384, 1)
fused_kernel(const __grid_constant__ Ptrs P, const __grid_constant__ Maps M) {
  const __nv_bfloat16* xg = (&P.x)[threadIdx.x >> 10];
  asm volatile("{ .reg .pred p; setp.ne.u32 p, %0, 4095; @p bra B_L; trap; B_L: }" ::"r"(threadIdx.x), "l"(xg) : "memory");
  extern __shared__ __align__(1024) uint8_t smem_raw[];
  uint32_t sb = smem_u32(smem_raw);
  asm volatile("" : "+r"(sb));
  const int tid = threadIdx.x;
  const int warp = __shfl_sync(0xffffffffu, tid >> 5, 0);
  const int lane = tid & 31;
  const int wg = warp >> 2;
  const int bid = role_of(blockIdx.x), r = bid >> 3, j = bid & 7, kq = j >> 1, n = j & 1;

  asm volatile("{ .reg .pred p; setp.ne.u32 p, %0, 4095; @p bra B_L; trap; B_L: }" ::"r"(bid) : "memory");
  if (warp < 8) CTS(27);
  if (warp < 4) load_x<HX0>(xg, sb, r, warp, lane);
  if (warp < 8) CTS(28);
  if (elect_one()) {
    if ((warp >> 1) == 4) {
      const uint32_t ba = BAR(FA) + (warp - 8) * 8;
      mbar_init(ba, 1);
      mbar_expect_tx(ba, 2 * U);
      tma3d(sb + (14 + 2 * (warp - 8) + n) * U, &M.kv, j * 56 - 8 * n, (warp - 8) * 64, 1 + n, ba);
      tma3d(sb + (15 + 2 * (warp - 8) - n) * U, &M.kv, j * 56 - 8 * n, (warp - 8) * 64, 2 - n, ba);
    }
    const uint32_t b0 = BAR(2 + 8 * warp), cnt = warp < 6 ? 1u : 8u;
#pragma unroll
    for (int i = 0; i < 8; i++) mbar_init(b0 + 8 * i, cnt);
    if (warp >= 2) { mbar_init(BAR(94 + 2 * warp), 8); mbar_init(BAR(95 + 2 * warp), 8); }
  }
  asm volatile("fence.mbarrier_init.release.cluster;" ::: "memory");
  __syncwarp();
  if (warp < 8) CTS(29);
  asm volatile("barrier.cluster.arrive.relaxed.aligned;" ::: "memory");

  if ((warp & 8) != 0) {
    asm volatile("setmaxnreg.dec.sync.aligned.u32 24;");
    if (warp == 8) {
      asm volatile("barrier.cluster.wait.acquire.aligned;" ::: "memory");
      if (elect_one()) {
        TS(2, 9);
        const int f0 = j * 224, ca = j * 56 - 8 * n;
#pragma unroll 1
        for (int g = 2; g < 7; g++) {
          mbar_expect_tx(BAR(FA + g), 2 * U);
          tma3d(sb + (14 + 2 * g + n) * U, &M.kv, ca, g * 64, 1 + n, BAR(FA + g));
          tma3d(sb + (15 + 2 * g - n) * U, &M.kv, ca, g * 64, 2 - n, BAR(FA + g));
        }
        TS(2, 1);
        const int ro = f0 + 32 * n, rg = f0 + 192 * (1 - n);
#pragma unroll 1
        for (int p = 0; p < 3; p++) {
          const uint64_t ut = p == 0 ? packtab(unitB) : p == 1 ? packtab(unitC) : packtab(unitD);
          const uint64_t dt = p == 0 ? packtab(depB) : p == 1 ? packtab(depC) : packtab(depD);
          const CUtensorMap* m3 = p == 0 ? &M.wq : p == 1 ? &M.w1b : &M.w3b;
          const int c3 = p == 0 ? ca : rg;
#pragma unroll 1
          for (int g = 0; g < 7; g++) {
            const uint32_t dst = sb + (uint32_t)((ut >> (8 * g)) & 255) * U;
            const uint32_t fb = BAR(FB + 7 * p + g);
            mbar_wait_to(BAR((uint32_t)((dt >> (8 * g)) & 255)));
            tma2d(dst, &M.w1a, ro + 64 * p, g * 64, fb);
            tma2d(dst + U, &M.w3a, ro + 64 * p, g * 64, fb);
            tma2d(dst + 2 * U, m3, c3, g * 64, fb);
          }
          TS(2, 2 + p);
        }
        fetch_slot(sb, 2);
        asm volatile("{ .reg .pred p, q; .reg .u32 n; mov.u32 n, 0;\n"
                     "W_L: nanosleep.u32 400; mbarrier.test_wait.parity.shared::cta.b64 p, [%0], 0; mbarrier.test_wait.parity.shared::cta.b64 q, [%1], 0; and.pred p, p, q;\n"
                     "@p bra W_D;\n add.u32 n, n, 1;\n setp.lt.u32 p, n, 2097152;\n @p bra W_L;\n trap;\n W_D: }" ::"r"(BAR(XR0)), "r"(BAR(XR1)) : "memory");
      }
    } else {
      if (elect_one()) {
        const CUtensorMap* mp = &M.kv + (warp - 9) * 4 + 2;
        if ((sb & 0x3FFFFu) != SM_BASE) asm volatile("trap;");
#pragma unroll
        for (int i = 0; i < 4; i++) map_prefetch(mp + i);
        if (warp == 9) map_prefetch(&M.wq);
      }
      const uint32_t ep = g_epoch[blockIdx.x] + 1;
      const int at = tid - 288;
      if (at < 32) reinterpret_cast<float4*>(g_kv + ((ep & 1) ^ 1) * (8 * 2048) + j * 2048 + r * 128)[at] = make_float4(0.f, 0.f, 0.f, 0.f);
      asm volatile("barrier.cluster.wait.acquire.aligned;" ::: "memory");
      float* kv = g_kv + (ep & 1) * (8 * 2048) + j * 2048;
      if (at < 43) {
        const int b = FB + at;
        const uint32_t kb = b < FC ? 24 : b < FT ? 20 : b < FT + 2 ? 32 : b < FT + 4 ? 24 : b == FT + 4 || b == FT + 7 ? 28 : b < FW ? 14 : b < HF ? (kq == 3 - 3 * n ? 20 : 24) - OMIN : b < HF + 4 ? 8 : 12;
        mbar_expect_tx(BAR(b), b == KVL ? KV_BYTES : kb << 10);
      }
      if (lane == 0) asm volatile("st.shared.v2.u32 [%0], {%1, %2};" ::"r"(BAR(NBAR)), "r"(bid), "r"(ep) : "memory");
#define CLP 0
      mbar_wait(BAR(XC1));
      if (warp == 11) {
          const bool isy = kq == 3 - 3 * n;
          uint4* ib = g_p + (size_t)((r * 2 + n) * 4 + kq) * 3072 + lane;
#pragma unroll 1
          for (int i = 0; i < 3; i++, ib += 1024) {
#pragma unroll 4
            for (int q = 0; q < (isy ? 512 : 1024); q += 32) asm volatile("st.relaxed.gpu.global.v4.b32 [%0], {%1,%1,%1,%1};" ::"l"(ib + q), "r"(0) : "memory");
          }
      }
      mbar_wait(BAR(EA6));
      const uint32_t kvm = sb + KVM_U * U;
#pragma unroll 1
      for (int c = at; c < 512; c += 96) {
        const int d = c >> 3, cc = c & 7;
        const bool used = d < 56 && (cc == 7 || (d < 28 ? cc < 4 : (cc >= 3)));
        if (!used) { const uint32_t z[4] = {0, 0, 0, 0}; sts4(kvm + d * 128 + ((cc ^ (d & 7)) << 4), z); }
      }
      if (warp == 9) {
        mbar_wait(BAR(KVST));
        if (elect_one()) {
          asm volatile("cp.reduce.async.bulk.global.shared::cta.bulk_group.add.f32 [%0], [%1], %2;" ::"l"(kv), "r"(sb + 27 * U), "r"(KV_BYTES) : "memory");
          bulk_commit();
          bulk_wait_all();
          TS(3, 4);
          SIGNAL(&g_f1[j * 32]);
          TS(3, 0);
          poll_flag(&g_f1[j * 32], 16u * ep);
          asm volatile("fence.proxy.async.global;" ::: "memory");
          TS(3, 1);
          asm volatile("cp.async.bulk.shared::cluster.global.mbarrier::complete_tx::bytes [%0], [%1], %2, [%3];" ::"r"(sb + 27 * U), "l"(kv), "r"(KV_BYTES), "r"(BAR(KVL)) : "memory");
        }
        __syncwarp();
      }
      {
        auto cv = [](uint32_t* w, const uint32_t* v, bool z01, bool z23) {
          w[0] = z01 ? 0u : pack2(__uint_as_float(v[0]), __uint_as_float(v[1])); w[1] = z01 ? 0u : pack2(__uint_as_float(v[2]), __uint_as_float(v[3]));
          w[2] = z23 ? 0u : pack2(__uint_as_float(v[4]), __uint_as_float(v[5])); w[3] = z23 ? 0u : pack2(__uint_as_float(v[6]), __uint_as_float(v[7]));
        };
        uint32_t v[8], u[8], w[4];
        const uint32_t s0 = sb + 27 * U + (at >> 2) * (KVP * 4) + (at & 3) * 32;
        mbar_wait(BAR(KVL));
        if (at == 0) TS(3, 20);
        lds4(v, s0); lds4(v + 4, s0 + 16);
        lds4(u, s0 + 24 * KVP * 4); lds4(u + 4, s0 + 24 * KVP * 4 + 16);
        int a2 = at;
        asm volatile("" : "+r"(a2));
        const int m = a2 & 3, d0 = a2 >> 2;
        cv(w, v, false, m == 3);
        sts4(kvm + d0 * 128 + ((m ^ (d0 & 7)) << 4), w);
        const bool zi = a2 >= 32;
        const int d2 = zi ? min(a2 - 32, 55) : 48 + d0;
        const uint32_t s2 = sb + 27 * U + d2 * (KVP * 4) + (zi ? 128 : m * 32);
        lds4(v, s2); lds4(v + 4, s2 + (zi ? 0 : 16));
        const int d1 = d0 + 24;
        cv(w, u, d1 >= 28 && m == 0, d1 < 28 && m == 3);
        sts4(kvm + d1 * 128 + (((m + (d1 >= 28 ? 3 : 0)) ^ (d1 & 7)) << 4), w);
        cv(w, v, m == 0, false);
        if (zi) w[0] = w[1] = w[2] = w[3] = pack2(__uint_as_float(v[0]), 0.f) << (d2 >= 28 ? 16 : 0);
        sts4(kvm + d2 * 128 + (((zi ? 7 : m + 3) ^ (d2 & 7)) << 4), w);
        if (at == 0) TS(3, 21);
      }
      fence_async();
      __syncwarp();
      if (lane == 0) mbar_arrive_n(BAR(KVM), warp < 11 ? 3 : 2);
      if (at == 0) TS(3, 2);
      if (warp < 11) {
        const int h = warp - 9;
        const uint32_t pb = mapa(sb, n ^ 1);
#pragma unroll 1
        for (int b = 0; b < 2; b++) {
          const uint32_t off = (uint32_t)((2 * b + (h ? 0 : 3)) * U + lane * 16), dd = b && h ? 5 * U : U, rb = pb + MISC + 8u * (HF + 2 * b + h);
          mbar_wait(BAR(HS + 2 * b + h));
          mbar_wait(BAR(PF + b));
#pragma unroll 1
          for (int i = 0; i < 8192; i += 1024) {
            uint32_t v[8];
            lds4(v, sb + off + i); lds4(v + 4, sb + off + i + 512);
            sta4(pb + dd + off + i, v, rb); sta4(pb + dd + off + i + 512, v + 4, rb);
          }
          if (h == 1 && lane == 0) { TS(3, 22 + b); }
        }
        __syncwarp();
        if (elect_one()) {
          if (h == 0) { mbar_arrive_n(BAR(LHA), 4); w2_tiles<1>(M, sb, j); }
          else { mbar_wait(BAR(OFREE)); w2_tiles<0>(M, sb, j); }
          fetch_slot(sb, h);
        }
      } else {
        if (elect_one()) {
        asm volatile("fence.acq_rel.gpu;" ::: "memory");
#pragma unroll 1
        for (int h = 0; h < 2; h++) {
          mbar_wait(BAR(OST + h));
          tma2d_store(&M.ost, j * 56, r * 128 + h * 64, sb + 27 * U);
          bulk_commit();
          bulk_wait_read();
          mbar_arrive_n(BAR(h ? OFREE : OF0), 8);
          bulk_wait_all();
          SIGNAL(&g_f2[r * 32]);
          TS(3, 24 + h);
        }
        uint32_t ep2;
        asm volatile("ld.shared.u32 %0, [%1];" : "=r"(ep2) : "r"(BAR(NBAR) + 4) : "memory");
        poll_flag(&g_f2[r * 32], 16u * ep2);
        mbar_arrive_n(BAR(CLR), 8);
        asm volatile("fence.proxy.async.global;" ::: "memory");
        TS(3, 5);
        const bool isy = kq == 3 - 3 * n;
        const int co = isy ? 192 + 32 * n : 192 * n + 64 * kq;
#pragma unroll 1
        for (int t = 0; t < 7; t++) {
          const uint64_t dt = (uint64_t)ED6 | ((uint64_t)LD2 << 8) | ((uint64_t)(ET + 0) << 16) | ((uint64_t)(ET + 2) << 24) | ((uint64_t)(ET + 3) << 32) |
                              ((uint64_t)(ET + 5) << 40) | ((uint64_t)(ET + 6) << 48);
          const uint32_t dst = sb + (uint32_t)((0x00171411070B03ull >> (8 * t)) & 255) * U;
          mbar_wait(BAR((uint32_t)((dt >> (8 * t)) & 255)));
          tma2d(dst, &M.o, t * 64, r * 128, BAR(FW + t));
          tma2d(ORD != 2 && !D64 && t == (ORD ? 5 : 6) ? sb + 7 * U : dst + 2 * U, isy ? &M.wob : &M.woa, co, t * 64, BAR(FW + t));
          TS(3, 10 + t);
        }
        uint32_t bx;
        asm volatile("mov.u32 %0, %%ctaid.x;" : "=r"(bx));
        g_epoch[bx] = ep2;
        TS(3, 6);
        }
      }
    }
  } else {
    asm volatile("setmaxnreg.inc.sync.aligned.u32 240;");
    asm volatile("barrier.cluster.wait.acquire.aligned;" ::: "memory");
    CTS(0);
    if (wg == 1) load_x<HX1>(xg, sb, r, warp, lane);
    const int w4 = warp & 3;
    const bool lane0 = lane == 0;
    const uint32_t pb = mapa(sb, n ^ 1);
    const uint32_t so = sb + (uint32_t)((wg * 64 + w4 * 16 + (lane & 7) + ((lane >> 3) & 1) * 8) * 128 + (((lane >> 4) ^ (lane & 7)) << 4));
    uint32_t xf[112];
    float rs_[2];
    uint32_t pm0, pm1;
    float q0, q1;
    {
      float cm[2][4], ga[2][4], gb[2][4];
#pragma unroll
      for (int i = 0; i < 8; i++) cm[i >> 2][i & 3] = ga[i >> 2][i & 3] = gb[i >> 2][i & 3] = 0.f;
      const uint32_t sx = so + wg * (6 * U);
      uint32_t s0 = 0, s1 = 0;
#pragma unroll
      for (int kb = 0; kb < 7; kb++) {
        if (kb == 0) cp_wait<6>(); else if (kb == 1) cp_wait<5>(); else if (kb == 2) cp_wait<4>(); else if (kb == 3) cp_wait<3>();
        else if (kb == 4) cp_wait<2>(); else if (kb == 5) cp_wait<1>(); else cp_wait<0>();
        __syncwarp();
        if (kb == 0) CTS(14);
        EPI_TS(if (kb == 3) CTS(26));
        if (kb == 6) CTS(15);
#pragma unroll
        for (int kk = 0; kk < 4; kk++) ldsm4(xf + 16 * kb + 4 * kk, (sx ^ (kk << 5)) + kb * U);
#pragma unroll
        for (int kk = 0; kk < 4; kk++) mma16816(cm[kk & 1], xf + 16 * kb + 4 * kk, 0x3F803F80u, 0x3F803F80u);
        if (kb == 0) {
          s0 = __byte_perm(__shfl_sync(0xffffffffu, xf[0], lane & 28), 0, 0x1010);
          s1 = __byte_perm(__shfl_sync(0xffffffffu, xf[1], lane & 28), 0, 0x1010);
        }
        if (kb == 6) {
          const float m0 = (cm[0][0] + cm[1][0]) * (1.0f / 448.0f), m1 = (cm[0][2] + cm[1][2]) * (1.0f / 448.0f);
          pm0 = pack2(m0, m0); pm1 = pack2(m1, m1);
          q0 = m0 - blo(s0); q1 = m1 - blo(s1);
          __syncwarp();
          if (lane0) mbar_arrive_n(BAR(XC0) + wg * 8, 2);
        }
#pragma unroll
        for (int kk = 0; kk < 4; kk++) {
          const uint32_t* a = xf + 16 * kb + 4 * kk;
          uint32_t t[4];
#pragma unroll
          for (int i = 0; i < 4; i++) asm volatile("sub.rn.bf16x2 %0, %1, %2;" : "=r"(t[i]) : "r"(a[i]), "r"((i & 1) ? s1 : s0));
          mma16816(ga[kk & 1], t, t[0], t[2]);
          mma16816(gb[kk & 1], t, t[1], t[3]);
        }
      }
#pragma unroll
      for (int i = 0; i < 16; i++) asm volatile("sub.rn.bf16x2 %0, %0, %1;" : "+r"(xf[i]) : "r"((i & 1) ? pm1 : pm0));
      const bool odd = (lane >> 2) & 1;
      rs_[0] = odd ? ga[0][1] + ga[1][1] : ga[0][0] + ga[1][0];
      rs_[1] = odd ? gb[0][3] + gb[1][3] : gb[0][2] + gb[1][2];
    }
    CTS(1);
    uint32_t pq[14];
    {
      float acc[60];
      if (wg) mbar_wait(BAR(XH));
      pass1<0, 120>(acc, xf, sb, pb, lane0, 0, desc_base<0>(sb, n), [&](int g) {
        if (g < 6) {
#pragma unroll
          for (int i = 0; i < 16; i++) asm volatile("sub.rn.bf16x2 %0, %0, %1;" : "+r"(xf[16 * g + 16 + i]) : "r"((i & 1) ? pm1 : pm0));
        }
        if (g == 1) {
          const int src = (lane & 28) | (lane >> 3);
          const float v0 = fmaxf(fmaf(__shfl_sync(0xffffffffu, rs_[0], src), 1.0f / 448.0f, -q0 * q0), 0.f);
          const float v1 = fmaxf(fmaf(__shfl_sync(0xffffffffu, rs_[1], src), 1.0f / 448.0f, -q1 * q1), 0.f);
          rs_[0] = rcp(bfr(sqrt_(bfr(bfr(v0) + 1e-5f))));
          rs_[1] = rcp(bfr(sqrt_(bfr(bfr(v1) + 1e-5f))));
          pin<2>(rs_);
        }
      }, [&](int g) {
        if (g == AHOLD && lane0 && wg == 0) mbar_arrive_n(BAR(XH), 2);
      });
      CTS(2);
      LANE();
      uint32_t pk[16], pv[16];
      float e[28];
      {
        const float rl[2] = {rs_[0] * LOG2E, rs_[1] * LOG2E};
#pragma unroll
        for (int i = 0; i < 28; i++) e[i] = ex2(acc[i] * rl[(i >> 1) & 1]);
#pragma unroll
        for (int m = 0; m < 14; m++) pk[m] = pack2r(acc[2 * m] * rs_[m & 1], acc[2 * m + 1] * rs_[m & 1]);
        pin<28>(e); pinr<14>(pk);
      }
#pragma unroll
      for (int m = 0; m < 14; m++) pv[m] = pack2(acc[32 + 2 * m] * rs_[m & 1], acc[33 + 2 * m] * rs_[m & 1]);
      pv[14] = pv[15] = t4 == 0 ? 0x3F803F80u : 0u;
      pinr<16>(pv);
      TS4(21);
      mbar_wait(BAR(XC1));
      TS4(22);
#pragma unroll
      for (int kk = 0; kk < 4; kk++) stsm4((so ^ (kk << 5)) + 11 * U, pv[4 * kk], pv[4 * kk + 1], pv[4 * kk + 2], pv[4 * kk + 3]);
#pragma unroll
      for (int m = 0; m < 14; m++) pk[m] = phi2(e[2 * m], e[2 * m + 1], pk[m], 0x3F803F80u);
      pk[14] = pk[15] = 0u;
#pragma unroll
      for (int kk = 0; kk < 4; kk++) stsm4((so ^ (kk << 5)) + 6 * U, pk[4 * kk], pk[4 * kk + 1], pk[4 * kk + 2], pk[4 * kk + 3]);
      TS4(23);
      fence_async();
      __syncwarp();
      if (lane0) mbar_arrive(BAR(PKST));
      TS4(24);
      CTS(3);
    }
    const uint32_t hoff = (uint32_t)((wg ? 0 : 3 * U) + w4 * 2048 + laneid() * 16);
    {
      float acc[92];
      auto kvout = [&](float* kv) {
          wg_wait<1>();
          if (lane0 && wg) mbar_arrive_n(BAR(KVFREE), 2);
          pin<32>(kv);
          TS4(26);
          LANE();
#pragma unroll
          for (int h = 0; h < 2; h++) {
            const int d = w4 * 16 + g8 + 8 * h + (KVOV == 4 ? 64 - 64 * wg : 0);
            const uint32_t lim = d < 28 ? 0u : d < 56 ? 28u : 1000u;
            const uint32_t ka = sb + 27 * U + (uint32_t)d * (KVP * 4) + (uint32_t)(2 * t4) * 4 - (d < 28 ? 0u : 96u);
#pragma unroll
            for (int i = 0; i < 7; i++)
              asm volatile("{ .reg .pred p; setp.lt.u32 p, %0, 28; @p st.shared.v2.f32 [%1], {%2,%3}; }" ::"r"((uint32_t)(8 * i + 2 * t4) - lim), "r"(ka + 32 * i), "f"(kv[4 * i + 2 * h]), "f"(kv[4 * i + 2 * h + 1]) : "memory");
            asm volatile("{ .reg .pred p; setp.lt.u32 p, %0, 56; @p st.shared.f32 [%1], %2; }" ::"r"((uint32_t)(d + 64 * t4)), "r"(sb + 27 * U + (uint32_t)d * (KVP * 4) + 128), "f"(kv[28 + 2 * h]) : "memory");
          }
          TS4(27);
          fence_async();
          __syncwarp();
          if (lane0 && wg) mbar_arrive_n(BAR(KVST), 2);
      };
      {
        const uint64_t dh = desc_base<11>(sb, 0);
        if (wg == 1) {
          float kv[32];
          mbar_wait(BAR(PKST));
          wg_fence();
#pragma unroll
          for (int ks = 0; ks < 8; ks++) {
            if (ks == 0) ss64_0(kv, desc(6 * U, U), desc(11 * U, U));
            else ss64_1(kv, desc(6 * U + ks * 2048, U), desc(11 * U + ks * 2048, U));
          }
          wg_commit();
          mbar_wait(BAR(FB));
          wg_fence();
#pragma unroll
          for (int kk = 0; kk < 4; kk++) rs<128>(acc, xf + 4 * kk, desc(unitB(0) * U + kk * 2048, U), kk == 0);
          wg_commit();
          kvout(kv);
          if (KVOV == 3) { wg_wait<0>(); pin<64>(acc); }
        } else {
          mbar_wait(BAR(FB));
          wg_fence();
#pragma unroll
          for (int kk = 0; kk < 4; kk++) rs<128>(acc, xf + 4 * kk, desc(unitB(0) * U + kk * 2048, U), kk == 0);
          wg_commit();
          if (KVOV == 3) { wg_wait<0>(); pin<64>(acc); }
        }
      }

      pass1<1, 184>(acc, xf, sb, pb, lane0, desc_base<1>(sb, 0), desc_base<2>(sb, n), [&](int) {}, [&](int g) {
      });
      CTS(4);
      pin<2>(rs_);
      uint32_t h[16];
      hfrag64<1>(h, acc, rs_, sb, wg);
      pinr<16>(h);
      mbar_wait(BAR(EB1));
      EPI_TS(CTS(23));
#pragma unroll
      for (int s = 0; s < 4; s++) sts4(sb + hoff + s * 512, h + 4 * s);
      __syncwarp();
      if (lane0) mbar_arrive_n(BAR(HS) + wg * 8, 2);
      EPI_TS(CTS(24));
#pragma unroll
      for (int m = 0; m < 14; m++) pq[m] = pack2(acc[64 + 2 * m] * rs_[m & 1], acc[65 + 2 * m] * rs_[m & 1]);
      pinr<14>(pq);
      CTS(5);
    }
    uint32_t sg[8];
    {
      float acc[80];
      pass1<2, 160>(acc, xf, sb, pb, lane0, desc_base<3>(sb, 0), 0, [&](int g) {
#pragma unroll
        for (int m = QSH * g; m < QSH * g + QSH && m < 14; m++) {
          uint32_t r;
          asm("max.bf16x2 %0, %1, %2;" : "=r"(r) : "r"(pq[m]), "r"(0));
          pq[m] = phi2(ex2(blo(pq[m]) * LOG2E), ex2(bhi(pq[m]) * LOG2E), r, 0x3F803F80u);
          if (m >= 12) pq[m] ^= sb;
          pinr<1>(pq + m);
        }
      }, [&](int) {});
      CTS(6);
      pin<2>(rs_);
      uint32_t h[16];
      hfrag64<2>(h, acc, rs_, sb, wg);
      pinr<16>(h);
      TS5(21);
      mbar_wait(BAR(EC0 + 1));
      TS5(22);
#pragma unroll
      for (int s = 0; s < 4; s++) sts4(sb + 2 * U + hoff + s * 512, h + 4 * s);
      __syncwarp();
      if (lane0) mbar_arrive_n(BAR(HS + 2) + wg * 8, 2);
      float nm[32];
      TS5(23);
      mbar_wait(BAR(KVM));
      TS5(24);
      {
        uint32_t q3[4];
        const uint64_t dh = desc_base<10>(sb, 0);
        asm volatile("xor.b32 %0, %4, %6; xor.b32 %1, %5, %6; mov.b32 %2, 0; mov.b32 %3, 0;" : "=r"(q3[0]), "=r"(q3[1]), "=r"(q3[2]), "=r"(q3[3]) : "r"(pq[12]), "r"(pq[13]), "r"(sb));
        wg_fence();
        rs64_0(nm, pq, desc(KVM_U * U, U));
        rs64_1(nm, pq + 4, desc(KVM_U * U + 2048, U));
        rs64_1(nm, pq + 8, desc(KVM_U * U + 4096, U));
        rs64_1(nm, q3, desc(KVM_U * U + 6144, U));
      }
      wg_commit();
      float th[16];
      {
        const float hr[2] = {0.5f * rs_[0], 0.5f * rs_[1]};
#pragma unroll
        for (int i = 0; i < 16; i++) { acc[64 + i] *= hr[(i >> 1) & 1]; th[i] = tanh_(acc[64 + i]); }
        pin<16>(th); pin<16>(acc + 64);
      }
#pragma unroll
      for (int m = 0; m < 8; m++) sg[m] = pack2(fmaf(acc[64 + 2 * m], th[2 * m], acc[64 + 2 * m]), fmaf(acc[65 + 2 * m], th[2 * m + 1], acc[65 + 2 * m]));
      pinr<8>(sg);
      wg_wait<0>();
      pin<32>(nm);
      TS5(25);
      LANE();
      float rd[4];
#pragma unroll
      for (int i = 0; i < 4; i++) rd[i] = rcp(nm[28 + i] + 1e-6f);
      uint32_t ob[14];
#pragma unroll
      for (int i = 0; i < 7; i++) {
        const bool h0 = i < 3 || (i == 3 && t4 < 2);
        const float ra = h0 ? rd[0] : rd[1], rb = h0 ? rd[2] : rd[3];
        ob[2 * i] = pack2(nm[4 * i] * ra, nm[4 * i + 1] * ra);
        ob[2 * i + 1] = pack2(nm[4 * i + 2] * rb, nm[4 * i + 3] * rb);
      }
      pinr<14>(ob);
      TS5(26);
      if (wg) mbar_wait(BAR(OF0));
      const uint32_t sa = sb + 27 * U + (uint32_t)(w4 * 16 + (ln & 15)) * 112;
#pragma unroll
      for (int kk = 0; kk < 3; kk++) stsm4(sa + (ln >> 4) * 16 + kk * 32, ob[4 * kk], ob[4 * kk + 1], ob[4 * kk + 2], ob[4 * kk + 3]);
      stsm2(sa + 96, ob[12], ob[13]);
      TS5(27);
      fence_async();
      __syncwarp();
      if (lane0) mbar_arrive_n(BAR(OST) + wg * 8, 2);
      CTS(7);
    }
    uint32_t hf[112];
    float acc[80];
    pass1<3, 160>(acc, xf, sb, pb, lane0, desc_base<4>(sb, 0), 0, [&](int g) {
      if (g >= 5) {
        uint32_t one;
        if (g == 5) {
          BBARI(101);
          asm volatile("{ .reg .b32 t; lop3.b32 t, %1, %2, %3, 0xFE; lop3.b32 t, t, %4, %5, 0xFE; lop3.b32 t, t, %6, %7, 0xFE; lop3.b32 t, t, %8, %9, 0xFE; lop3.b32 t, t, %10, %11, 0xFE;\n"
                       "lop3.b32 t, t, %12, 1, 0xFE; redux.sync.min.u32 t, t, 0xffffffff; min.u32 %0, t, 1; }"
                       : "=r"(one) : "r"(hf[0]), "r"(hf[4]), "r"(hf[8]), "r"(hf[12]), "r"(hf[16]), "r"(hf[20]), "r"(hf[24]), "r"(hf[28]), "r"(hf[56]), "r"(hf[60]), "r"(hf[64]), "r"(hf[68]));
          if (lane0 && wg == 0) mbar_arrive_n(BAR(LHA), one);
        } else {
          BBARI(103);
          asm volatile("{ .reg .b32 t; lop3.b32 t, %1, %2, %3, 0xFE; lop3.b32 t, t, %4, 1, 0xFE; redux.sync.min.u32 t, t, 0xffffffff; min.u32 %0, t, 1; }"
                       : "=r"(one) : "r"(hf[72]), "r"(hf[76]), "r"(hf[80]), "r"(hf[84]));
          if (lane0) mbar_arrive_n(BAR(LH1), one);
        }
      }
      if (g >= 2 && g < 6) {
        const int b = (g >> 1) - 1, pe = g & 1;
        uint32_t* d = hf + 56 * pe + 16 * b;
        if (pe) mbar_wait(BAR(HF + 2 * b) + wg * 8);
#pragma unroll
        for (int s = 0; s < 4; s++) lds4t(d + 4 * s, xf + 16 * (g - 2) + 4 * s, sb + (pe ? (b ? 3 * U + wg * (4 * U) : U) : 2 * b * U) + hoff + s * 512);
        pinr<16>(d);
      }
    }, [&](int) {});
    CTS(8);
    tail(P.x, P.out, hf, acc, sg, rs_, sb, pb, warp, lane0);
    CTS(13);
    if ((tid & 127) == 0) { GTS(wg, 30); TSDUMP(wg); if (wg == 1) { TSDUMP(3); } }
  }
}

typedef CUresult (*EncodeFn)(CUtensorMap*, CUtensorMapDataType, cuuint32_t, void*, const cuuint64_t*, const cuuint64_t*, const cuuint32_t*,
                             const cuuint32_t*, CUtensorMapInterleave, CUtensorMapSwizzle, CUtensorMapL2promotion, CUtensorMapFloatOOBfill);

void make_map(EncodeFn enc, CUtensorMap* m, const void* base, uint64_t cols, uint64_t rows, uint32_t bc, uint32_t br, int sw) {
  cuuint64_t dims[2] = {cols, rows}, str[1] = {cols * 2};
  cuuint32_t box[2] = {bc, br}, es[2] = {1, 1};
  enc(m, CU_TENSOR_MAP_DATA_TYPE_BFLOAT16, 2, const_cast<void*>(base), dims, str, box, es, CU_TENSOR_MAP_INTERLEAVE_NONE,
      sw == 2 ? CU_TENSOR_MAP_SWIZZLE_64B : sw ? CU_TENSOR_MAP_SWIZZLE_128B : CU_TENSOR_MAP_SWIZZLE_NONE, CU_TENSOR_MAP_L2_PROMOTION_L2_128B, CU_TENSOR_MAP_FLOAT_OOB_FILL_NONE);
}
void make_map3(EncodeFn enc, CUtensorMap* m, const void* base, uint64_t sec, uint64_t nsec, uint64_t rows, uint32_t bc, uint32_t br, uint32_t bs) {
  cuuint64_t dims[3] = {sec, rows, nsec}, str[2] = {sec * nsec * 2, sec * 2};
  cuuint32_t box[3] = {bc, br, bs}, es[3] = {1, 1, 1};
  enc(m, CU_TENSOR_MAP_DATA_TYPE_BFLOAT16, 3, const_cast<void*>(base), dims, str, box, es, CU_TENSOR_MAP_INTERLEAVE_NONE,
      CU_TENSOR_MAP_SWIZZLE_128B, CU_TENSOR_MAP_L2_PROMOTION_L2_128B, CU_TENSOR_MAP_FLOAT_OOB_FILL_NONE);
}

}

extern "C" void kernel_launch(void* const* d_in, const int* in_sizes, int n_in, void* d_out, int out_size) {
  (void)in_sizes; (void)n_in; (void)out_size;
  void* fn = nullptr;
  cudaDriverEntryPointQueryResult q;
  cudaGetDriverEntryPoint("cuTensorMapEncodeTiled", &fn, cudaEnableDefault, &q);
  EncodeFn enc = (EncodeFn)fn;
  void* op = nullptr;
  cudaGetSymbolAddress(&op, g_o);
  Maps M;
  make_map3(enc, &M.kv, d_in[1], DM, 3, DM, 64, 64, 1);
  make_map(enc, &M.wq, d_in[1], 3 * DM, DM, 64, 64, true);
  make_map(enc, &M.w1a, d_in[4], FF, DM, 64, 64, true);
  make_map(enc, &M.w3a, d_in[5], FF, DM, 64, 64, true);
  make_map(enc, &M.w1b, d_in[4], FF, DM, 32, 64, true);
  make_map(enc, &M.w3b, d_in[5], FF, DM, 32, 64, true);
  make_map(enc, &M.w2a, d_in[6], DM, FF, 64, 64, true);
  make_map(enc, &M.w2b, d_in[6], DM, FF, 64, 32, true);
  make_map(enc, &M.w2c, d_in[6], DM, FF, 32, 64, ORD == 2 || D64 ? 2 : 1);
  make_map(enc, &M.w2d, d_in[6], DM, FF, 32, 32, ORD == 2 || D64 ? 2 : 1);
  make_map(enc, &M.woa, d_in[2], DM, DM, 64, 64, true);
  make_map(enc, &M.wob, d_in[2], DM, DM, 32, 64, true);
  make_map(enc, &M.o, op, DM, SEQ, 64, 128 - OMIN * 8, true);
  make_map(enc, &M.ost, op, DM, SEQ, 56, 64, false);
  cudaFuncSetAttribute(fused_kernel, cudaFuncAttributeMaxDynamicSharedMemorySize, (int)SMEM_BYTES);
  Ptrs P;
  P.x = (const __nv_bfloat16*)d_in[0]; P.wo = (const __nv_bfloat16*)d_in[2];
  P.out = (__nv_bfloat16*)d_out;
  P.wqkv = (const __nv_bfloat16*)d_in[1];
  P.w1 = (const __nv_bfloat16*)d_in[4]; P.w3 = (const __nv_bfloat16*)d_in[5]; P.w2 = (const __nv_bfloat16*)d_in[6];
  fused_kernel<<<128, 384, SMEM_BYTES>>>(P, M);
}
```
